```python
import torch

def _softmax(x, axis=-1):
    return torch.softmax(x, dim=axis)
def _gelu(x):
    return torch.nn.functional.gelu(x, approximate="tanh")
def _silu(x):
    return torch.nn.functional.silu(x)
def _sigmoid(x):
    return torch.sigmoid(x)
def _layernorm(x, axis=-1, eps=1e-5):
    m = x.mean(dim=axis, keepdim=True)
    v = x.var(dim=axis, keepdim=True, unbiased=False)
    return (x - m) / torch.sqrt(v + eps)
def _scatter_add(tgt, idx, src, axis=0):
    return tgt.clone().index_add_(axis, idx, src)
def _segment_sum(src, seg, n):
    out = torch.zeros((n,) + src.shape[1:], dtype=src.dtype)
    return out.index_add_(0, seg, src)
def _pad(x, pw):
    flat = tuple(v for pair in reversed(pw) for v in pair)
    return torch.nn.functional.pad(x, flat)

kernel_name = 'standalone__mixer_channel_mlp__prompt'

def setup_inputs():

    _w = (lambda a: (lambda t: t.to(torch.bfloat16) if t.is_floating_point() else t)(torch.as_tensor(a)))
    B, S, D, F = 1, 2048, 512, 1792
    return {
        "x": _w((lambda *s: torch.randn(*s, dtype=torch.bfloat16) * 0.05)(B, S, D)),
        "w1": _w((lambda *s: torch.randn(*s, dtype=torch.bfloat16) * 0.8)(D, F) * (D ** -0.5)),
        "b1": _w((lambda *s: torch.randn(*s, dtype=torch.bfloat16) * 0.4)(F)),
        "w2": _w((lambda *s: torch.randn(*s, dtype=torch.bfloat16) * 0.05)(F, D) * (F ** -0.5)),
        "b2": _w((lambda *s: torch.randn(*s, dtype=torch.bfloat16) * 0.05)(D)),
    }

def reference(x, w1, b1, w2, b2):
    y = _layernorm(x, axis=-1)
    h = _gelu(torch.einsum("bsd,df->bsf", y, w1) + b1)
    return torch.einsum("bsf,fd->bsd", h, w2) + b2
```

```cpp
#include <cuda_runtime.h>
#include <cuda_bf16.h>
#include <cuda.h>
#include <stdint.h>

namespace {

constexpr int S_TOK = 2048, D_MOD = 512, F_HID = 1792;
constexpr int BM = 128, NSPLIT = 8, BF = F_HID / NSPLIT;
constexpr int BN2 = D_MOD / NSPLIT;
constexpr int NMB = S_TOK / BM;
constexpr int STAGE_BYTES = 28672;
constexpr int Y_BYTES = BM * D_MOD * 2;
constexpr int NRING = 3;
constexpr int OFF_RING = Y_BYTES;
constexpr int OFF_BAR = OFF_RING + NRING * STAGE_BYTES;
constexpr int OFF_RSTD = OFF_BAR + 512;
constexpr int OFF_B1 = OFF_RSTD + 512;
constexpr int OFF_B2 = OFF_B1 + 512;
constexpr int SMEM_TOTAL = OFF_B2 + 128;
constexpr int NTHREADS = 384;

__device__ uint4 g_part[(size_t)NMB * NSPLIT * NSPLIT * 2 * 4 * 128];
__device__ unsigned int g_flag[NMB * NSPLIT * NSPLIT];

__device__ __forceinline__ uint32_t smem_u32(const void* p) { return (uint32_t)__cvta_generic_to_shared(p); }
__device__ __forceinline__ void mbar_init(uint32_t bar, uint32_t cnt) {
  asm volatile("mbarrier.init.shared::cta.b64 [%0], %1;" :: "r"(bar), "r"(cnt) : "memory");
}
__device__ __forceinline__ void mbar_expect_tx(uint32_t bar, uint32_t bytes) {
  asm volatile("mbarrier.arrive.expect_tx.shared::cta.b64 _, [%0], %1;" :: "r"(bar), "r"(bytes) : "memory");
}
__device__ __forceinline__ void mbar_arrive(uint32_t bar) {
  asm volatile("mbarrier.arrive.shared::cta.b64 _, [%0];" :: "r"(bar) : "memory");
}
__device__ __forceinline__ void mbar_wait(uint32_t bar, uint32_t parity) {
  uint32_t done = 0; uint32_t it = 0;
  while (true) {
    asm volatile("{\n.reg .pred p;\nmbarrier.try_wait.parity.shared::cta.b64 p, [%1], %2;\nselp.u32 %0, 1, 0, p;\n}"
                 : "=r"(done) : "r"(bar), "r"(parity) : "memory");
    if (done) break;
    if (++it > (1u << 22)) asm volatile("trap;");
  }
}
__device__ __forceinline__ void tma_load_3d(uint32_t dst, const CUtensorMap* tm, int c0, int c1, int c2, uint32_t bar) {
  asm volatile("cp.async.bulk.tensor.3d.shared::cluster.global.mbarrier::complete_tx::bytes [%0], [%1, {%3, %4, %5}], [%2];"
               :: "r"(dst), "l"(tm), "r"(bar), "r"(c0), "r"(c1), "r"(c2) : "memory");
}
__device__ __forceinline__ void tma_load_2d(uint32_t dst, const CUtensorMap* tm, int c0, int c1, uint32_t bar) {
  asm volatile("cp.async.bulk.tensor.2d.shared::cluster.global.mbarrier::complete_tx::bytes [%0], [%1, {%3, %4}], [%2];"
               :: "r"(dst), "l"(tm), "r"(bar), "r"(c0), "r"(c1) : "memory");
}
__device__ __forceinline__ void tma_prefetch_3d(const CUtensorMap* tm, int c0, int c1, int c2) {
  asm volatile("cp.async.bulk.prefetch.tensor.3d.L2.global.tile [%0, {%1, %2, %3}];" :: "l"(tm), "r"(c0), "r"(c1), "r"(c2) : "memory");
}
__device__ __forceinline__ void tma_prefetch_2d(const CUtensorMap* tm, int c0, int c1) {
  asm volatile("cp.async.bulk.prefetch.tensor.2d.L2.global.tile [%0, {%1, %2}];" :: "l"(tm), "r"(c0), "r"(c1) : "memory");
}
__device__ __forceinline__ void wg_fence() { asm volatile("wgmma.fence.sync.aligned;" ::: "memory"); }
__device__ __forceinline__ void wg_commit() { asm volatile("wgmma.commit_group.sync.aligned;" ::: "memory"); }
template <int N> __device__ __forceinline__ void wg_wait() { asm volatile("wgmma.wait_group.sync.aligned %0;" :: "n"(N) : "memory"); }
template <int N> __device__ __forceinline__ void reg_fence(float (&d)[N]) {
#pragma unroll
  for (int i = 0; i < N; i++) asm volatile("" : "+f"(d[i]) :: "memory");
}
__device__ __forceinline__ uint64_t make_desc(uint32_t addr, uint32_t lbo, uint32_t sbo, uint32_t lt) {
  return (uint64_t)((addr & 0x3FFFF) >> 4) | ((uint64_t)(lbo >> 4) << 16) | ((uint64_t)(sbo >> 4) << 32) | ((uint64_t)lt << 62);
}
__device__ __forceinline__ uint32_t pack_bf16(float lo, float hi) {
  uint32_t r; asm("cvt.rn.bf16x2.f32 %0, %1, %2;" : "=r"(r) : "f"(hi), "f"(lo)); return r;
}
__device__ __forceinline__ float bf_lo(uint32_t v) { return __uint_as_float(v << 16); }
__device__ __forceinline__ float bf_hi(uint32_t v) { return __uint_as_float(v & 0xffff0000u); }
__device__ __forceinline__ float bf16r(float v) { return __bfloat162float(__float2bfloat16_rn(v)); }
__device__ __forceinline__ uint32_t hadd2_bf(uint32_t a, uint32_t b) {
  uint32_t r; asm("add.rn.bf16x2 %0, %1, %2;" : "=r"(r) : "r"(a), "r"(b)); return r;
}
__device__ __forceinline__ uint32_t hsub2_bf(uint32_t a, uint32_t b) {
  uint32_t r; asm("sub.rn.bf16x2 %0, %1, %2;" : "=r"(r) : "r"(a), "r"(b)); return r;
}
__device__ __forceinline__ float gelu_tanh(float u) {
  float inner = u * fmaf(0.035677408136300125f, u * u, 0.7978845608028654f);
  float th; asm("tanh.approx.f32 %0, %1;" : "=f"(th) : "f"(inner));
  float hu = 0.5f * u;
  return fmaf(hu, th, hu);
}

__device__ __forceinline__ void wgmma_ss_n224(float (&d)[112], uint64_t descA, uint64_t descB, int scaleD) {
  asm volatile("{\n.reg .pred p;\nsetp.ne.b32 p, %114, 0;\n"
    "wgmma.mma_async.sync.aligned.m64n224k16.f32.bf16.bf16 {%0, %1, %2, %3, %4, %5, %6, %7, %8, %9, %10, %11, %12, %13, %14, %15, %16, %17, %18, %19, %20, %21, %22, %23, %24, %25, %26, %27, %28, %29, %30, %31, %32, %33, %34, %35, %36, %37, %38, %39, %40, %41, %42, %43, %44, %45, %46, %47, %48, %49, %50, %51, %52, %53, %54, %55, %56, %57, %58, %59, %60, %61, %62, %63, %64, %65, %66, %67, %68, %69, %70, %71, %72, %73, %74, %75, %76, %77, %78, %79, %80, %81, %82, %83, %84, %85, %86, %87, %88, %89, %90, %91, %92, %93, %94, %95, %96, %97, %98, %99, %100, %101, %102, %103, %104, %105, %106, %107, %108, %109, %110, %111}, %112, %113, p, 1, 1, 0, 1;\n}\n"
    : "+f"(d[0]), "+f"(d[1]), "+f"(d[2]), "+f"(d[3]), "+f"(d[4]), "+f"(d[5]), "+f"(d[6]), "+f"(d[7]), "+f"(d[8]), "+f"(d[9]), "+f"(d[10]), "+f"(d[11]), "+f"(d[12]), "+f"(d[13]), "+f"(d[14]), "+f"(d[15]), "+f"(d[16]), "+f"(d[17]), "+f"(d[18]), "+f"(d[19]), "+f"(d[20]), "+f"(d[21]), "+f"(d[22]), "+f"(d[23]), "+f"(d[24]), "+f"(d[25]), "+f"(d[26]), "+f"(d[27]), "+f"(d[28]), "+f"(d[29]), "+f"(d[30]), "+f"(d[31]), "+f"(d[32]), "+f"(d[33]), "+f"(d[34]), "+f"(d[35]), "+f"(d[36]), "+f"(d[37]), "+f"(d[38]), "+f"(d[39]), "+f"(d[40]), "+f"(d[41]), "+f"(d[42]), "+f"(d[43]), "+f"(d[44]), "+f"(d[45]), "+f"(d[46]), "+f"(d[47]), "+f"(d[48]), "+f"(d[49]), "+f"(d[50]), "+f"(d[51]), "+f"(d[52]), "+f"(d[53]), "+f"(d[54]), "+f"(d[55]), "+f"(d[56]), "+f"(d[57]), "+f"(d[58]), "+f"(d[59]), "+f"(d[60]), "+f"(d[61]), "+f"(d[62]), "+f"(d[63]), "+f"(d[64]), "+f"(d[65]), "+f"(d[66]), "+f"(d[67]), "+f"(d[68]), "+f"(d[69]), "+f"(d[70]), "+f"(d[71]), "+f"(d[72]), "+f"(d[73]), "+f"(d[74]), "+f"(d[75]), "+f"(d[76]), "+f"(d[77]), "+f"(d[78]), "+f"(d[79]), "+f"(d[80]), "+f"(d[81]), "+f"(d[82]), "+f"(d[83]), "+f"(d[84]), "+f"(d[85]), "+f"(d[86]), "+f"(d[87]), "+f"(d[88]), "+f"(d[89]), "+f"(d[90]), "+f"(d[91]), "+f"(d[92]), "+f"(d[93]), "+f"(d[94]), "+f"(d[95]), "+f"(d[96]), "+f"(d[97]), "+f"(d[98]), "+f"(d[99]), "+f"(d[100]), "+f"(d[101]), "+f"(d[102]), "+f"(d[103]), "+f"(d[104]), "+f"(d[105]), "+f"(d[106]), "+f"(d[107]), "+f"(d[108]), "+f"(d[109]), "+f"(d[110]), "+f"(d[111])
    : "l"(descA), "l"(descB), "r"(scaleD));
}

__device__ __forceinline__ void wgmma_rs_n64(float (&d)[32], const uint32_t (&a)[4], uint64_t descB, int scaleD) {
  asm volatile("{\n.reg .pred p;\nsetp.ne.b32 p, %37, 0;\n"
    "wgmma.mma_async.sync.aligned.m64n64k16.f32.bf16.bf16 {%0, %1, %2, %3, %4, %5, %6, %7, %8, %9, %10, %11, %12, %13, %14, %15, %16, %17, %18, %19, %20, %21, %22, %23, %24, %25, %26, %27, %28, %29, %30, %31}, {%32, %33, %34, %35}, %36, p, 1, 1, 1;\n}\n"
    : "+f"(d[0]), "+f"(d[1]), "+f"(d[2]), "+f"(d[3]), "+f"(d[4]), "+f"(d[5]), "+f"(d[6]), "+f"(d[7]), "+f"(d[8]), "+f"(d[9]), "+f"(d[10]), "+f"(d[11]), "+f"(d[12]), "+f"(d[13]), "+f"(d[14]), "+f"(d[15]), "+f"(d[16]), "+f"(d[17]), "+f"(d[18]), "+f"(d[19]), "+f"(d[20]), "+f"(d[21]), "+f"(d[22]), "+f"(d[23]), "+f"(d[24]), "+f"(d[25]), "+f"(d[26]), "+f"(d[27]), "+f"(d[28]), "+f"(d[29]), "+f"(d[30]), "+f"(d[31])
    : "r"(a[0]), "r"(a[1]), "r"(a[2]), "r"(a[3]), "l"(descB), "r"(scaleD));
}


__global__ void __launch_bounds__(NTHREADS, 1)
fused_mlp_kernel(const __grid_constant__ CUtensorMap tm_w1, const __grid_constant__ CUtensorMap tm_w2,
                 const __nv_bfloat16* __restrict__ x, const __nv_bfloat16* __restrict__ b1,
                 const __nv_bfloat16* __restrict__ b2, __nv_bfloat16* __restrict__ out)
{
  extern __shared__ __align__(1024) unsigned char smem[];
  const uint32_t sbase = smem_u32(smem);
  const uint32_t bar_full = sbase + OFF_BAR;
  const uint32_t bar_cons = sbase + OFF_BAR + 128;
  const int tid = threadIdx.x, warp = tid >> 5, lane = tid & 31;
  const int mb = blockIdx.x >> 3, j = blockIdx.x & 7;

  if (warp == 8) {
    if (lane == 0) {
      for (int i = 0; i < 16; i++) { mbar_init(bar_full + 8 * i, 1); mbar_init(bar_cons + 8 * i, 2); }
      asm volatile("fence.mbarrier_init.release.cluster;" ::: "memory");
      asm volatile("fence.proxy.async.shared::cta;" ::: "memory");
      for (int i = 0; i < NRING; i++) {
        mbar_expect_tx(bar_full + 8 * i, STAGE_BYTES);
        tma_load_3d(sbase + OFF_RING + i * STAGE_BYTES, &tm_w1, 0, i * 64, j * 7, bar_full + 8 * i);
      }
      if (mb < 8) { if (mb >= NRING) tma_prefetch_3d(&tm_w1, 0, mb * 64, j * 7); }
      else tma_prefetch_2d(&tm_w2, (mb - 8) * 64, j * BF);
    }
  }
  __syncthreads();

  if (warp >= 8) {
    asm volatile("setmaxnreg.dec.sync.aligned.u32 40;");
    if (warp == 8 && lane == 0) {
      for (int i = NRING; i < 16; i++) {
        uint32_t dst;
        if (i < 11)      { mbar_wait(bar_cons + 8 * (i - NRING), 0); dst = sbase + OFF_RING + (i % NRING) * STAGE_BYTES; }
        else if (i < 15) { if (i == 11) mbar_wait(bar_cons + 8 * 7, 0); dst = sbase + (i - 11) * STAGE_BYTES; }
        else             { mbar_wait(bar_cons + 8 * 8, 0); dst = sbase + OFF_RING + (8 % NRING) * STAGE_BYTES; }
        mbar_expect_tx(bar_full + 8 * i, STAGE_BYTES);
        if (i < 8) tma_load_3d(dst, &tm_w1, 0, i * 64, j * 7, bar_full + 8 * i);
        else {
          int sl = (j + 1 + (i - 8)) & 7;
          tma_load_2d(dst, &tm_w2, sl * BN2, j * BF, bar_full + 8 * i);
        }
      }
    }
  } else {
    asm volatile("setmaxnreg.inc.sync.aligned.u32 232;");
    const int wg = warp >> 2;
    const int q = lane & 3, g = lane >> 2;
    float* rstd_s = reinterpret_cast<float*>(smem + OFF_RSTD);
    if (tid < BF / 2) reinterpret_cast<uint32_t*>(smem + OFF_B1)[tid] = reinterpret_cast<const uint32_t*>(b1 + j * BF)[tid];
    else if (tid >= 128 && tid < 128 + BN2 / 2) reinterpret_cast<uint32_t*>(smem + OFF_B2)[tid - 128] = reinterpret_cast<const uint32_t*>(b2 + j * BN2)[tid - 128];

    {
      const uint4* xg = reinterpret_cast<const uint4*>(x + (size_t)mb * BM * D_MOD);
      uint4 xv[16][2];
#pragma unroll
      for (int r = 0; r < 16; r++) {
        int row = (r >> 3) * 64 + warp * 8 + (r & 7);
        xv[r][0] = __ldg(xg + row * 64 + lane);
        xv[r][1] = __ldg(xg + row * 64 + 32 + lane);
      }
#pragma unroll
      for (int r = 0; r < 16; r++) {
        int row = (r >> 3) * 64 + warp * 8 + (r & 7);
        uint32_t w[8] = {xv[r][0].x, xv[r][0].y, xv[r][0].z, xv[r][0].w, xv[r][1].x, xv[r][1].y, xv[r][1].z, xv[r][1].w};
        float s = 0.f;
#pragma unroll
        for (int e = 0; e < 8; e++) s += bf_lo(w[e]) + bf_hi(w[e]);
#pragma unroll
        for (int o = 16; o > 0; o >>= 1) s += __shfl_xor_sync(0xffffffffu, s, o);
        const float mean = s * (1.0f / D_MOD);
        const uint32_t m2 = pack_bf16(mean, mean);
        uint4 d0, d1;
        d0.x = hsub2_bf(w[0], m2); d0.y = hsub2_bf(w[1], m2); d0.z = hsub2_bf(w[2], m2); d0.w = hsub2_bf(w[3], m2);
        d1.x = hsub2_bf(w[4], m2); d1.y = hsub2_bf(w[5], m2); d1.z = hsub2_bf(w[6], m2); d1.w = hsub2_bf(w[7], m2);
        const uint32_t a0 = (uint32_t)((lane >> 3) * 16384 + row * 128 + (((lane & 7) ^ (row & 7)) << 4));
        *reinterpret_cast<uint4*>(smem + a0) = d0;
        *reinterpret_cast<uint4*>(smem + a0 + 4 * 16384) = d1;
        float v = 0.f;
#pragma unroll
        for (int e = 0; e < 8; e++) { float a = bf_lo(w[e]) - mean, b = bf_hi(w[e]) - mean; v = fmaf(a, a, v); v = fmaf(b, b, v); }
#pragma unroll
        for (int o = 16; o > 0; o >>= 1) v += __shfl_xor_sync(0xffffffffu, v, o);
        if (lane == 0) {
          float vb = bf16r(v * (1.0f / D_MOD));
          float sd = bf16r(sqrtf(bf16r(vb + 1e-5f)));
          rstd_s[row] = 1.0f / sd;
        }
      }
    }
    asm volatile("fence.proxy.async.shared::cta;" ::: "memory");
    asm volatile("bar.sync 1, 256;" ::: "memory");

    uint32_t h[14][4];
    {
      float acc[112];
#pragma unroll
      for (int kb = 0; kb < 8; kb++) {
        mbar_wait(bar_full + 8 * kb, 0);
        wg_fence();
        const uint32_t abase = sbase + kb * 16384 + wg * 8192;
        const uint32_t bbase = sbase + OFF_RING + (kb % NRING) * STAGE_BYTES;
#pragma unroll
        for (int kk = 0; kk < 4; kk++) {
          wgmma_ss_n224(acc, make_desc(abase + kk * 32, 16, 1024, 1), make_desc(bbase + kk * 1024, 4096, 512, 2), (kb | kk) != 0);
        }
        wg_commit();
        if (kb > 0) { wg_wait<1>(); if ((tid & 127) == 0) mbar_arrive(bar_cons + 8 * (kb - 1)); }
      }
      wg_wait<0>();
      reg_fence(acc);
      if ((tid & 127) == 0) mbar_arrive(bar_cons + 8 * 7);

      const int row0 = wg * 64 + (warp & 3) * 16 + g;
      const float r0 = rstd_s[row0], r1 = rstd_s[row0 + 8];
      const uint32_t* b1s = reinterpret_cast<const uint32_t*>(smem + OFF_B1);
#pragma unroll
      for (int i = 0; i < 28; i++) {
        const uint32_t bb = b1s[i * 4 + q];
        uint32_t p0 = hadd2_bf(pack_bf16(acc[4 * i] * r0, acc[4 * i + 1] * r0), bb);
        uint32_t p1 = hadd2_bf(pack_bf16(acc[4 * i + 2] * r1, acc[4 * i + 3] * r1), bb);
        h[i >> 1][(i & 1) * 2 + 0] = pack_bf16(gelu_tanh(bf_lo(p0)), gelu_tanh(bf_hi(p0)));
        h[i >> 1][(i & 1) * 2 + 1] = pack_bf16(gelu_tanh(bf_lo(p1)), gelu_tanh(bf_hi(p1)));
      }
    }

    float acc2[2][32];
    float sum[32];
#pragma unroll
    for (int i = 0; i < 32; i++) sum[i] = 0.f;
    const int t128 = tid & 127;
    auto recv = [&](int n) {
      const int src = (j + 7 - n) & 7;
      unsigned int* fl = &g_flag[(mb * NSPLIT + j) * NSPLIT + src];
      if (lane == 0) {
        uint32_t it = 0, v;
        while (true) {
          asm volatile("ld.acquire.gpu.global.u32 %0, [%1];" : "=r"(v) : "l"(fl) : "memory");
          if (v >= 8) break;
          if (++it > (1u << 22)) asm volatile("trap;");
        }
      }
      __syncwarp();
      const uint4* p = &g_part[((size_t)((mb * NSPLIT + j) * NSPLIT + src) * 2 + wg) * 512 + t128];
#pragma unroll
      for (int c = 0; c < 4; c++) {
        uint4 v = __ldcg(p + c * 128);
        sum[c * 8 + 0] += bf_lo(v.x); sum[c * 8 + 1] += bf_hi(v.x);
        sum[c * 8 + 2] += bf_lo(v.y); sum[c * 8 + 3] += bf_hi(v.y);
        sum[c * 8 + 4] += bf_lo(v.z); sum[c * 8 + 5] += bf_hi(v.z);
        sum[c * 8 + 6] += bf_lo(v.w); sum[c * 8 + 7] += bf_hi(v.w);
      }
    };
#pragma unroll
    for (int i = 0; i < 8; i++) {
      mbar_wait(bar_full + 8 * (8 + i), 0);
      uint32_t bbase;
      if (i < 3) bbase = sbase + OFF_RING + ((8 + i) % NRING) * STAGE_BYTES;
      else if (i < 7) bbase = sbase + (i - 3) * STAGE_BYTES;
      else bbase = sbase + OFF_RING + (8 % NRING) * STAGE_BYTES;
      wg_fence();
#pragma unroll
      for (int ks = 0; ks < 14; ks++) {
        wgmma_rs_n64(acc2[i & 1], h[ks], make_desc(bbase + ks * 2048, 16, 1024, 1), ks != 0);
      }
      wg_commit();
      if (i > 0) {
        wg_wait<1>();
        reg_fence(acc2[(i - 1) & 1]);
        if (i == 1 && t128 == 0) mbar_arrive(bar_cons + 8 * 8);
        const int dest = (j + i) & 7;
        uint4* p = &g_part[((size_t)((mb * NSPLIT + dest) * NSPLIT + j) * 2 + wg) * 512 + t128];
        const float* a = acc2[(i - 1) & 1];
#pragma unroll
        for (int c = 0; c < 4; c++) {
          uint4 v;
          v.x = pack_bf16(a[c * 8 + 0], a[c * 8 + 1]); v.y = pack_bf16(a[c * 8 + 2], a[c * 8 + 3]);
          v.z = pack_bf16(a[c * 8 + 4], a[c * 8 + 5]); v.w = pack_bf16(a[c * 8 + 6], a[c * 8 + 7]);
          __stcg(p + c * 128, v);
        }
        __syncwarp();
        if (lane == 0) {
          __threadfence();
          asm volatile("red.release.gpu.global.add.u32 [%0], 1;" :: "l"(&g_flag[(mb * NSPLIT + dest) * NSPLIT + j]) : "memory");
        }
      }
      if (i >= 2) recv(i - 2);
    }
    wg_wait<0>();
    reg_fence(acc2[1]);
    recv(6);
    asm volatile("bar.sync 1, 256;" ::: "memory");
    if (tid < NSPLIT) g_flag[(mb * NSPLIT + j) * NSPLIT + tid] = 0;

    {
      const uint32_t* b2s = reinterpret_cast<const uint32_t*>(smem + OFF_B2);
      const int row0 = mb * BM + wg * 64 + (warp & 3) * 16 + g;
      uint32_t* o0 = reinterpret_cast<uint32_t*>(out + (size_t)row0 * D_MOD + j * BN2) + q;
      uint32_t* o1 = o0 + 8 * D_MOD / 2;
#pragma unroll
      for (int i = 0; i < 8; i++) {
        const uint32_t bb = b2s[i * 4 + q];
        o0[i * 4] = hadd2_bf(pack_bf16(acc2[1][4 * i] + sum[4 * i], acc2[1][4 * i + 1] + sum[4 * i + 1]), bb);
        o1[i * 4] = hadd2_bf(pack_bf16(acc2[1][4 * i + 2] + sum[4 * i + 2], acc2[1][4 * i + 3] + sum[4 * i + 3]), bb);
      }
    }
  }
}

typedef CUresult (*EncodeFn)(CUtensorMap*, CUtensorMapDataType, cuuint32_t, void*, const cuuint64_t*, const cuuint64_t*,
                             const cuuint32_t*, const cuuint32_t*, CUtensorMapInterleave, CUtensorMapSwizzle,
                             CUtensorMapL2promotion, CUtensorMapFloatOOBfill);

}

extern "C" void kernel_launch(void* const* d_in, const int* in_sizes, int n_in, void* d_out, int out_size) {
  (void)in_sizes; (void)n_in; (void)out_size;
  static CUtensorMap tm_w1, tm_w2;
  static const void* cached_w1 = nullptr; static const void* cached_w2 = nullptr;
  const void* w1 = d_in[1]; const void* w2 = d_in[3];
  if (cached_w1 != w1 || cached_w2 != w2) {
    void* fn = nullptr; cudaDriverEntryPointQueryResult st;
    cudaGetDriverEntryPoint("cuTensorMapEncodeTiled", &fn, cudaEnableDefault, &st);
    EncodeFn enc = (EncodeFn)fn;
    {
      cuuint64_t dims[3] = {32, (cuuint64_t)D_MOD, (cuuint64_t)(F_HID / 32)};
      cuuint64_t strides[2] = {(cuuint64_t)F_HID * 2, 64};
      cuuint32_t box[3] = {32, 64, 7};
      cuuint32_t es[3] = {1, 1, 1};
      enc(&tm_w1, CU_TENSOR_MAP_DATA_TYPE_BFLOAT16, 3, const_cast<void*>(w1), dims, strides, box, es,
          CU_TENSOR_MAP_INTERLEAVE_NONE, CU_TENSOR_MAP_SWIZZLE_64B, CU_TENSOR_MAP_L2_PROMOTION_L2_128B, CU_TENSOR_MAP_FLOAT_OOB_FILL_NONE);
    }
    {
      cuuint64_t dims[2] = {(cuuint64_t)D_MOD, (cuuint64_t)F_HID};
      cuuint64_t strides[1] = {(cuuint64_t)D_MOD * 2};
      cuuint32_t box[2] = {64, 224};
      cuuint32_t es[2] = {1, 1};
      enc(&tm_w2, CU_TENSOR_MAP_DATA_TYPE_BFLOAT16, 2, const_cast<void*>(w2), dims, strides, box, es,
          CU_TENSOR_MAP_INTERLEAVE_NONE, CU_TENSOR_MAP_SWIZZLE_128B, CU_TENSOR_MAP_L2_PROMOTION_L2_128B, CU_TENSOR_MAP_FLOAT_OOB_FILL_NONE);
    }
    cudaFuncSetAttribute(fused_mlp_kernel, cudaFuncAttributeMaxDynamicSharedMemorySize, SMEM_TOTAL);
    cached_w1 = w1; cached_w2 = w2;
  }
  fused_mlp_kernel<<<NMB * NSPLIT, NTHREADS, SMEM_TOTAL>>>(tm_w1, tm_w2,
      (const __nv_bfloat16*)d_in[0], (const __nv_bfloat16*)d_in[2], (const __nv_bfloat16*)d_in[4], (__nv_bfloat16*)d_out);
}
```

```cpp
#include <cuda_runtime.h>
#include <cuda_bf16.h>
#include <cuda.h>
#include <stdint.h>

namespace {

constexpr int S_TOK = 2048, D_MOD = 512, F_HID = 1792;
constexpr int BM = 128, NSPLIT = 8, BF = F_HID / NSPLIT;
constexpr int BN2 = D_MOD / NSPLIT;
constexpr int NMB = S_TOK / BM;
constexpr int STAGE_BYTES = 28672;
constexpr int Y_BYTES = BM * D_MOD * 2;
constexpr int NRING = 3;
constexpr int OFF_RING = Y_BYTES;
constexpr int OFF_BAR = OFF_RING + NRING * STAGE_BYTES;
constexpr int OFF_PSLOT = 2 * STAGE_BYTES;
constexpr int PSLOT_BYTES = 16384;
constexpr int OFF_RSTD = OFF_BAR + 512;
constexpr int OFF_B1 = OFF_RSTD + 512;
constexpr int OFF_B2 = OFF_B1 + 512;
constexpr int SMEM_TOTAL = OFF_B2 + 128;
constexpr int NTHREADS = 384;

__device__ uint4 g_part[(size_t)NMB * NSPLIT * NSPLIT * 2 * 4 * 128];
__device__ unsigned int g_flag[NMB * NSPLIT * NSPLIT];

#define TS(role, idx) do {} while (0)
#define TSC(idx) do {} while (0)

__device__ __forceinline__ uint32_t smem_u32(const void* p) { return (uint32_t)__cvta_generic_to_shared(p); }
__device__ __forceinline__ void mbar_init(uint32_t bar, uint32_t cnt) {
  asm volatile("mbarrier.init.shared::cta.b64 [%0], %1;" :: "r"(bar), "r"(cnt) : "memory");
}
__device__ __forceinline__ void mbar_expect_tx(uint32_t bar, uint32_t bytes) {
  asm volatile("mbarrier.arrive.expect_tx.shared::cta.b64 _, [%0], %1;" :: "r"(bar), "r"(bytes) : "memory");
}
__device__ __forceinline__ void mbar_arrive(uint32_t bar) {
  asm volatile("mbarrier.arrive.shared::cta.b64 _, [%0];" :: "r"(bar) : "memory");
}
__device__ __forceinline__ void mbar_wait(uint32_t bar, uint32_t parity) {
  uint32_t done = 0; uint32_t it = 0;
  while (true) {
    asm volatile("{\n.reg .pred p;\nmbarrier.try_wait.parity.shared::cta.b64 p, [%1], %2;\nselp.u32 %0, 1, 0, p;\n}"
                 : "=r"(done) : "r"(bar), "r"(parity) : "memory");
    if (done) break;
    if (++it > (1u << 22)) asm volatile("trap;");
  }
}
__device__ __forceinline__ void tma_load_3d(uint32_t dst, const CUtensorMap* tm, int c0, int c1, int c2, uint32_t bar) {
  asm volatile("cp.async.bulk.tensor.3d.shared::cluster.global.mbarrier::complete_tx::bytes [%0], [%1, {%3, %4, %5}], [%2];"
               :: "r"(dst), "l"(tm), "r"(bar), "r"(c0), "r"(c1), "r"(c2) : "memory");
}
__device__ __forceinline__ void tma_load_2d(uint32_t dst, const CUtensorMap* tm, int c0, int c1, uint32_t bar) {
  asm volatile("cp.async.bulk.tensor.2d.shared::cluster.global.mbarrier::complete_tx::bytes [%0], [%1, {%3, %4}], [%2];"
               :: "r"(dst), "l"(tm), "r"(bar), "r"(c0), "r"(c1) : "memory");
}
__device__ __forceinline__ void tma_prefetch_3d(const CUtensorMap* tm, int c0, int c1, int c2) {
  asm volatile("cp.async.bulk.prefetch.tensor.3d.L2.global.tile [%0, {%1, %2, %3}];" :: "l"(tm), "r"(c0), "r"(c1), "r"(c2) : "memory");
}
__device__ __forceinline__ void tma_prefetch_2d(const CUtensorMap* tm, int c0, int c1) {
  asm volatile("cp.async.bulk.prefetch.tensor.2d.L2.global.tile [%0, {%1, %2}];" :: "l"(tm), "r"(c0), "r"(c1) : "memory");
}
__device__ __forceinline__ void wg_fence() { asm volatile("wgmma.fence.sync.aligned;" ::: "memory"); }
__device__ __forceinline__ void wg_commit() { asm volatile("wgmma.commit_group.sync.aligned;" ::: "memory"); }
template <int N> __device__ __forceinline__ void wg_wait() { asm volatile("wgmma.wait_group.sync.aligned %0;" :: "n"(N) : "memory"); }
template <int N> __device__ __forceinline__ void reg_fence(float (&d)[N]) {
#pragma unroll
  for (int i = 0; i < N; i++) asm volatile("" : "+f"(d[i]) :: "memory");
}
__device__ __forceinline__ uint64_t make_desc(uint32_t addr, uint32_t lbo, uint32_t sbo, uint32_t lt) {
  return (uint64_t)((addr & 0x3FFFF) >> 4) | ((uint64_t)(lbo >> 4) << 16) | ((uint64_t)(sbo >> 4) << 32) | ((uint64_t)lt << 62);
}
__device__ __forceinline__ uint32_t pack_bf16(float lo, float hi) {
  uint32_t r; asm("cvt.rn.bf16x2.f32 %0, %1, %2;" : "=r"(r) : "f"(hi), "f"(lo)); return r;
}
__device__ __forceinline__ float bf_lo(uint32_t v) { return __uint_as_float(v << 16); }
__device__ __forceinline__ float bf_hi(uint32_t v) { return __uint_as_float(v & 0xffff0000u); }
__device__ __forceinline__ float bf16r(float v) { return __bfloat162float(__float2bfloat16_rn(v)); }
__device__ __forceinline__ uint32_t hadd2_bf(uint32_t a, uint32_t b) {
  uint32_t r; asm("add.rn.bf16x2 %0, %1, %2;" : "=r"(r) : "r"(a), "r"(b)); return r;
}
__device__ __forceinline__ uint32_t hsub2_bf(uint32_t a, uint32_t b) {
  uint32_t r; asm("sub.rn.bf16x2 %0, %1, %2;" : "=r"(r) : "r"(a), "r"(b)); return r;
}
__device__ __forceinline__ float gelu_tanh(float u) {
  float inner = u * fmaf(0.035677408136300125f, u * u, 0.7978845608028654f);
  float th; asm("tanh.approx.f32 %0, %1;" : "=f"(th) : "f"(inner));
  float hu = 0.5f * u;
  return fmaf(hu, th, hu);
}

__device__ __forceinline__ void wgmma_ss_n224(float (&d)[112], uint64_t descA, uint64_t descB, int scaleD) {
  asm volatile("{\n.reg .pred p;\nsetp.ne.b32 p, %114, 0;\n"
    "wgmma.mma_async.sync.aligned.m64n224k16.f32.bf16.bf16 {%0, %1, %2, %3, %4, %5, %6, %7, %8, %9, %10, %11, %12, %13, %14, %15, %16, %17, %18, %19, %20, %21, %22, %23, %24, %25, %26, %27, %28, %29, %30, %31, %32, %33, %34, %35, %36, %37, %38, %39, %40, %41, %42, %43, %44, %45, %46, %47, %48, %49, %50, %51, %52, %53, %54, %55, %56, %57, %58, %59, %60, %61, %62, %63, %64, %65, %66, %67, %68, %69, %70, %71, %72, %73, %74, %75, %76, %77, %78, %79, %80, %81, %82, %83, %84, %85, %86, %87, %88, %89, %90, %91, %92, %93, %94, %95, %96, %97, %98, %99, %100, %101, %102, %103, %104, %105, %106, %107, %108, %109, %110, %111}, %112, %113, p, 1, 1, 0, 1;\n}\n"
    : "+f"(d[0]), "+f"(d[1]), "+f"(d[2]), "+f"(d[3]), "+f"(d[4]), "+f"(d[5]), "+f"(d[6]), "+f"(d[7]), "+f"(d[8]), "+f"(d[9]), "+f"(d[10]), "+f"(d[11]), "+f"(d[12]), "+f"(d[13]), "+f"(d[14]), "+f"(d[15]), "+f"(d[16]), "+f"(d[17]), "+f"(d[18]), "+f"(d[19]), "+f"(d[20]), "+f"(d[21]), "+f"(d[22]), "+f"(d[23]), "+f"(d[24]), "+f"(d[25]), "+f"(d[26]), "+f"(d[27]), "+f"(d[28]), "+f"(d[29]), "+f"(d[30]), "+f"(d[31]), "+f"(d[32]), "+f"(d[33]), "+f"(d[34]), "+f"(d[35]), "+f"(d[36]), "+f"(d[37]), "+f"(d[38]), "+f"(d[39]), "+f"(d[40]), "+f"(d[41]), "+f"(d[42]), "+f"(d[43]), "+f"(d[44]), "+f"(d[45]), "+f"(d[46]), "+f"(d[47]), "+f"(d[48]), "+f"(d[49]), "+f"(d[50]), "+f"(d[51]), "+f"(d[52]), "+f"(d[53]), "+f"(d[54]), "+f"(d[55]), "+f"(d[56]), "+f"(d[57]), "+f"(d[58]), "+f"(d[59]), "+f"(d[60]), "+f"(d[61]), "+f"(d[62]), "+f"(d[63]), "+f"(d[64]), "+f"(d[65]), "+f"(d[66]), "+f"(d[67]), "+f"(d[68]), "+f"(d[69]), "+f"(d[70]), "+f"(d[71]), "+f"(d[72]), "+f"(d[73]), "+f"(d[74]), "+f"(d[75]), "+f"(d[76]), "+f"(d[77]), "+f"(d[78]), "+f"(d[79]), "+f"(d[80]), "+f"(d[81]), "+f"(d[82]), "+f"(d[83]), "+f"(d[84]), "+f"(d[85]), "+f"(d[86]), "+f"(d[87]), "+f"(d[88]), "+f"(d[89]), "+f"(d[90]), "+f"(d[91]), "+f"(d[92]), "+f"(d[93]), "+f"(d[94]), "+f"(d[95]), "+f"(d[96]), "+f"(d[97]), "+f"(d[98]), "+f"(d[99]), "+f"(d[100]), "+f"(d[101]), "+f"(d[102]), "+f"(d[103]), "+f"(d[104]), "+f"(d[105]), "+f"(d[106]), "+f"(d[107]), "+f"(d[108]), "+f"(d[109]), "+f"(d[110]), "+f"(d[111])
    : "l"(descA), "l"(descB), "r"(scaleD));
}

__device__ __forceinline__ void wgmma_rs_n64(float (&d)[32], const uint32_t (&a)[4], uint64_t descB, int scaleD) {
  asm volatile("{\n.reg .pred p;\nsetp.ne.b32 p, %37, 0;\n"
    "wgmma.mma_async.sync.aligned.m64n64k16.f32.bf16.bf16 {%0, %1, %2, %3, %4, %5, %6, %7, %8, %9, %10, %11, %12, %13, %14, %15, %16, %17, %18, %19, %20, %21, %22, %23, %24, %25, %26, %27, %28, %29, %30, %31}, {%32, %33, %34, %35}, %36, p, 1, 1, 1;\n}\n"
    : "+f"(d[0]), "+f"(d[1]), "+f"(d[2]), "+f"(d[3]), "+f"(d[4]), "+f"(d[5]), "+f"(d[6]), "+f"(d[7]), "+f"(d[8]), "+f"(d[9]), "+f"(d[10]), "+f"(d[11]), "+f"(d[12]), "+f"(d[13]), "+f"(d[14]), "+f"(d[15]), "+f"(d[16]), "+f"(d[17]), "+f"(d[18]), "+f"(d[19]), "+f"(d[20]), "+f"(d[21]), "+f"(d[22]), "+f"(d[23]), "+f"(d[24]), "+f"(d[25]), "+f"(d[26]), "+f"(d[27]), "+f"(d[28]), "+f"(d[29]), "+f"(d[30]), "+f"(d[31])
    : "r"(a[0]), "r"(a[1]), "r"(a[2]), "r"(a[3]), "l"(descB), "r"(scaleD));
}

__global__ void __launch_bounds__(NTHREADS, 1)
fused_mlp_kernel(const __grid_constant__ CUtensorMap tm_w1, const __grid_constant__ CUtensorMap tm_w2,
                 const __nv_bfloat16* __restrict__ x, const __nv_bfloat16* __restrict__ b1,
                 const __nv_bfloat16* __restrict__ b2, __nv_bfloat16* __restrict__ out)
{
  extern __shared__ __align__(1024) unsigned char smem[];
  const uint32_t sbase = smem_u32(smem);
  const uint32_t bar_full = sbase + OFF_BAR;
  const uint32_t bar_cons = sbase + OFF_BAR + 128;
  const uint32_t bar_sent = sbase + OFF_BAR + 256;
  const uint32_t bar_pfull = sbase + OFF_BAR + 320;
  const uint32_t bar_pcons = sbase + OFF_BAR + 384;
  const int tid = threadIdx.x, warp = tid >> 5, lane = tid & 31;
  const int mb = blockIdx.x >> 3, j = blockIdx.x & 7;

  TSC(0);
  if (warp == 8) {
    if (lane == 0) {
      for (int i = 0; i < 16; i++) { mbar_init(bar_full + 8 * i, 1); mbar_init(bar_cons + 8 * i, 2); }
      for (int i = 0; i < 8; i++) { mbar_init(bar_sent + 8 * i, 8); mbar_init(bar_pfull + 8 * i, 1); mbar_init(bar_pcons + 8 * i, 8); }
      asm volatile("fence.mbarrier_init.release.cluster;" ::: "memory");
      asm volatile("fence.proxy.async.shared::cta;" ::: "memory");
      for (int i = 0; i < NRING; i++) {
        mbar_expect_tx(bar_full + 8 * i, STAGE_BYTES);
        tma_load_3d(sbase + OFF_RING + i * STAGE_BYTES, &tm_w1, 0, i * 64, j * 7, bar_full + 8 * i);
      }
      if (mb < 8) { if (mb >= NRING) tma_prefetch_3d(&tm_w1, 0, mb * 64, j * 7); }
      else tma_prefetch_2d(&tm_w2, (mb - 8) * 64, j * BF);
    }
  }
  __syncthreads();

  if (warp >= 8) {
    asm volatile("setmaxnreg.dec.sync.aligned.u32 40;");
    if (warp == 8 && lane == 0) {
      for (int i = NRING; i < 16; i++) {
        uint32_t dst;
        if (i < 11)      { mbar_wait(bar_cons + 8 * (i - NRING), 0); dst = sbase + OFF_RING + (i % NRING) * STAGE_BYTES; }
        else if (i < 13) { dst = sbase + (i - 11) * STAGE_BYTES; }
        else             { mbar_wait(bar_cons + 8 * (i - 5), 0); dst = sbase + OFF_RING + ((i - 5) % NRING) * STAGE_BYTES; }
        TS(2, i);
        mbar_expect_tx(bar_full + 8 * i, STAGE_BYTES);
        if (i < 8) tma_load_3d(dst, &tm_w1, 0, i * 64, j * 7, bar_full + 8 * i);
        else {
          int sl = (j + 1 + (i - 8)) & 7;
          tma_load_2d(dst, &tm_w2, sl * BN2, j * BF, bar_full + 8 * i);
        }
      }
    } else if (warp == 9 && lane == 0) {
      for (int n = 0; n < 7; n++) {
        const int src = (j + 7 - n) & 7;
        unsigned int* fl = &g_flag[(mb * NSPLIT + j) * NSPLIT + src];
        uint32_t it = 0, v;
        while (true) {
          asm volatile("ld.acquire.gpu.global.u32 %0, [%1];" : "=r"(v) : "l"(fl) : "memory");
          if (v != 0) break;
          if (++it > (1u << 22)) asm volatile("trap;");
        }
        *reinterpret_cast<volatile unsigned int*>(fl) = 0;
        if (n == 0) mbar_wait(bar_cons + 8 * 7, 0);
        if (n >= 4) mbar_wait(bar_pcons + 8 * (n - 4), 0);
        asm volatile("fence.proxy.async;" ::: "memory");
        mbar_expect_tx(bar_pfull + 8 * n, PSLOT_BYTES);
        const uint4* p = &g_part[(size_t)((mb * NSPLIT + j) * NSPLIT + src) * 1024];
        asm volatile("cp.async.bulk.shared::cluster.global.mbarrier::complete_tx::bytes [%0], [%1], %2, [%3];"
                     :: "r"(sbase + OFF_PSLOT + (n & 3) * PSLOT_BYTES), "l"(p), "r"(PSLOT_BYTES), "r"(bar_pfull + 8 * n) : "memory");
      }
    } else if (warp == 10 && lane == 0) {
      for (int i = 0; i < 7; i++) {
        mbar_wait(bar_sent + 8 * i, 0);
        __threadfence();
        const int dest = (j + 1 + i) & 7;
        asm volatile("st.release.gpu.global.u32 [%0], %1;" :: "l"(&g_flag[(mb * NSPLIT + dest) * NSPLIT + j]), "r"(1u) : "memory");
      }
    }
  } else {
    asm volatile("setmaxnreg.inc.sync.aligned.u32 232;");
    const int wg = warp >> 2;
    const int q = lane & 3, g = lane >> 2;
    float* rstd_s = reinterpret_cast<float*>(smem + OFF_RSTD);
    if (tid < BF / 2) reinterpret_cast<uint32_t*>(smem + OFF_B1)[tid] = reinterpret_cast<const uint32_t*>(b1 + j * BF)[tid];
    else if (tid >= 128 && tid < 128 + BN2 / 2) reinterpret_cast<uint32_t*>(smem + OFF_B2)[tid - 128] = reinterpret_cast<const uint32_t*>(b2 + j * BN2)[tid - 128];

    {
      const uint4* xg = reinterpret_cast<const uint4*>(x + (size_t)mb * BM * D_MOD);
      uint4 xv[16][2];
#pragma unroll
      for (int r = 0; r < 16; r++) {
        int row = (r >> 3) * 64 + warp * 8 + (r & 7);
        xv[r][0] = __ldg(xg + row * 64 + lane);
        xv[r][1] = __ldg(xg + row * 64 + 32 + lane);
      }
#pragma unroll
      for (int hf = 0; hf < 2; hf++) {
        float s[8];
#pragma unroll
        for (int r = 0; r < 8; r++) {
          const uint4 a = xv[hf * 8 + r][0], b = xv[hf * 8 + r][1];
          s[r] = ((bf_lo(a.x) + bf_hi(a.x)) + (bf_lo(a.y) + bf_hi(a.y))) + ((bf_lo(a.z) + bf_hi(a.z)) + (bf_lo(a.w) + bf_hi(a.w)))
               + ((bf_lo(b.x) + bf_hi(b.x)) + (bf_lo(b.y) + bf_hi(b.y))) + ((bf_lo(b.z) + bf_hi(b.z)) + (bf_lo(b.w) + bf_hi(b.w)));
        }
#pragma unroll
        for (int o = 16; o > 0; o >>= 1)
#pragma unroll
          for (int r = 0; r < 8; r++) s[r] += __shfl_xor_sync(0xffffffffu, s[r], o);
        float v[8];
#pragma unroll
        for (int r = 0; r < 8; r++) {
          const int row = hf * 64 + warp * 8 + r;
          const uint4 a = xv[hf * 8 + r][0], b = xv[hf * 8 + r][1];
          const float mean = s[r] * (1.0f / D_MOD);
          const uint32_t m2 = pack_bf16(mean, mean);
          uint4 d0, d1;
          d0.x = hsub2_bf(a.x, m2); d0.y = hsub2_bf(a.y, m2); d0.z = hsub2_bf(a.z, m2); d0.w = hsub2_bf(a.w, m2);
          d1.x = hsub2_bf(b.x, m2); d1.y = hsub2_bf(b.y, m2); d1.z = hsub2_bf(b.z, m2); d1.w = hsub2_bf(b.w, m2);
          const uint32_t a0 = (uint32_t)((lane >> 3) * 16384 + row * 128 + (((lane & 7) ^ (row & 7)) << 4));
          *reinterpret_cast<uint4*>(smem + a0) = d0;
          *reinterpret_cast<uint4*>(smem + a0 + 4 * 16384) = d1;
          const uint32_t w[8] = {a.x, a.y, a.z, a.w, b.x, b.y, b.z, b.w};
          float v0 = 0.f, v1 = 0.f;
#pragma unroll
          for (int e = 0; e < 8; e++) { float p = bf_lo(w[e]) - mean, t = bf_hi(w[e]) - mean; v0 = fmaf(p, p, v0); v1 = fmaf(t, t, v1); }
          v[r] = v0 + v1;
        }
#pragma unroll
        for (int o = 16; o > 0; o >>= 1)
#pragma unroll
          for (int r = 0; r < 8; r++) v[r] += __shfl_xor_sync(0xffffffffu, v[r], o);
        float vs = v[0];
#pragma unroll
        for (int r = 1; r < 8; r++) vs = (lane == r) ? v[r] : vs;
        const float vb = bf16r(vs * (1.0f / D_MOD));
        const float sd = bf16r(sqrtf(bf16r(vb + 1e-5f)));
        if (lane < 8) rstd_s[hf * 64 + warp * 8 + lane] = 1.0f / sd;
      }
    }
    TSC(1);
    asm volatile("fence.proxy.async.shared::cta;" ::: "memory");
    asm volatile("bar.sync 1, 256;" ::: "memory");
    TSC(2);

    uint32_t h[14][4];
    {
      float acc[112];
#pragma unroll
      for (int kb = 0; kb < 8; kb++) {
        mbar_wait(bar_full + 8 * kb, 0);
        TSC(3 + kb);
        wg_fence();
        const uint32_t abase = sbase + kb * 16384 + wg * 8192;
        const uint32_t bbase = sbase + OFF_RING + (kb % NRING) * STAGE_BYTES;
#pragma unroll
        for (int kk = 0; kk < 4; kk++) {
          wgmma_ss_n224(acc, make_desc(abase + kk * 32, 16, 1024, 1), make_desc(bbase + kk * 1024, 4096, 512, 2), (kb | kk) != 0);
        }
        wg_commit();
        if (kb > 0) { wg_wait<1>(); if ((tid & 127) == 0) mbar_arrive(bar_cons + 8 * (kb - 1)); }
      }
      wg_wait<0>();
      reg_fence(acc);
      if ((tid & 127) == 0) mbar_arrive(bar_cons + 8 * 7);
      TSC(11);

      const int row0 = wg * 64 + (warp & 3) * 16 + g;
      const float r0 = rstd_s[row0], r1 = rstd_s[row0 + 8];
      const uint32_t* b1s = reinterpret_cast<const uint32_t*>(smem + OFF_B1);
#pragma unroll
      for (int i = 0; i < 28; i++) {
        const uint32_t bb = b1s[i * 4 + q];
        uint32_t p0 = hadd2_bf(pack_bf16(acc[4 * i] * r0, acc[4 * i + 1] * r0), bb);
        uint32_t p1 = hadd2_bf(pack_bf16(acc[4 * i + 2] * r1, acc[4 * i + 3] * r1), bb);
        h[i >> 1][(i & 1) * 2 + 0] = pack_bf16(gelu_tanh(bf_lo(p0)), gelu_tanh(bf_hi(p0)));
        h[i >> 1][(i & 1) * 2 + 1] = pack_bf16(gelu_tanh(bf_lo(p1)), gelu_tanh(bf_hi(p1)));
      }
    }

    float acc2[2][32];
    float sum[32];
#pragma unroll
    for (int i = 0; i < 32; i++) sum[i] = 0.f;
    const int t128 = tid & 127;
    auto recv = [&](int n) {
      mbar_wait(bar_pfull + 8 * n, 0);
      const uint4* p = reinterpret_cast<const uint4*>(smem + OFF_PSLOT + (n & 3) * PSLOT_BYTES) + wg * 512 + t128;
#pragma unroll
      for (int c = 0; c < 4; c++) {
        uint4 v = p[c * 128];
        sum[c * 8 + 0] += bf_lo(v.x); sum[c * 8 + 1] += bf_hi(v.x);
        sum[c * 8 + 2] += bf_lo(v.y); sum[c * 8 + 3] += bf_hi(v.y);
        sum[c * 8 + 4] += bf_lo(v.z); sum[c * 8 + 5] += bf_hi(v.z);
        sum[c * 8 + 6] += bf_lo(v.w); sum[c * 8 + 7] += bf_hi(v.w);
      }
      if (n < 3) { __syncwarp(); if (lane == 0) mbar_arrive(bar_pcons + 8 * n); }
    };
#pragma unroll
    for (int i = 0; i < 8; i++) {
      TSC(12 + i);
      mbar_wait(bar_full + 8 * (8 + i), 0);
      uint32_t bbase;
      if (i < 3) bbase = sbase + OFF_RING + ((8 + i) % NRING) * STAGE_BYTES;
      else if (i < 5) bbase = sbase + (i - 3) * STAGE_BYTES;
      else bbase = sbase + OFF_RING + ((8 + i - 5) % NRING) * STAGE_BYTES;
      wg_fence();
#pragma unroll
      for (int ks = 0; ks < 14; ks++) {
        wgmma_rs_n64(acc2[i & 1], h[ks], make_desc(bbase + ks * 2048, 16, 1024, 1), ks != 0);
      }
      wg_commit();
      if (i > 0) {
        wg_wait<1>();
        reg_fence(acc2[(i - 1) & 1]);
        if (i <= 3 && t128 == 0) mbar_arrive(bar_cons + 8 * (8 + i - 1));
        const int dest = (j + i) & 7;
        uint4* p = &g_part[((size_t)((mb * NSPLIT + dest) * NSPLIT + j) * 2 + wg) * 512 + t128];
        const float* a = acc2[(i - 1) & 1];
#pragma unroll
        for (int c = 0; c < 4; c++) {
          uint4 v;
          v.x = pack_bf16(a[c * 8 + 0], a[c * 8 + 1]); v.y = pack_bf16(a[c * 8 + 2], a[c * 8 + 3]);
          v.z = pack_bf16(a[c * 8 + 4], a[c * 8 + 5]); v.w = pack_bf16(a[c * 8 + 6], a[c * 8 + 7]);
          __stcg(p + c * 128, v);
        }
        __syncwarp();
        if (lane == 0) mbar_arrive(bar_sent + 8 * (i - 1));
      }
      if (i >= 3) recv(i - 3);
    }
    recv(5);
    wg_wait<0>();
    reg_fence(acc2[1]);
    TSC(20);
    recv(6);
    TSC(21);

    {
      const uint32_t* b2s = reinterpret_cast<const uint32_t*>(smem + OFF_B2);
      const int row0 = mb * BM + wg * 64 + (warp & 3) * 16 + g;
      uint32_t* o0 = reinterpret_cast<uint32_t*>(out + (size_t)row0 * D_MOD + j * BN2) + q;
      uint32_t* o1 = o0 + 8 * D_MOD / 2;
#pragma unroll
      for (int i = 0; i < 8; i++) {
        const uint32_t bb = b2s[i * 4 + q];
        o0[i * 4] = hadd2_bf(pack_bf16(acc2[1][4 * i] + sum[4 * i], acc2[1][4 * i + 1] + sum[4 * i + 1]), bb);
        o1[i * 4] = hadd2_bf(pack_bf16(acc2[1][4 * i + 2] + sum[4 * i + 2], acc2[1][4 * i + 3] + sum[4 * i + 3]), bb);
      }
    }
  }
}

typedef CUresult (*EncodeFn)(CUtensorMap*, CUtensorMapDataType, cuuint32_t, void*, const cuuint64_t*, const cuuint64_t*,
                             const cuuint32_t*, const cuuint32_t*, CUtensorMapInterleave, CUtensorMapSwizzle,
                             CUtensorMapL2promotion, CUtensorMapFloatOOBfill);

}

extern "C" void kernel_launch(void* const* d_in, const int* in_sizes, int n_in, void* d_out, int out_size) {
  (void)in_sizes; (void)n_in; (void)out_size;
  static CUtensorMap tm_w1, tm_w2;
  static const void* cached_w1 = nullptr; static const void* cached_w2 = nullptr;
  const void* w1 = d_in[1]; const void* w2 = d_in[3];
  if (cached_w1 != w1 || cached_w2 != w2) {
    void* fn = nullptr; cudaDriverEntryPointQueryResult st;
    cudaGetDriverEntryPoint("cuTensorMapEncodeTiled", &fn, cudaEnableDefault, &st);
    EncodeFn enc = (EncodeFn)fn;
    {
      cuuint64_t dims[3] = {32, (cuuint64_t)D_MOD, (cuuint64_t)(F_HID / 32)};
      cuuint64_t strides[2] = {(cuuint64_t)F_HID * 2, 64};
      cuuint32_t box[3] = {32, 64, 7};
      cuuint32_t es[3] = {1, 1, 1};
      enc(&tm_w1, CU_TENSOR_MAP_DATA_TYPE_BFLOAT16, 3, const_cast<void*>(w1), dims, strides, box, es,
          CU_TENSOR_MAP_INTERLEAVE_NONE, CU_TENSOR_MAP_SWIZZLE_64B, CU_TENSOR_MAP_L2_PROMOTION_L2_128B, CU_TENSOR_MAP_FLOAT_OOB_FILL_NONE);
    }
    {
      cuuint64_t dims[2] = {(cuuint64_t)D_MOD, (cuuint64_t)F_HID};
      cuuint64_t strides[1] = {(cuuint64_t)D_MOD * 2};
      cuuint32_t box[2] = {64, 224};
      cuuint32_t es[2] = {1, 1};
      enc(&tm_w2, CU_TENSOR_MAP_DATA_TYPE_BFLOAT16, 2, const_cast<void*>(w2), dims, strides, box, es,
          CU_TENSOR_MAP_INTERLEAVE_NONE, CU_TENSOR_MAP_SWIZZLE_128B, CU_TENSOR_MAP_L2_PROMOTION_L2_128B, CU_TENSOR_MAP_FLOAT_OOB_FILL_NONE);
    }
    cudaFuncSetAttribute(fused_mlp_kernel, cudaFuncAttributeMaxDynamicSharedMemorySize, SMEM_TOTAL);
    cached_w1 = w1; cached_w2 = w2;
  }
  fused_mlp_kernel<<<NMB * NSPLIT, NTHREADS, SMEM_TOTAL>>>(tm_w1, tm_w2,
      (const __nv_bfloat16*)d_in[0], (const __nv_bfloat16*)d_in[2], (const __nv_bfloat16*)d_in[4], (__nv_bfloat16*)d_out);
}
```

```cpp
#include <cuda_runtime.h>
#include <cuda_bf16.h>
#include <cuda.h>
#include <stdint.h>

namespace {

constexpr int S_TOK = 2048, D_MOD = 512, F_HID = 1792;
constexpr int BM = 128, NSPLIT = 8, BF = F_HID / NSPLIT;
constexpr int BN2 = D_MOD / NSPLIT;
constexpr int NMB = S_TOK / BM;
constexpr int STAGE_BYTES = 28672;
constexpr int Y_BYTES = BM * D_MOD * 2;
constexpr int NRING = 3;
constexpr int OFF_RING = Y_BYTES;
constexpr int OFF_BAR = OFF_RING + NRING * STAGE_BYTES;
constexpr int OFF_PSLOT = 2 * STAGE_BYTES;
constexpr int PSLOT_BYTES = 16384;
constexpr int OFF_RSTD = OFF_BAR + 512;
constexpr int OFF_B1 = OFF_RSTD + 512;
constexpr int OFF_B2 = OFF_B1 + 512;
constexpr int SMEM_TOTAL = OFF_B2 + 128;
constexpr int NTHREADS = 384;

__device__ uint4 g_part[(size_t)NMB * NSPLIT * NSPLIT * 2 * 4 * 128];
__device__ unsigned int g_epoch[NMB * NSPLIT];

#define TS(role, idx) do {} while (0)
#define TSC(idx) do {} while (0)

__device__ __forceinline__ uint32_t smem_u32(const void* p) { return (uint32_t)__cvta_generic_to_shared(p); }
__device__ __forceinline__ void mbar_init(uint32_t bar, uint32_t cnt) {
  asm volatile("mbarrier.init.shared::cta.b64 [%0], %1;" :: "r"(bar), "r"(cnt) : "memory");
}
__device__ __forceinline__ void mbar_expect_tx(uint32_t bar, uint32_t bytes) {
  asm volatile("mbarrier.arrive.expect_tx.shared::cta.b64 _, [%0], %1;" :: "r"(bar), "r"(bytes) : "memory");
}
__device__ __forceinline__ void mbar_arrive(uint32_t bar) {
  asm volatile("mbarrier.arrive.shared::cta.b64 _, [%0];" :: "r"(bar) : "memory");
}
__device__ __forceinline__ void mbar_wait(uint32_t bar, uint32_t parity) {
  uint32_t done = 0; uint32_t it = 0;
  while (true) {
    asm volatile("{\n.reg .pred p;\nmbarrier.try_wait.parity.shared::cta.b64 p, [%1], %2;\nselp.u32 %0, 1, 0, p;\n}"
                 : "=r"(done) : "r"(bar), "r"(parity) : "memory");
    if (done) break;
    if (++it > (1u << 22)) asm volatile("trap;");
  }
}
__device__ __forceinline__ void tma_load_3d(uint32_t dst, const CUtensorMap* tm, int c0, int c1, int c2, uint32_t bar) {
  asm volatile("cp.async.bulk.tensor.3d.shared::cluster.global.mbarrier::complete_tx::bytes [%0], [%1, {%3, %4, %5}], [%2];"
               :: "r"(dst), "l"(tm), "r"(bar), "r"(c0), "r"(c1), "r"(c2) : "memory");
}
__device__ __forceinline__ void tma_load_2d(uint32_t dst, const CUtensorMap* tm, int c0, int c1, uint32_t bar) {
  asm volatile("cp.async.bulk.tensor.2d.shared::cluster.global.mbarrier::complete_tx::bytes [%0], [%1, {%3, %4}], [%2];"
               :: "r"(dst), "l"(tm), "r"(bar), "r"(c0), "r"(c1) : "memory");
}
__device__ __forceinline__ void tma_prefetch_3d(const CUtensorMap* tm, int c0, int c1, int c2) {
  asm volatile("cp.async.bulk.prefetch.tensor.3d.L2.global.tile [%0, {%1, %2, %3}];" :: "l"(tm), "r"(c0), "r"(c1), "r"(c2) : "memory");
}
__device__ __forceinline__ void tma_prefetch_2d(const CUtensorMap* tm, int c0, int c1) {
  asm volatile("cp.async.bulk.prefetch.tensor.2d.L2.global.tile [%0, {%1, %2}];" :: "l"(tm), "r"(c0), "r"(c1) : "memory");
}
__device__ __forceinline__ void wg_fence() { asm volatile("wgmma.fence.sync.aligned;" ::: "memory"); }
__device__ __forceinline__ void wg_commit() { asm volatile("wgmma.commit_group.sync.aligned;" ::: "memory"); }
template <int N> __device__ __forceinline__ void wg_wait() { asm volatile("wgmma.wait_group.sync.aligned %0;" :: "n"(N) : "memory"); }
template <int N> __device__ __forceinline__ void reg_fence(float (&d)[N]) {
#pragma unroll
  for (int i = 0; i < N; i++) asm volatile("" : "+f"(d[i]) :: "memory");
}
__device__ __forceinline__ uint64_t make_desc(uint32_t addr, uint32_t lbo, uint32_t sbo, uint32_t lt) {
  return (uint64_t)((addr & 0x3FFFF) >> 4) | ((uint64_t)(lbo >> 4) << 16) | ((uint64_t)(sbo >> 4) << 32) | ((uint64_t)lt << 62);
}
__device__ __forceinline__ uint32_t pack_bf16(float lo, float hi) {
  uint32_t r; asm("cvt.rn.bf16x2.f32 %0, %1, %2;" : "=r"(r) : "f"(hi), "f"(lo)); return r;
}
__device__ __forceinline__ float bf_lo(uint32_t v) { return __uint_as_float(v << 16); }
__device__ __forceinline__ float bf_hi(uint32_t v) { return __uint_as_float(v & 0xffff0000u); }
__device__ __forceinline__ float bf16r(float v) { return __bfloat162float(__float2bfloat16_rn(v)); }
__device__ __forceinline__ uint32_t hadd2_bf(uint32_t a, uint32_t b) {
  uint32_t r; asm("add.rn.bf16x2 %0, %1, %2;" : "=r"(r) : "r"(a), "r"(b)); return r;
}
__device__ __forceinline__ uint32_t hsub2_bf(uint32_t a, uint32_t b) {
  uint32_t r; asm("sub.rn.bf16x2 %0, %1, %2;" : "=r"(r) : "r"(a), "r"(b)); return r;
}
__device__ __forceinline__ float gelu_tanh(float u) {
  float inner = u * fmaf(0.035677408136300125f, u * u, 0.7978845608028654f);
  float th; asm("tanh.approx.f32 %0, %1;" : "=f"(th) : "f"(inner));
  float hu = 0.5f * u;
  return fmaf(hu, th, hu);
}

__device__ __forceinline__ void wgmma_ss_n224(float (&d)[112], uint64_t descA, uint64_t descB, int scaleD) {
  asm volatile("{\n.reg .pred p;\nsetp.ne.b32 p, %114, 0;\n"
    "wgmma.mma_async.sync.aligned.m64n224k16.f32.bf16.bf16 {%0, %1, %2, %3, %4, %5, %6, %7, %8, %9, %10, %11, %12, %13, %14, %15, %16, %17, %18, %19, %20, %21, %22, %23, %24, %25, %26, %27, %28, %29, %30, %31, %32, %33, %34, %35, %36, %37, %38, %39, %40, %41, %42, %43, %44, %45, %46, %47, %48, %49, %50, %51, %52, %53, %54, %55, %56, %57, %58, %59, %60, %61, %62, %63, %64, %65, %66, %67, %68, %69, %70, %71, %72, %73, %74, %75, %76, %77, %78, %79, %80, %81, %82, %83, %84, %85, %86, %87, %88, %89, %90, %91, %92, %93, %94, %95, %96, %97, %98, %99, %100, %101, %102, %103, %104, %105, %106, %107, %108, %109, %110, %111}, %112, %113, p, 1, 1, 0, 1;\n}\n"
    : "+f"(d[0]), "+f"(d[1]), "+f"(d[2]), "+f"(d[3]), "+f"(d[4]), "+f"(d[5]), "+f"(d[6]), "+f"(d[7]), "+f"(d[8]), "+f"(d[9]), "+f"(d[10]), "+f"(d[11]), "+f"(d[12]), "+f"(d[13]), "+f"(d[14]), "+f"(d[15]), "+f"(d[16]), "+f"(d[17]), "+f"(d[18]), "+f"(d[19]), "+f"(d[20]), "+f"(d[21]), "+f"(d[22]), "+f"(d[23]), "+f"(d[24]), "+f"(d[25]), "+f"(d[26]), "+f"(d[27]), "+f"(d[28]), "+f"(d[29]), "+f"(d[30]), "+f"(d[31]), "+f"(d[32]), "+f"(d[33]), "+f"(d[34]), "+f"(d[35]), "+f"(d[36]), "+f"(d[37]), "+f"(d[38]), "+f"(d[39]), "+f"(d[40]), "+f"(d[41]), "+f"(d[42]), "+f"(d[43]), "+f"(d[44]), "+f"(d[45]), "+f"(d[46]), "+f"(d[47]), "+f"(d[48]), "+f"(d[49]), "+f"(d[50]), "+f"(d[51]), "+f"(d[52]), "+f"(d[53]), "+f"(d[54]), "+f"(d[55]), "+f"(d[56]), "+f"(d[57]), "+f"(d[58]), "+f"(d[59]), "+f"(d[60]), "+f"(d[61]), "+f"(d[62]), "+f"(d[63]), "+f"(d[64]), "+f"(d[65]), "+f"(d[66]), "+f"(d[67]), "+f"(d[68]), "+f"(d[69]), "+f"(d[70]), "+f"(d[71]), "+f"(d[72]), "+f"(d[73]), "+f"(d[74]), "+f"(d[75]), "+f"(d[76]), "+f"(d[77]), "+f"(d[78]), "+f"(d[79]), "+f"(d[80]), "+f"(d[81]), "+f"(d[82]), "+f"(d[83]), "+f"(d[84]), "+f"(d[85]), "+f"(d[86]), "+f"(d[87]), "+f"(d[88]), "+f"(d[89]), "+f"(d[90]), "+f"(d[91]), "+f"(d[92]), "+f"(d[93]), "+f"(d[94]), "+f"(d[95]), "+f"(d[96]), "+f"(d[97]), "+f"(d[98]), "+f"(d[99]), "+f"(d[100]), "+f"(d[101]), "+f"(d[102]), "+f"(d[103]), "+f"(d[104]), "+f"(d[105]), "+f"(d[106]), "+f"(d[107]), "+f"(d[108]), "+f"(d[109]), "+f"(d[110]), "+f"(d[111])
    : "l"(descA), "l"(descB), "r"(scaleD));
}

__device__ __forceinline__ void wgmma_rs_n64(float (&d)[32], const uint32_t (&a)[4], uint64_t descB, int scaleD) {
  asm volatile("{\n.reg .pred p;\nsetp.ne.b32 p, %37, 0;\n"
    "wgmma.mma_async.sync.aligned.m64n64k16.f32.bf16.bf16 {%0, %1, %2, %3, %4, %5, %6, %7, %8, %9, %10, %11, %12, %13, %14, %15, %16, %17, %18, %19, %20, %21, %22, %23, %24, %25, %26, %27, %28, %29, %30, %31}, {%32, %33, %34, %35}, %36, p, 1, 1, 1;\n}\n"
    : "+f"(d[0]), "+f"(d[1]), "+f"(d[2]), "+f"(d[3]), "+f"(d[4]), "+f"(d[5]), "+f"(d[6]), "+f"(d[7]), "+f"(d[8]), "+f"(d[9]), "+f"(d[10]), "+f"(d[11]), "+f"(d[12]), "+f"(d[13]), "+f"(d[14]), "+f"(d[15]), "+f"(d[16]), "+f"(d[17]), "+f"(d[18]), "+f"(d[19]), "+f"(d[20]), "+f"(d[21]), "+f"(d[22]), "+f"(d[23]), "+f"(d[24]), "+f"(d[25]), "+f"(d[26]), "+f"(d[27]), "+f"(d[28]), "+f"(d[29]), "+f"(d[30]), "+f"(d[31])
    : "r"(a[0]), "r"(a[1]), "r"(a[2]), "r"(a[3]), "l"(descB), "r"(scaleD));
}

__global__ void __launch_bounds__(NTHREADS, 1)
fused_mlp_kernel(const __grid_constant__ CUtensorMap tm_x, const __grid_constant__ CUtensorMap tm_w1, const __grid_constant__ CUtensorMap tm_w2,
                 const __nv_bfloat16* __restrict__ b1,
                 const __nv_bfloat16* __restrict__ b2, __nv_bfloat16* __restrict__ out)
{
  extern __shared__ __align__(1024) unsigned char smem[];
  const uint32_t sbase = smem_u32(smem);
  const uint32_t bar_full = sbase + OFF_BAR;
  const uint32_t bar_cons = sbase + OFF_BAR + 128;
  const uint32_t bar_x = sbase + OFF_BAR + 256;
  const int tid = threadIdx.x, warp = tid >> 5, lane = tid & 31;
  const int mb = blockIdx.x >> 3, j = blockIdx.x & 7;

  TSC(0);
  if (warp == 8) {
    if (lane == 0) {
      for (int i = 0; i < 16; i++) { mbar_init(bar_full + 8 * i, 1); mbar_init(bar_cons + 8 * i, 2); }
      for (int i = 0; i < 4; i++) mbar_init(bar_x + 8 * i, 1);
      asm volatile("fence.mbarrier_init.release.cluster;" ::: "memory");
      asm volatile("fence.proxy.async.shared::cta;" ::: "memory");
      for (int gq = 0; gq < 4; gq++) {
        mbar_expect_tx(bar_x + 8 * gq, 32768);
        for (int kb = 0; kb < 8; kb++)
          tma_load_2d(sbase + kb * 16384 + gq * 4096, &tm_x, kb * 64, mb * BM + gq * 32, bar_x + 8 * gq);
        if (gq >= 1) {
          const int i = gq - 1;
          mbar_expect_tx(bar_full + 8 * i, STAGE_BYTES);
          tma_load_3d(sbase + OFF_RING + i * STAGE_BYTES, &tm_w1, 0, i * 64, j * 7, bar_full + 8 * i);
        }
      }
      if (mb < 8) { if (mb >= NRING) tma_prefetch_3d(&tm_w1, 0, mb * 64, j * 7); }
      else tma_prefetch_2d(&tm_w2, (mb - 8) * 64, j * BF);
    }
  }
  __syncthreads();

  if (warp >= 8) {
    asm volatile("setmaxnreg.dec.sync.aligned.u32 40;");
    if (warp == 8 && lane == 0) {
      for (int i = NRING; i < 16; i++) {
        uint32_t dst;
        if (i < 11)      { mbar_wait(bar_cons + 8 * (i - NRING), 0); dst = sbase + OFF_RING + (i % NRING) * STAGE_BYTES; }
        else if (i < 15) { dst = sbase + (i - 11) * STAGE_BYTES; }
        else             { mbar_wait(bar_cons + 8 * 8, 0); dst = sbase + OFF_RING + (8 % NRING) * STAGE_BYTES; }
        TS(2, i);
        mbar_expect_tx(bar_full + 8 * i, STAGE_BYTES);
        if (i < 8) tma_load_3d(dst, &tm_w1, 0, i * 64, j * 7, bar_full + 8 * i);
        else {
          int sl = (j + 1 + (i - 8)) & 7;
          tma_load_2d(dst, &tm_w2, sl * BN2, j * BF, bar_full + 8 * i);
        }
      }
    }
  } else {
    asm volatile("setmaxnreg.inc.sync.aligned.u32 232;");
    const int wg = warp >> 2;
    const int q = lane & 3, g = lane >> 2;
    float* rstd_s = reinterpret_cast<float*>(smem + OFF_RSTD);
    if (tid < BF / 2) reinterpret_cast<uint32_t*>(smem + OFF_B1)[tid] = reinterpret_cast<const uint32_t*>(b1 + j * BF)[tid];
    else if (tid >= 128 && tid < 128 + BN2 / 2) reinterpret_cast<uint32_t*>(smem + OFF_B2)[tid - 128] = reinterpret_cast<const uint32_t*>(b2 + j * BN2)[tid - 128];

    const uint32_t epoch = g_epoch[blockIdx.x];
    const uint32_t par = (epoch + 1) & 1;

#pragma unroll
    for (int gq = 0; gq < 4; gq++) {
      mbar_wait(bar_x + 8 * gq, 0);
      uint4 xa[4], xb[4];
      uint32_t ad[4];
      float s[4];
#pragma unroll
      for (int r = 0; r < 4; r++) {
        const int row = gq * 32 + warp * 4 + r;
        ad[r] = (uint32_t)((lane >> 3) * 16384 + row * 128 + (((lane & 7) ^ (row & 7)) << 4));
        xa[r] = *reinterpret_cast<const uint4*>(smem + ad[r]);
        xb[r] = *reinterpret_cast<const uint4*>(smem + ad[r] + 4 * 16384);
      }
#pragma unroll
      for (int r = 0; r < 4; r++) {
        const uint4 a = xa[r], b = xb[r];
        s[r] = ((bf_lo(a.x) + bf_hi(a.x)) + (bf_lo(a.y) + bf_hi(a.y))) + ((bf_lo(a.z) + bf_hi(a.z)) + (bf_lo(a.w) + bf_hi(a.w)))
             + ((bf_lo(b.x) + bf_hi(b.x)) + (bf_lo(b.y) + bf_hi(b.y))) + ((bf_lo(b.z) + bf_hi(b.z)) + (bf_lo(b.w) + bf_hi(b.w)));
      }
#pragma unroll
      for (int o = 16; o > 0; o >>= 1)
#pragma unroll
        for (int r = 0; r < 4; r++) s[r] += __shfl_xor_sync(0xffffffffu, s[r], o);
      float v[4];
#pragma unroll
      for (int r = 0; r < 4; r++) {
        const uint4 a = xa[r], b = xb[r];
        const float mean = s[r] * (1.0f / D_MOD);
        const uint32_t m2 = pack_bf16(mean, mean);
        uint4 d0, d1;
        d0.x = hsub2_bf(a.x, m2); d0.y = hsub2_bf(a.y, m2); d0.z = hsub2_bf(a.z, m2); d0.w = hsub2_bf(a.w, m2);
        d1.x = hsub2_bf(b.x, m2); d1.y = hsub2_bf(b.y, m2); d1.z = hsub2_bf(b.z, m2); d1.w = hsub2_bf(b.w, m2);
        *reinterpret_cast<uint4*>(smem + ad[r]) = d0;
        *reinterpret_cast<uint4*>(smem + ad[r] + 4 * 16384) = d1;
        const uint32_t w[8] = {a.x, a.y, a.z, a.w, b.x, b.y, b.z, b.w};
        float v0 = 0.f, v1 = 0.f;
#pragma unroll
        for (int e = 0; e < 8; e++) { float p = bf_lo(w[e]) - mean, t = bf_hi(w[e]) - mean; v0 = fmaf(p, p, v0); v1 = fmaf(t, t, v1); }
        v[r] = v0 + v1;
      }
#pragma unroll
      for (int o = 16; o > 0; o >>= 1)
#pragma unroll
        for (int r = 0; r < 4; r++) v[r] += __shfl_xor_sync(0xffffffffu, v[r], o);
      float vs = v[0];
#pragma unroll
      for (int r = 1; r < 4; r++) vs = (lane == r) ? v[r] : vs;
      const float vb = bf16r(vs * (1.0f / D_MOD));
      const float sd = bf16r(sqrtf(bf16r(vb + 1e-5f)));
      if (lane < 4) rstd_s[gq * 32 + warp * 4 + lane] = 1.0f / sd;
    }
    TSC(1);
    asm volatile("fence.proxy.async.shared::cta;" ::: "memory");
    asm volatile("bar.sync 1, 256;" ::: "memory");
    TSC(2);

    uint32_t h[14][4];
    {
      float acc[112];
#pragma unroll
      for (int kb = 0; kb < 8; kb++) {
        mbar_wait(bar_full + 8 * kb, 0);
        TSC(3 + kb);
        wg_fence();
        const uint32_t abase = sbase + kb * 16384 + wg * 8192;
        const uint32_t bbase = sbase + OFF_RING + (kb % NRING) * STAGE_BYTES;
#pragma unroll
        for (int kk = 0; kk < 4; kk++) {
          wgmma_ss_n224(acc, make_desc(abase + kk * 32, 16, 1024, 1), make_desc(bbase + kk * 1024, 4096, 512, 2), (kb | kk) != 0);
        }
        wg_commit();
        if (kb > 0) { wg_wait<1>(); if ((tid & 127) == 0) mbar_arrive(bar_cons + 8 * (kb - 1)); }
      }
      wg_wait<0>();
      reg_fence(acc);
      if ((tid & 127) == 0) mbar_arrive(bar_cons + 8 * 7);
      TSC(11);

      const int row0 = wg * 64 + (warp & 3) * 16 + g;
      const float r0 = rstd_s[row0], r1 = rstd_s[row0 + 8];
      const uint32_t* b1s = reinterpret_cast<const uint32_t*>(smem + OFF_B1);
#pragma unroll
      for (int i = 0; i < 28; i++) {
        const uint32_t bb = b1s[i * 4 + q];
        uint32_t p0 = hadd2_bf(pack_bf16(acc[4 * i] * r0, acc[4 * i + 1] * r0), bb);
        uint32_t p1 = hadd2_bf(pack_bf16(acc[4 * i + 2] * r1, acc[4 * i + 3] * r1), bb);
        h[i >> 1][(i & 1) * 2 + 0] = pack_bf16(gelu_tanh(bf_lo(p0)), gelu_tanh(bf_hi(p0)));
        h[i >> 1][(i & 1) * 2 + 1] = pack_bf16(gelu_tanh(bf_lo(p1)), gelu_tanh(bf_hi(p1)));
      }
    }

    float acc2[2][32];
    float sum[32];
#pragma unroll
    for (int i = 0; i < 32; i++) sum[i] = 0.f;
    const int t128 = tid & 127;
    uint4 pf[4];
    auto part_ptr = [&](int n) {
      const int src = (j + 7 - n) & 7;
      return &g_part[((size_t)((mb * NSPLIT + j) * NSPLIT + src) * 2 + wg) * 512 + t128];
    };
    auto ld_part = [&](const uint4* p) {
      uint4 v;
      asm volatile("ld.relaxed.gpu.global.v4.u32 {%0, %1, %2, %3}, [%4];" : "=r"(v.x), "=r"(v.y), "=r"(v.z), "=r"(v.w) : "l"(p) : "memory");
      return v;
    };
    auto prefetch = [&](int n) {
      const uint4* p = part_ptr(n);
#pragma unroll
      for (int c = 0; c < 4; c++) pf[c] = ld_part(p + c * 128);
    };
    auto consume = [&](int n) {
      const uint4* p = part_ptr(n);
#pragma unroll
      for (int c = 0; c < 4; c++) {
        uint4 v = pf[c];
        uint32_t it = 0;
        while ((((v.x ^ par) | (v.y ^ par) | (v.z ^ par) | (v.w ^ par)) & 1u) != 0) {
          v = ld_part(p + c * 128);
          if (++it > (1u << 20)) asm volatile("trap;");
        }
        sum[c * 8 + 0] += bf_lo(v.x & ~1u); sum[c * 8 + 1] += bf_hi(v.x);
        sum[c * 8 + 2] += bf_lo(v.y & ~1u); sum[c * 8 + 3] += bf_hi(v.y);
        sum[c * 8 + 4] += bf_lo(v.z & ~1u); sum[c * 8 + 5] += bf_hi(v.z);
        sum[c * 8 + 6] += bf_lo(v.w & ~1u); sum[c * 8 + 7] += bf_hi(v.w);
      }
    };
#pragma unroll
    for (int i = 0; i < 8; i++) {
      TSC(12 + i);
      mbar_wait(bar_full + 8 * (8 + i), 0);
      uint32_t bbase;
      if (i < 3) bbase = sbase + OFF_RING + ((8 + i) % NRING) * STAGE_BYTES;
      else if (i < 7) bbase = sbase + (i - 3) * STAGE_BYTES;
      else bbase = sbase + OFF_RING + (8 % NRING) * STAGE_BYTES;
      wg_fence();
#pragma unroll
      for (int ks = 0; ks < 14; ks++) {
        wgmma_rs_n64(acc2[i & 1], h[ks], make_desc(bbase + ks * 2048, 16, 1024, 1), ks != 0);
      }
      wg_commit();
      if (i > 0) {
        wg_wait<1>();
        reg_fence(acc2[(i - 1) & 1]);
        if (i == 1 && t128 == 0) mbar_arrive(bar_cons + 8 * 8);
        const int dest = (j + i) & 7;
        uint4* p = &g_part[((size_t)((mb * NSPLIT + dest) * NSPLIT + j) * 2 + wg) * 512 + t128];
        const float* a = acc2[(i - 1) & 1];
#pragma unroll
        for (int c = 0; c < 4; c++) {
          uint4 v;
          v.x = (pack_bf16(a[c * 8 + 0], a[c * 8 + 1]) & ~1u) | par; v.y = (pack_bf16(a[c * 8 + 2], a[c * 8 + 3]) & ~1u) | par;
          v.z = (pack_bf16(a[c * 8 + 4], a[c * 8 + 5]) & ~1u) | par; v.w = (pack_bf16(a[c * 8 + 6], a[c * 8 + 7]) & ~1u) | par;
          __stcg(p + c * 128, v);
        }
      }
      if (i >= 4) consume(i - 4);
      if (i >= 3) prefetch(i - 3);
    }
    consume(4);
    prefetch(5);
    consume(5);
    prefetch(6);
    wg_wait<0>();
    reg_fence(acc2[1]);
    TSC(20);
    consume(6);
    TSC(21);
    if (tid == 0) g_epoch[blockIdx.x] = epoch + 1;

    {
      const uint32_t* b2s = reinterpret_cast<const uint32_t*>(smem + OFF_B2);
      const int row0 = mb * BM + wg * 64 + (warp & 3) * 16 + g;
      uint32_t* o0 = reinterpret_cast<uint32_t*>(out + (size_t)row0 * D_MOD + j * BN2) + q;
      uint32_t* o1 = o0 + 8 * D_MOD / 2;
#pragma unroll
      for (int i = 0; i < 8; i++) {
        const uint32_t bb = b2s[i * 4 + q];
        o0[i * 4] = hadd2_bf(pack_bf16(acc2[1][4 * i] + sum[4 * i], acc2[1][4 * i + 1] + sum[4 * i + 1]), bb);
        o1[i * 4] = hadd2_bf(pack_bf16(acc2[1][4 * i + 2] + sum[4 * i + 2], acc2[1][4 * i + 3] + sum[4 * i + 3]), bb);
      }
    }
  }
}

typedef CUresult (*EncodeFn)(CUtensorMap*, CUtensorMapDataType, cuuint32_t, void*, const cuuint64_t*, const cuuint64_t*,
                             const cuuint32_t*, const cuuint32_t*, CUtensorMapInterleave, CUtensorMapSwizzle,
                             CUtensorMapL2promotion, CUtensorMapFloatOOBfill);

}

extern "C" void kernel_launch(void* const* d_in, const int* in_sizes, int n_in, void* d_out, int out_size) {
  (void)in_sizes; (void)n_in; (void)out_size;
  static CUtensorMap tm_x, tm_w1, tm_w2;
  static const void* cached_w1 = nullptr; static const void* cached_w2 = nullptr; static const void* cached_x = nullptr;
  const void* w1 = d_in[1]; const void* w2 = d_in[3]; const void* xp = d_in[0];
  if (cached_w1 != w1 || cached_w2 != w2 || cached_x != xp) {
    void* fn = nullptr; cudaDriverEntryPointQueryResult st;
    cudaGetDriverEntryPoint("cuTensorMapEncodeTiled", &fn, cudaEnableDefault, &st);
    EncodeFn enc = (EncodeFn)fn;
    {
      cuuint64_t dims[3] = {32, (cuuint64_t)D_MOD, (cuuint64_t)(F_HID / 32)};
      cuuint64_t strides[2] = {(cuuint64_t)F_HID * 2, 64};
      cuuint32_t box[3] = {32, 64, 7};
      cuuint32_t es[3] = {1, 1, 1};
      enc(&tm_w1, CU_TENSOR_MAP_DATA_TYPE_BFLOAT16, 3, const_cast<void*>(w1), dims, strides, box, es,
          CU_TENSOR_MAP_INTERLEAVE_NONE, CU_TENSOR_MAP_SWIZZLE_64B, CU_TENSOR_MAP_L2_PROMOTION_L2_128B, CU_TENSOR_MAP_FLOAT_OOB_FILL_NONE);
    }
    {
      cuuint64_t dims[2] = {(cuuint64_t)D_MOD, (cuuint64_t)F_HID};
      cuuint64_t strides[1] = {(cuuint64_t)D_MOD * 2};
      cuuint32_t box[2] = {64, 224};
      cuuint32_t es[2] = {1, 1};
      enc(&tm_w2, CU_TENSOR_MAP_DATA_TYPE_BFLOAT16, 2, const_cast<void*>(w2), dims, strides, box, es,
          CU_TENSOR_MAP_INTERLEAVE_NONE, CU_TENSOR_MAP_SWIZZLE_128B, CU_TENSOR_MAP_L2_PROMOTION_L2_128B, CU_TENSOR_MAP_FLOAT_OOB_FILL_NONE);
    }
    {
      cuuint64_t dims[2] = {(cuuint64_t)D_MOD, (cuuint64_t)S_TOK};
      cuuint64_t strides[1] = {(cuuint64_t)D_MOD * 2};
      cuuint32_t box[2] = {64, 32};
      cuuint32_t es[2] = {1, 1};
      enc(&tm_x, CU_TENSOR_MAP_DATA_TYPE_BFLOAT16, 2, const_cast<void*>(xp), dims, strides, box, es,
          CU_TENSOR_MAP_INTERLEAVE_NONE, CU_TENSOR_MAP_SWIZZLE_128B, CU_TENSOR_MAP_L2_PROMOTION_L2_128B, CU_TENSOR_MAP_FLOAT_OOB_FILL_NONE);
    }
    cudaFuncSetAttribute(fused_mlp_kernel, cudaFuncAttributeMaxDynamicSharedMemorySize, SMEM_TOTAL);
    cached_w1 = w1; cached_w2 = w2; cached_x = xp;
  }
  fused_mlp_kernel<<<NMB * NSPLIT, NTHREADS, SMEM_TOTAL>>>(tm_x, tm_w1, tm_w2,
      (const __nv_bfloat16*)d_in[2], (const __nv_bfloat16*)d_in[4], (__nv_bfloat16*)d_out);
}
```

```cpp
#include <cuda_runtime.h>
#include <cuda_bf16.h>
#include <cuda.h>
#include <stdint.h>

namespace {

constexpr int S_TOK = 2048, D_MOD = 512, F_HID = 1792;
constexpr int BM = 128, NSPLIT = 8, BF = F_HID / NSPLIT;
constexpr int BN2 = D_MOD / NSPLIT;
constexpr int NMB = S_TOK / BM;
constexpr int STAGE_BYTES = 28672;
constexpr int Y_BYTES = BM * D_MOD * 2;
constexpr int NRING = 3;
constexpr int OFF_RING = Y_BYTES;
constexpr int OFF_DSLOT = 2 * STAGE_BYTES;
constexpr int DSLOT_BYTES = 16384;
constexpr int OFF_BAR = OFF_RING + NRING * STAGE_BYTES;
constexpr int OFF_RSTD = OFF_BAR + 512;
constexpr int OFF_B1 = OFF_RSTD + 512;
constexpr int OFF_B2 = OFF_B1 + 1024;
constexpr int SMEM_TOTAL = OFF_B2 + 256;
constexpr int NTHREADS = 384;

__device__ uint4 g_part[(size_t)NMB * NSPLIT * 3 * 1024];
__device__ unsigned int g_epoch[NMB * NSPLIT];

#define TS(role, idx) do {} while (0)
#define TSC(idx) do {} while (0)

__device__ __forceinline__ uint32_t smem_u32(const void* p) { return (uint32_t)__cvta_generic_to_shared(p); }
__device__ __forceinline__ uint32_t mapa(uint32_t a, uint32_t r) {
  uint32_t d; asm volatile("mapa.shared::cluster.u32 %0, %1, %2;" : "=r"(d) : "r"(a), "r"(r)); return d;
}
__device__ __forceinline__ void mbar_init(uint32_t bar, uint32_t cnt) {
  asm volatile("mbarrier.init.shared::cta.b64 [%0], %1;" :: "r"(bar), "r"(cnt) : "memory");
}
__device__ __forceinline__ void mbar_expect_tx(uint32_t bar, uint32_t bytes) {
  asm volatile("mbarrier.arrive.expect_tx.shared::cta.b64 _, [%0], %1;" :: "r"(bar), "r"(bytes) : "memory");
}
__device__ __forceinline__ void mbar_arrive(uint32_t bar) {
  asm volatile("mbarrier.arrive.shared::cta.b64 _, [%0];" :: "r"(bar) : "memory");
}
__device__ __forceinline__ void mbar_arrive_remote(uint32_t rbar) {
  asm volatile("mbarrier.arrive.release.cluster.shared::cluster.b64 _, [%0];" :: "r"(rbar) : "memory");
}
__device__ __forceinline__ void mbar_wait(uint32_t bar, uint32_t parity) {
  uint32_t done = 0; uint32_t it = 0;
  while (true) {
    asm volatile("{\n.reg .pred p;\nmbarrier.try_wait.parity.shared::cta.b64 p, [%1], %2;\nselp.u32 %0, 1, 0, p;\n}"
                 : "=r"(done) : "r"(bar), "r"(parity) : "memory");
    if (done) break;
    if (++it > (1u << 22)) asm volatile("trap;");
  }
}
__device__ __forceinline__ void mbar_wait_cluster(uint32_t bar, uint32_t parity) {
  uint32_t done = 0; uint32_t it = 0;
  while (true) {
    asm volatile("{\n.reg .pred p;\nmbarrier.try_wait.parity.acquire.cluster.shared::cta.b64 p, [%1], %2;\nselp.u32 %0, 1, 0, p;\n}"
                 : "=r"(done) : "r"(bar), "r"(parity) : "memory");
    if (done) break;
    if (++it > (1u << 22)) asm volatile("trap;");
  }
}
__device__ __forceinline__ void tma_load_3d(uint32_t dst, const CUtensorMap* tm, int c0, int c1, int c2, uint32_t bar) {
  asm volatile("cp.async.bulk.tensor.3d.shared::cluster.global.mbarrier::complete_tx::bytes [%0], [%1, {%3, %4, %5}], [%2];"
               :: "r"(dst), "l"(tm), "r"(bar), "r"(c0), "r"(c1), "r"(c2) : "memory");
}
__device__ __forceinline__ void tma_load_2d(uint32_t dst, const CUtensorMap* tm, int c0, int c1, uint32_t bar) {
  asm volatile("cp.async.bulk.tensor.2d.shared::cluster.global.mbarrier::complete_tx::bytes [%0], [%1, {%3, %4}], [%2];"
               :: "r"(dst), "l"(tm), "r"(bar), "r"(c0), "r"(c1) : "memory");
}
__device__ __forceinline__ void tma_prefetch_3d(const CUtensorMap* tm, int c0, int c1, int c2) {
  asm volatile("cp.async.bulk.prefetch.tensor.3d.L2.global.tile [%0, {%1, %2, %3}];" :: "l"(tm), "r"(c0), "r"(c1), "r"(c2) : "memory");
}
__device__ __forceinline__ void tma_prefetch_2d(const CUtensorMap* tm, int c0, int c1) {
  asm volatile("cp.async.bulk.prefetch.tensor.2d.L2.global.tile [%0, {%1, %2}];" :: "l"(tm), "r"(c0), "r"(c1) : "memory");
}
__device__ __forceinline__ void wg_fence() { asm volatile("wgmma.fence.sync.aligned;" ::: "memory"); }
__device__ __forceinline__ void wg_commit() { asm volatile("wgmma.commit_group.sync.aligned;" ::: "memory"); }
template <int N> __device__ __forceinline__ void wg_wait() { asm volatile("wgmma.wait_group.sync.aligned %0;" :: "n"(N) : "memory"); }
template <int N> __device__ __forceinline__ void reg_fence(float (&d)[N]) {
#pragma unroll
  for (int i = 0; i < N; i++) asm volatile("" : "+f"(d[i]) :: "memory");
}
__device__ __forceinline__ uint64_t make_desc(uint32_t addr, uint32_t lbo, uint32_t sbo, uint32_t lt) {
  return (uint64_t)((addr & 0x3FFFF) >> 4) | ((uint64_t)(lbo >> 4) << 16) | ((uint64_t)(sbo >> 4) << 32) | ((uint64_t)lt << 62);
}
__device__ __forceinline__ uint32_t pack_bf16(float lo, float hi) {
  uint32_t r; asm("cvt.rn.bf16x2.f32 %0, %1, %2;" : "=r"(r) : "f"(hi), "f"(lo)); return r;
}
__device__ __forceinline__ float bf_lo(uint32_t v) { return __uint_as_float(v << 16); }
__device__ __forceinline__ float bf_hi(uint32_t v) { return __uint_as_float(v & 0xffff0000u); }
__device__ __forceinline__ float bf16r(float v) { return __bfloat162float(__float2bfloat16_rn(v)); }
__device__ __forceinline__ uint32_t hadd2_bf(uint32_t a, uint32_t b) {
  uint32_t r; asm("add.rn.bf16x2 %0, %1, %2;" : "=r"(r) : "r"(a), "r"(b)); return r;
}
__device__ __forceinline__ uint32_t hsub2_bf(uint32_t a, uint32_t b) {
  uint32_t r; asm("sub.rn.bf16x2 %0, %1, %2;" : "=r"(r) : "r"(a), "r"(b)); return r;
}
__device__ __forceinline__ float gelu_tanh(float u) {
  float inner = u * fmaf(0.035677408136300125f, u * u, 0.7978845608028654f);
  float th; asm("tanh.approx.f32 %0, %1;" : "=f"(th) : "f"(inner));
  float hu = 0.5f * u;
  return fmaf(hu, th, hu);
}

__device__ __forceinline__ void wgmma_ss_n224(float (&d)[112], uint64_t descA, uint64_t descB, int scaleD) {
  asm volatile("{\n.reg .pred p;\nsetp.ne.b32 p, %114, 0;\n"
    "wgmma.mma_async.sync.aligned.m64n224k16.f32.bf16.bf16 {%0, %1, %2, %3, %4, %5, %6, %7, %8, %9, %10, %11, %12, %13, %14, %15, %16, %17, %18, %19, %20, %21, %22, %23, %24, %25, %26, %27, %28, %29, %30, %31, %32, %33, %34, %35, %36, %37, %38, %39, %40, %41, %42, %43, %44, %45, %46, %47, %48, %49, %50, %51, %52, %53, %54, %55, %56, %57, %58, %59, %60, %61, %62, %63, %64, %65, %66, %67, %68, %69, %70, %71, %72, %73, %74, %75, %76, %77, %78, %79, %80, %81, %82, %83, %84, %85, %86, %87, %88, %89, %90, %91, %92, %93, %94, %95, %96, %97, %98, %99, %100, %101, %102, %103, %104, %105, %106, %107, %108, %109, %110, %111}, %112, %113, p, 1, 1, 0, 1;\n}\n"
    : "+f"(d[0]), "+f"(d[1]), "+f"(d[2]), "+f"(d[3]), "+f"(d[4]), "+f"(d[5]), "+f"(d[6]), "+f"(d[7]), "+f"(d[8]), "+f"(d[9]), "+f"(d[10]), "+f"(d[11]), "+f"(d[12]), "+f"(d[13]), "+f"(d[14]), "+f"(d[15]), "+f"(d[16]), "+f"(d[17]), "+f"(d[18]), "+f"(d[19]), "+f"(d[20]), "+f"(d[21]), "+f"(d[22]), "+f"(d[23]), "+f"(d[24]), "+f"(d[25]), "+f"(d[26]), "+f"(d[27]), "+f"(d[28]), "+f"(d[29]), "+f"(d[30]), "+f"(d[31]), "+f"(d[32]), "+f"(d[33]), "+f"(d[34]), "+f"(d[35]), "+f"(d[36]), "+f"(d[37]), "+f"(d[38]), "+f"(d[39]), "+f"(d[40]), "+f"(d[41]), "+f"(d[42]), "+f"(d[43]), "+f"(d[44]), "+f"(d[45]), "+f"(d[46]), "+f"(d[47]), "+f"(d[48]), "+f"(d[49]), "+f"(d[50]), "+f"(d[51]), "+f"(d[52]), "+f"(d[53]), "+f"(d[54]), "+f"(d[55]), "+f"(d[56]), "+f"(d[57]), "+f"(d[58]), "+f"(d[59]), "+f"(d[60]), "+f"(d[61]), "+f"(d[62]), "+f"(d[63]), "+f"(d[64]), "+f"(d[65]), "+f"(d[66]), "+f"(d[67]), "+f"(d[68]), "+f"(d[69]), "+f"(d[70]), "+f"(d[71]), "+f"(d[72]), "+f"(d[73]), "+f"(d[74]), "+f"(d[75]), "+f"(d[76]), "+f"(d[77]), "+f"(d[78]), "+f"(d[79]), "+f"(d[80]), "+f"(d[81]), "+f"(d[82]), "+f"(d[83]), "+f"(d[84]), "+f"(d[85]), "+f"(d[86]), "+f"(d[87]), "+f"(d[88]), "+f"(d[89]), "+f"(d[90]), "+f"(d[91]), "+f"(d[92]), "+f"(d[93]), "+f"(d[94]), "+f"(d[95]), "+f"(d[96]), "+f"(d[97]), "+f"(d[98]), "+f"(d[99]), "+f"(d[100]), "+f"(d[101]), "+f"(d[102]), "+f"(d[103]), "+f"(d[104]), "+f"(d[105]), "+f"(d[106]), "+f"(d[107]), "+f"(d[108]), "+f"(d[109]), "+f"(d[110]), "+f"(d[111])
    : "l"(descA), "l"(descB), "r"(scaleD));
}

__device__ __forceinline__ void wgmma_rs_n64(float (&d)[32], const uint32_t (&a)[4], uint64_t descB, int scaleD) {
  asm volatile("{\n.reg .pred p;\nsetp.ne.b32 p, %37, 0;\n"
    "wgmma.mma_async.sync.aligned.m64n64k16.f32.bf16.bf16 {%0, %1, %2, %3, %4, %5, %6, %7, %8, %9, %10, %11, %12, %13, %14, %15, %16, %17, %18, %19, %20, %21, %22, %23, %24, %25, %26, %27, %28, %29, %30, %31}, {%32, %33, %34, %35}, %36, p, 1, 1, 1;\n}\n"
    : "+f"(d[0]), "+f"(d[1]), "+f"(d[2]), "+f"(d[3]), "+f"(d[4]), "+f"(d[5]), "+f"(d[6]), "+f"(d[7]), "+f"(d[8]), "+f"(d[9]), "+f"(d[10]), "+f"(d[11]), "+f"(d[12]), "+f"(d[13]), "+f"(d[14]), "+f"(d[15]), "+f"(d[16]), "+f"(d[17]), "+f"(d[18]), "+f"(d[19]), "+f"(d[20]), "+f"(d[21]), "+f"(d[22]), "+f"(d[23]), "+f"(d[24]), "+f"(d[25]), "+f"(d[26]), "+f"(d[27]), "+f"(d[28]), "+f"(d[29]), "+f"(d[30]), "+f"(d[31])
    : "r"(a[0]), "r"(a[1]), "r"(a[2]), "r"(a[3]), "l"(descB), "r"(scaleD));
}

__host__ __device__ constexpr int step_kind(int i) { return (i == 0 || i == 1 || i == 3 || i == 6) ? 0 : (i == 7 ? 2 : 1); }
__host__ __device__ constexpr int step_k(int i) { return i == 0 ? 0 : i == 1 ? 1 : i == 2 ? 0 : i == 3 ? 2 : i == 4 ? 1 : i == 5 ? 2 : 3; }
__device__ __forceinline__ int step_slice(int i, int j) {
  const int kind = step_kind(i), k = step_k(i);
  const int base = (kind == 0) ? (j ^ 1) : j;
  return (k == 3) ? base : ((base + 2 * (k + 1)) & 7);
}

__global__ void __cluster_dims__(2, 1, 1) __launch_bounds__(NTHREADS, 1)
fused_mlp_kernel(const __grid_constant__ CUtensorMap tm_x, const __grid_constant__ CUtensorMap tm_w1, const __grid_constant__ CUtensorMap tm_w2,
                 const __nv_bfloat16* __restrict__ b1, const __nv_bfloat16* __restrict__ b2, __nv_bfloat16* __restrict__ out)
{
  extern __shared__ __align__(1024) unsigned char smem[];
  const uint32_t sbase = smem_u32(smem);
  const uint32_t bar_full = sbase + OFF_BAR;
  const uint32_t bar_cons = sbase + OFF_BAR + 128;
  const uint32_t bar_x = sbase + OFF_BAR + 256;
  const uint32_t bar_dfull = sbase + OFF_BAR + 272;
  const uint32_t bar_peer = sbase + OFF_BAR + 304;
  const int tid = threadIdx.x, warp = tid >> 5, lane = tid & 31;
  const int mb = blockIdx.x >> 3, j = blockIdx.x & 7;

  TSC(0);
  if (warp == 8 && lane == 0) {
    for (int i = 0; i < 16; i++) { mbar_init(bar_full + 8 * i, 1); mbar_init(bar_cons + 8 * i, 2); }
    for (int i = 0; i < 2; i++) mbar_init(bar_x + 8 * i, 1);
    for (int i = 0; i < 4; i++) mbar_init(bar_dfull + 8 * i, 1);
    mbar_init(bar_peer, 2);
    asm volatile("fence.mbarrier_init.release.cluster;" ::: "memory");
    asm volatile("fence.proxy.async.shared::cta;" ::: "memory");
    mbar_expect_tx(bar_x, 65536);
    tma_load_3d(sbase, &tm_x, 0, mb * BM, 0, bar_x);
    mbar_expect_tx(bar_full, STAGE_BYTES);
    tma_load_3d(sbase + OFF_RING, &tm_w1, 0, 0, j * 7, bar_full);
    mbar_expect_tx(bar_x + 8, 65536);
    tma_load_3d(sbase + 65536, &tm_x, 0, mb * BM + 64, 0, bar_x + 8);
    for (int i = 1; i < NRING; i++) {
      mbar_expect_tx(bar_full + 8 * i, STAGE_BYTES);
      tma_load_3d(sbase + OFF_RING + i * STAGE_BYTES, &tm_w1, 0, i * 64, j * 7, bar_full + 8 * i);
    }
    for (int i = 0; i < 4; i++) mbar_expect_tx(bar_dfull + 8 * i, DSLOT_BYTES);
    if (mb < 8) { if (mb >= NRING) tma_prefetch_3d(&tm_w1, 0, mb * 64, j * 7); }
    else tma_prefetch_2d(&tm_w2, (mb - 8) * 64, j * BF);
    TS(2, 1);
  }
  asm volatile("barrier.cluster.arrive.release.aligned;\nbarrier.cluster.wait.acquire.aligned;" ::: "memory");

  if (warp >= 8) {
    asm volatile("setmaxnreg.dec.sync.aligned.u32 40;");
    if (warp == 8 && lane == 0) {
      for (int i = NRING; i < 16; i++) {
        uint32_t dst;
        if (i < 11)      { mbar_wait(bar_cons + 8 * (i - NRING), 0); dst = sbase + OFF_RING + (i % NRING) * STAGE_BYTES; }
        else if (i < 13) { dst = sbase + (i - 11) * STAGE_BYTES; }
        else             { mbar_wait(bar_cons + 8 * (i - 5), 0); dst = sbase + OFF_RING + ((i - 5) % NRING) * STAGE_BYTES; }
        TS(2, i);
        mbar_expect_tx(bar_full + 8 * i, STAGE_BYTES);
        if (i < 8) tma_load_3d(dst, &tm_w1, 0, i * 64, j * 7, bar_full + 8 * i);
        else tma_load_2d(dst, &tm_w2, step_slice(i - 8, j) * BN2, j * BF, bar_full + 8 * i);
      }
    }
  } else {
    asm volatile("setmaxnreg.inc.sync.aligned.u32 232;");
    const int wg = warp >> 2, w4 = warp & 3, t128 = tid & 127;
    const int q = lane & 3, g = lane >> 2;
    float* rstd_s = reinterpret_cast<float*>(smem + OFF_RSTD);
    uint32_t* b1s = reinterpret_cast<uint32_t*>(smem + OFF_B1 + wg * 512);
    uint32_t* b2s = reinterpret_cast<uint32_t*>(smem + OFF_B2 + wg * 128);
    uint32_t bias_a = 0, bias_b = 0;
    if (t128 < BF / 2) bias_a = reinterpret_cast<const uint32_t*>(b1 + j * BF)[t128];
    if (t128 < BN2 / 2) bias_b = reinterpret_cast<const uint32_t*>(b2 + j * BN2)[t128];
    const uint32_t epoch = g_epoch[blockIdx.x];

    float vpart[16];
    unsigned char* ywg = smem + wg * 65536;
    mbar_wait(bar_x + 8 * wg, 0);
    TSC(25);
#pragma unroll
    for (int bt = 0; bt < 2; bt++) {
      uint4 xa[8], xb[8];
      float s[8];
#pragma unroll
      for (int r = 0; r < 8; r++) {
        const int row = w4 * 16 + bt * 8 + r;
        const uint32_t ad = (uint32_t)((lane >> 3) * 8192 + row * 128 + (((lane & 7) ^ r) << 4));
        xa[r] = *reinterpret_cast<const uint4*>(ywg + ad);
        xb[r] = *reinterpret_cast<const uint4*>(ywg + ad + 4 * 8192);
      }
#pragma unroll
      for (int r = 0; r < 8; r++) {
        const uint4 a = xa[r], b = xb[r];
        s[r] = ((bf_lo(a.x) + bf_hi(a.x)) + (bf_lo(a.y) + bf_hi(a.y))) + ((bf_lo(a.z) + bf_hi(a.z)) + (bf_lo(a.w) + bf_hi(a.w)))
             + ((bf_lo(b.x) + bf_hi(b.x)) + (bf_lo(b.y) + bf_hi(b.y))) + ((bf_lo(b.z) + bf_hi(b.z)) + (bf_lo(b.w) + bf_hi(b.w)));
      }
#pragma unroll
      for (int o = 16; o > 0; o >>= 1)
#pragma unroll
        for (int r = 0; r < 8; r++) s[r] += __shfl_xor_sync(0xffffffffu, s[r], o);
#pragma unroll
      for (int r = 0; r < 8; r++) {
        asm volatile("" : "+r"(xa[r].x), "+r"(xa[r].y), "+r"(xa[r].z), "+r"(xa[r].w), "+r"(xb[r].x), "+r"(xb[r].y), "+r"(xb[r].z), "+r"(xb[r].w));
      }
#pragma unroll
      for (int r = 0; r < 8; r++) {
        const int row = w4 * 16 + bt * 8 + r;
        const uint32_t ad = (uint32_t)((lane >> 3) * 8192 + row * 128 + (((lane & 7) ^ r) << 4));
        const uint4 a = xa[r], b = xb[r];
        const float mean = s[r] * (1.0f / D_MOD);
        const uint32_t m2 = pack_bf16(mean, mean);
        uint4 d0, d1;
        d0.x = hsub2_bf(a.x, m2); d0.y = hsub2_bf(a.y, m2); d0.z = hsub2_bf(a.z, m2); d0.w = hsub2_bf(a.w, m2);
        d1.x = hsub2_bf(b.x, m2); d1.y = hsub2_bf(b.y, m2); d1.z = hsub2_bf(b.z, m2); d1.w = hsub2_bf(b.w, m2);
        *reinterpret_cast<uint4*>(ywg + ad) = d0;
        *reinterpret_cast<uint4*>(ywg + ad + 4 * 8192) = d1;
        const uint32_t w[8] = {a.x, a.y, a.z, a.w, b.x, b.y, b.z, b.w};
        float v0 = 0.f, v1 = 0.f;
#pragma unroll
        for (int e = 0; e < 8; e++) { float p = bf_lo(w[e]) - mean, t = bf_hi(w[e]) - mean; v0 = fmaf(p, p, v0); v1 = fmaf(t, t, v1); }
        vpart[bt * 8 + r] = v0 + v1;
      }
    }
    if (t128 < BF / 2) b1s[t128] = bias_a;
    if (t128 < BN2 / 2) b2s[t128] = bias_b;
    TSC(1);
    asm volatile("fence.proxy.async.shared::cta;" ::: "memory");
    if (wg == 0) asm volatile("bar.sync 1, 128;" ::: "memory"); else asm volatile("bar.sync 2, 128;" ::: "memory");
    TSC(2);

    uint32_t h[14][4];
    {
      float acc[112];
#pragma unroll
      for (int kb = 0; kb < 8; kb++) {
        mbar_wait(bar_full + 8 * kb, 0);
        TSC(3 + kb);
        wg_fence();
        const uint32_t abase = sbase + wg * 65536 + kb * 8192;
        const uint32_t bbase = sbase + OFF_RING + (kb % NRING) * STAGE_BYTES;
#pragma unroll
        for (int kk = 0; kk < 4; kk++) {
          wgmma_ss_n224(acc, make_desc(abase + kk * 32, 16, 1024, 1), make_desc(bbase + kk * 1024, 4096, 512, 2), (kb | kk) != 0);
        }
        wg_commit();
        if (kb == 0) {
#pragma unroll
          for (int o = 16; o > 0; o >>= 1)
#pragma unroll
            for (int r = 0; r < 16; r++) vpart[r] += __shfl_xor_sync(0xffffffffu, vpart[r], o);
          float vs = vpart[0];
#pragma unroll
          for (int r = 1; r < 16; r++) vs = (lane == r) ? vpart[r] : vs;
          const float vb = bf16r(vs * (1.0f / D_MOD));
          const float sd = bf16r(sqrtf(bf16r(vb + 1e-5f)));
          if (lane < 16) rstd_s[wg * 64 + w4 * 16 + lane] = 1.0f / sd;
          __syncwarp();
        }
        if (kb > 0) { wg_wait<1>(); if (t128 == 0) mbar_arrive(bar_cons + 8 * (kb - 1)); }
      }
      wg_wait<0>();
      reg_fence(acc);
      if (t128 == 0) { mbar_arrive(bar_cons + 8 * 7); mbar_arrive_remote(mapa(bar_peer, (j & 1) ^ 1)); }
      TSC(11);

      const int row0 = wg * 64 + w4 * 16 + g;
      const float r0 = rstd_s[row0], r1 = rstd_s[row0 + 8];
#pragma unroll
      for (int i = 0; i < 28; i++) {
        const uint32_t bb = b1s[i * 4 + q];
        uint32_t p0 = hadd2_bf(pack_bf16(acc[4 * i] * r0, acc[4 * i + 1] * r0), bb);
        uint32_t p1 = hadd2_bf(pack_bf16(acc[4 * i + 2] * r1, acc[4 * i + 3] * r1), bb);
        h[i >> 1][(i & 1) * 2 + 0] = pack_bf16(gelu_tanh(bf_lo(p0)), gelu_tanh(bf_hi(p0)));
        h[i >> 1][(i & 1) * 2 + 1] = pack_bf16(gelu_tanh(bf_lo(p1)), gelu_tanh(bf_hi(p1)));
      }
    }

    const uint32_t par = (epoch + 1) & 1;
    float acc2[2][32];
    float sum[32];
#pragma unroll
    for (int i = 0; i < 32; i++) sum[i] = 0.f;
    uint4 pf[4];
    const uint32_t peer_slot = mapa(sbase + OFF_DSLOT + (wg * 512 + t128) * 16, (j & 1) ^ 1);
    const uint32_t peer_dfull = mapa(bar_dfull, (j & 1) ^ 1);
    const uint4* my_slot = reinterpret_cast<const uint4*>(smem + OFF_DSLOT) + wg * 512 + t128;
    const uint4* in_part = &g_part[(size_t)((mb * NSPLIT + j) * 3) * 1024 + wg * 512 + t128];
    auto ld_part = [&](const uint4* p) {
      uint4 v;
      asm volatile("ld.relaxed.gpu.global.v4.u32 {%0, %1, %2, %3}, [%4];" : "=r"(v.x), "=r"(v.y), "=r"(v.z), "=r"(v.w) : "l"(p) : "memory");
      return v;
    };
    auto prefetch = [&](int k) {
#pragma unroll
      for (int c = 0; c < 4; c++) pf[c] = ld_part(in_part + k * 1024 + c * 128);
    };
    auto consume = [&](int k) {
#pragma unroll
      for (int c = 0; c < 4; c++) {
        uint4 v = pf[c];
        uint32_t it = 0;
        while ((((v.x ^ par) | (v.y ^ par) | (v.z ^ par) | (v.w ^ par)) & 1u) != 0) {
          v = ld_part(in_part + k * 1024 + c * 128);
          if (++it > (1u << 20)) asm volatile("trap;");
        }
        sum[c * 8 + 0] += bf_lo(v.x & ~1u); sum[c * 8 + 1] += bf_hi(v.x);
        sum[c * 8 + 2] += bf_lo(v.y & ~1u); sum[c * 8 + 3] += bf_hi(v.y);
        sum[c * 8 + 4] += bf_lo(v.z & ~1u); sum[c * 8 + 5] += bf_hi(v.z);
        sum[c * 8 + 6] += bf_lo(v.w & ~1u); sum[c * 8 + 7] += bf_hi(v.w);
      }
    };
    auto post = [&](int st, float (&a)[32]) {
      const int kind = step_kind(st), k = step_k(st);
      if (kind == 0) {
        if (st == 0) mbar_wait_cluster(bar_peer, 0);
#pragma unroll
        for (int c = 0; c < 4; c++) {
          asm volatile("st.async.weak.shared::cluster.mbarrier::complete_tx::bytes.v4.b32 [%0], {%1,%2,%3,%4}, [%5];"
            :: "r"(peer_slot + k * DSLOT_BYTES + c * 2048),
               "r"(pack_bf16(a[c * 8 + 0], a[c * 8 + 1])), "r"(pack_bf16(a[c * 8 + 2], a[c * 8 + 3])),
               "r"(pack_bf16(a[c * 8 + 4], a[c * 8 + 5])), "r"(pack_bf16(a[c * 8 + 6], a[c * 8 + 7])),
               "r"(peer_dfull + 8 * k) : "memory");
        }
      } else {
        mbar_wait_cluster(bar_dfull + 8 * k, 0);
        const int dest = (j + 2 * (k + 1)) & 7;
        uint4* p = &g_part[(size_t)((mb * NSPLIT + dest) * 3 + k) * 1024 + wg * 512 + t128];
#pragma unroll
        for (int c = 0; c < 4; c++) {
          const uint4 d = my_slot[k * 1024 + c * 128];
          uint4 v;
          v.x = (pack_bf16(a[c * 8 + 0] + bf_lo(d.x), a[c * 8 + 1] + bf_hi(d.x)) & ~1u) | par;
          v.y = (pack_bf16(a[c * 8 + 2] + bf_lo(d.y), a[c * 8 + 3] + bf_hi(d.y)) & ~1u) | par;
          v.z = (pack_bf16(a[c * 8 + 4] + bf_lo(d.z), a[c * 8 + 5] + bf_hi(d.z)) & ~1u) | par;
          v.w = (pack_bf16(a[c * 8 + 6] + bf_lo(d.w), a[c * 8 + 7] + bf_hi(d.w)) & ~1u) | par;
          __stcg(p + c * 128, v);
        }
      }
    };
#pragma unroll
    for (int i = 0; i < 8; i++) {
      TSC(12 + i);
      mbar_wait(bar_full + 8 * (8 + i), 0);
      uint32_t bbase;
      if (i < 3) bbase = sbase + OFF_RING + ((8 + i) % NRING) * STAGE_BYTES;
      else if (i < 5) bbase = sbase + (i - 3) * STAGE_BYTES;
      else bbase = sbase + OFF_RING + ((8 + i - 5) % NRING) * STAGE_BYTES;
      wg_fence();
#pragma unroll
      for (int ks = 0; ks < 14; ks++) {
        wgmma_rs_n64(acc2[i & 1], h[ks], make_desc(bbase + ks * 2048, 16, 1024, 1), ks != 0);
      }
      wg_commit();
      if (i > 0) {
        wg_wait<1>();
        reg_fence(acc2[(i - 1) & 1]);
        if (i <= 3 && t128 == 0) mbar_arrive(bar_cons + 8 * (8 + i - 1));
        post(i - 1, acc2[(i - 1) & 1]);
      }
      if (i == 6) prefetch(0);
      if (i == 7) { consume(0); prefetch(1); }
    }
    consume(1);
    prefetch(2);
    mbar_wait_cluster(bar_dfull + 8 * 3, 0);
#pragma unroll
    for (int c = 0; c < 4; c++) {
      const uint4 d = my_slot[3 * 1024 + c * 128];
      sum[c * 8 + 0] += bf_lo(d.x); sum[c * 8 + 1] += bf_hi(d.x); sum[c * 8 + 2] += bf_lo(d.y); sum[c * 8 + 3] += bf_hi(d.y);
      sum[c * 8 + 4] += bf_lo(d.z); sum[c * 8 + 5] += bf_hi(d.z); sum[c * 8 + 6] += bf_lo(d.w); sum[c * 8 + 7] += bf_hi(d.w);
    }
    wg_wait<0>();
    reg_fence(acc2[1]);
    TSC(20);
    consume(2);
    TSC(21);
    if (tid == 0) g_epoch[blockIdx.x] = epoch + 1;

    {
      const int row0 = mb * BM + wg * 64 + w4 * 16 + g;
      uint32_t* o0 = reinterpret_cast<uint32_t*>(out + (size_t)row0 * D_MOD + j * BN2) + q;
      uint32_t* o1 = o0 + 8 * D_MOD / 2;
#pragma unroll
      for (int i = 0; i < 8; i++) {
        const uint32_t bb = b2s[i * 4 + q];
        o0[i * 4] = hadd2_bf(pack_bf16(acc2[1][4 * i] + sum[4 * i], acc2[1][4 * i + 1] + sum[4 * i + 1]), bb);
        o1[i * 4] = hadd2_bf(pack_bf16(acc2[1][4 * i + 2] + sum[4 * i + 2], acc2[1][4 * i + 3] + sum[4 * i + 3]), bb);
      }
    }
  }
}

typedef CUresult (*EncodeFn)(CUtensorMap*, CUtensorMapDataType, cuuint32_t, void*, const cuuint64_t*, const cuuint64_t*,
                             const cuuint32_t*, const cuuint32_t*, CUtensorMapInterleave, CUtensorMapSwizzle,
                             CUtensorMapL2promotion, CUtensorMapFloatOOBfill);

}

extern "C" void kernel_launch(void* const* d_in, const int* in_sizes, int n_in, void* d_out, int out_size) {
  (void)in_sizes; (void)n_in; (void)out_size;
  static CUtensorMap tm_x, tm_w1, tm_w2;
  static const void* cached_w1 = nullptr; static const void* cached_w2 = nullptr; static const void* cached_x = nullptr;
  const void* w1 = d_in[1]; const void* w2 = d_in[3]; const void* xp = d_in[0];
  if (cached_w1 != w1 || cached_w2 != w2 || cached_x != xp) {
    void* fn = nullptr; cudaDriverEntryPointQueryResult st;
    cudaGetDriverEntryPoint("cuTensorMapEncodeTiled", &fn, cudaEnableDefault, &st);
    EncodeFn enc = (EncodeFn)fn;
    {
      cuuint64_t dims[3] = {64, (cuuint64_t)S_TOK, (cuuint64_t)(D_MOD / 64)};
      cuuint64_t strides[2] = {(cuuint64_t)D_MOD * 2, 128};
      cuuint32_t box[3] = {64, 64, 8};
      cuuint32_t es[3] = {1, 1, 1};
      enc(&tm_x, CU_TENSOR_MAP_DATA_TYPE_BFLOAT16, 3, const_cast<void*>(xp), dims, strides, box, es,
          CU_TENSOR_MAP_INTERLEAVE_NONE, CU_TENSOR_MAP_SWIZZLE_128B, CU_TENSOR_MAP_L2_PROMOTION_L2_128B, CU_TENSOR_MAP_FLOAT_OOB_FILL_NONE);
    }
    {
      cuuint64_t dims[3] = {32, (cuuint64_t)D_MOD, (cuuint64_t)(F_HID / 32)};
      cuuint64_t strides[2] = {(cuuint64_t)F_HID * 2, 64};
      cuuint32_t box[3] = {32, 64, 7};
      cuuint32_t es[3] = {1, 1, 1};
      enc(&tm_w1, CU_TENSOR_MAP_DATA_TYPE_BFLOAT16, 3, const_cast<void*>(w1), dims, strides, box, es,
          CU_TENSOR_MAP_INTERLEAVE_NONE, CU_TENSOR_MAP_SWIZZLE_64B, CU_TENSOR_MAP_L2_PROMOTION_L2_128B, CU_TENSOR_MAP_FLOAT_OOB_FILL_NONE);
    }
    {
      cuuint64_t dims[2] = {(cuuint64_t)D_MOD, (cuuint64_t)F_HID};
      cuuint64_t strides[1] = {(cuuint64_t)D_MOD * 2};
      cuuint32_t box[2] = {64, 224};
      cuuint32_t es[2] = {1, 1};
      enc(&tm_w2, CU_TENSOR_MAP_DATA_TYPE_BFLOAT16, 2, const_cast<void*>(w2), dims, strides, box, es,
          CU_TENSOR_MAP_INTERLEAVE_NONE, CU_TENSOR_MAP_SWIZZLE_128B, CU_TENSOR_MAP_L2_PROMOTION_L2_128B, CU_TENSOR_MAP_FLOAT_OOB_FILL_NONE);
    }
    cudaFuncSetAttribute(fused_mlp_kernel, cudaFuncAttributeMaxDynamicSharedMemorySize, SMEM_TOTAL);
    cached_w1 = w1; cached_w2 = w2; cached_x = xp;
  }
  fused_mlp_kernel<<<NMB * NSPLIT, NTHREADS, SMEM_TOTAL>>>(tm_x, tm_w1, tm_w2,
      (const __nv_bfloat16*)d_in[2], (const __nv_bfloat16*)d_in[4], (__nv_bfloat16*)d_out);
}
```

```cpp
#include <cuda_runtime.h>
#include <cuda_bf16.h>
#include <cuda.h>
#include <stdint.h>

namespace {

constexpr int S_TOK = 2048, D_MOD = 512, F_HID = 1792;
constexpr int BM = 128, NSPLIT = 8, BF = F_HID / NSPLIT;
constexpr int BN2 = D_MOD / NSPLIT;
constexpr int NMB = S_TOK / BM;
constexpr int STAGE_BYTES = 28672;
constexpr int Y_BYTES = BM * D_MOD * 2;
constexpr int NRING = 3;
constexpr int OFF_RING = Y_BYTES;
constexpr int OFF_DSLOT = 2 * STAGE_BYTES;
constexpr int DSLOT_BYTES = 16384;
constexpr int OFF_BAR = OFF_RING + NRING * STAGE_BYTES;
constexpr int OFF_RSTD = OFF_BAR + 512;
constexpr int OFF_B1 = OFF_RSTD + 512;
constexpr int OFF_B2 = OFF_B1 + 1024;
constexpr int SMEM_TOTAL = OFF_B2 + 256;
constexpr int NTHREADS = 384;

__device__ uint4 g_part[(size_t)NMB * NSPLIT * 3 * 1024];
__device__ unsigned int g_epoch[NMB * NSPLIT];

#define TS(role, idx) do {} while (0)
#define TSC(idx) do {} while (0)

__device__ __forceinline__ uint32_t smem_u32(const void* p) { return (uint32_t)__cvta_generic_to_shared(p); }
__device__ __forceinline__ uint32_t mapa(uint32_t a, uint32_t r) {
  uint32_t d; asm volatile("mapa.shared::cluster.u32 %0, %1, %2;" : "=r"(d) : "r"(a), "r"(r)); return d;
}
__device__ __forceinline__ void mbar_init(uint32_t bar, uint32_t cnt) {
  asm volatile("mbarrier.init.shared::cta.b64 [%0], %1;" :: "r"(bar), "r"(cnt) : "memory");
}
__device__ __forceinline__ void mbar_expect_tx(uint32_t bar, uint32_t bytes) {
  asm volatile("mbarrier.arrive.expect_tx.shared::cta.b64 _, [%0], %1;" :: "r"(bar), "r"(bytes) : "memory");
}
__device__ __forceinline__ void mbar_arrive(uint32_t bar) {
  asm volatile("mbarrier.arrive.shared::cta.b64 _, [%0];" :: "r"(bar) : "memory");
}
__device__ __forceinline__ void mbar_arrive_remote(uint32_t rbar) {
  asm volatile("mbarrier.arrive.release.cluster.shared::cluster.b64 _, [%0];" :: "r"(rbar) : "memory");
}
__device__ __forceinline__ void mbar_wait(uint32_t bar, uint32_t parity) {
  uint32_t done = 0; uint32_t it = 0;
  while (true) {
    asm volatile("{\n.reg .pred p;\nmbarrier.try_wait.parity.shared::cta.b64 p, [%1], %2;\nselp.u32 %0, 1, 0, p;\n}"
                 : "=r"(done) : "r"(bar), "r"(parity) : "memory");
    if (done) break;
    if (++it > (1u << 22)) asm volatile("trap;");
  }
}
__device__ __forceinline__ void mbar_wait_cluster(uint32_t bar, uint32_t parity) {
  uint32_t done = 0; uint32_t it = 0;
  while (true) {
    asm volatile("{\n.reg .pred p;\nmbarrier.try_wait.parity.acquire.cluster.shared::cta.b64 p, [%1], %2;\nselp.u32 %0, 1, 0, p;\n}"
                 : "=r"(done) : "r"(bar), "r"(parity) : "memory");
    if (done) break;
    if (++it > (1u << 22)) asm volatile("trap;");
  }
}
__device__ __forceinline__ void tma_load_3d(uint32_t dst, const CUtensorMap* tm, int c0, int c1, int c2, uint32_t bar) {
  asm volatile("cp.async.bulk.tensor.3d.shared::cluster.global.mbarrier::complete_tx::bytes [%0], [%1, {%3, %4, %5}], [%2];"
               :: "r"(dst), "l"(tm), "r"(bar), "r"(c0), "r"(c1), "r"(c2) : "memory");
}
__device__ __forceinline__ void tma_load_2d(uint32_t dst, const CUtensorMap* tm, int c0, int c1, uint32_t bar) {
  asm volatile("cp.async.bulk.tensor.2d.shared::cluster.global.mbarrier::complete_tx::bytes [%0], [%1, {%3, %4}], [%2];"
               :: "r"(dst), "l"(tm), "r"(bar), "r"(c0), "r"(c1) : "memory");
}
__device__ __forceinline__ void tma_prefetch_3d(const CUtensorMap* tm, int c0, int c1, int c2) {
  asm volatile("cp.async.bulk.prefetch.tensor.3d.L2.global.tile [%0, {%1, %2, %3}];" :: "l"(tm), "r"(c0), "r"(c1), "r"(c2) : "memory");
}
__device__ __forceinline__ void tma_prefetch_2d(const CUtensorMap* tm, int c0, int c1) {
  asm volatile("cp.async.bulk.prefetch.tensor.2d.L2.global.tile [%0, {%1, %2}];" :: "l"(tm), "r"(c0), "r"(c1) : "memory");
}
__device__ __forceinline__ void wg_fence() { asm volatile("wgmma.fence.sync.aligned;" ::: "memory"); }
__device__ __forceinline__ void wg_commit() { asm volatile("wgmma.commit_group.sync.aligned;" ::: "memory"); }
template <int N> __device__ __forceinline__ void wg_wait() { asm volatile("wgmma.wait_group.sync.aligned %0;" :: "n"(N) : "memory"); }
template <int N> __device__ __forceinline__ void reg_fence(float (&d)[N]) {
#pragma unroll
  for (int i = 0; i < N; i++) asm volatile("" : "+f"(d[i]) :: "memory");
}
__device__ __forceinline__ uint64_t make_desc(uint32_t addr, uint32_t lbo, uint32_t sbo, uint32_t lt) {
  return (uint64_t)((addr & 0x3FFFF) >> 4) | ((uint64_t)(lbo >> 4) << 16) | ((uint64_t)(sbo >> 4) << 32) | ((uint64_t)lt << 62);
}
__device__ __forceinline__ uint32_t pack_bf16(float lo, float hi) {
  uint32_t r; asm("cvt.rn.bf16x2.f32 %0, %1, %2;" : "=r"(r) : "f"(hi), "f"(lo)); return r;
}
__device__ __forceinline__ float bf_lo(uint32_t v) { return __uint_as_float(v << 16); }
__device__ __forceinline__ float bf_hi(uint32_t v) { return __uint_as_float(v & 0xffff0000u); }
__device__ __forceinline__ float bf16r(float v) { return __bfloat162float(__float2bfloat16_rn(v)); }
__device__ __forceinline__ uint32_t hadd2_bf(uint32_t a, uint32_t b) {
  uint32_t r; asm("add.rn.bf16x2 %0, %1, %2;" : "=r"(r) : "r"(a), "r"(b)); return r;
}
__device__ __forceinline__ uint32_t hsub2_bf(uint32_t a, uint32_t b) {
  uint32_t r; asm("sub.rn.bf16x2 %0, %1, %2;" : "=r"(r) : "r"(a), "r"(b)); return r;
}
__device__ __forceinline__ float gelu_tanh(float u) {
  float inner = u * fmaf(0.035677408136300125f, u * u, 0.7978845608028654f);
  float th; asm("tanh.approx.f32 %0, %1;" : "=f"(th) : "f"(inner));
  float hu = 0.5f * u;
  return fmaf(hu, th, hu);
}

__device__ __forceinline__ void wgmma_ss_n224(float (&d)[112], uint64_t descA, uint64_t descB, int scaleD) {
  asm volatile("{\n.reg .pred p;\nsetp.ne.b32 p, %114, 0;\n"
    "wgmma.mma_async.sync.aligned.m64n224k16.f32.bf16.bf16 {%0, %1, %2, %3, %4, %5, %6, %7, %8, %9, %10, %11, %12, %13, %14, %15, %16, %17, %18, %19, %20, %21, %22, %23, %24, %25, %26, %27, %28, %29, %30, %31, %32, %33, %34, %35, %36, %37, %38, %39, %40, %41, %42, %43, %44, %45, %46, %47, %48, %49, %50, %51, %52, %53, %54, %55, %56, %57, %58, %59, %60, %61, %62, %63, %64, %65, %66, %67, %68, %69, %70, %71, %72, %73, %74, %75, %76, %77, %78, %79, %80, %81, %82, %83, %84, %85, %86, %87, %88, %89, %90, %91, %92, %93, %94, %95, %96, %97, %98, %99, %100, %101, %102, %103, %104, %105, %106, %107, %108, %109, %110, %111}, %112, %113, p, 1, 1, 0, 1;\n}\n"
    : "+f"(d[0]), "+f"(d[1]), "+f"(d[2]), "+f"(d[3]), "+f"(d[4]), "+f"(d[5]), "+f"(d[6]), "+f"(d[7]), "+f"(d[8]), "+f"(d[9]), "+f"(d[10]), "+f"(d[11]), "+f"(d[12]), "+f"(d[13]), "+f"(d[14]), "+f"(d[15]), "+f"(d[16]), "+f"(d[17]), "+f"(d[18]), "+f"(d[19]), "+f"(d[20]), "+f"(d[21]), "+f"(d[22]), "+f"(d[23]), "+f"(d[24]), "+f"(d[25]), "+f"(d[26]), "+f"(d[27]), "+f"(d[28]), "+f"(d[29]), "+f"(d[30]), "+f"(d[31]), "+f"(d[32]), "+f"(d[33]), "+f"(d[34]), "+f"(d[35]), "+f"(d[36]), "+f"(d[37]), "+f"(d[38]), "+f"(d[39]), "+f"(d[40]), "+f"(d[41]), "+f"(d[42]), "+f"(d[43]), "+f"(d[44]), "+f"(d[45]), "+f"(d[46]), "+f"(d[47]), "+f"(d[48]), "+f"(d[49]), "+f"(d[50]), "+f"(d[51]), "+f"(d[52]), "+f"(d[53]), "+f"(d[54]), "+f"(d[55]), "+f"(d[56]), "+f"(d[57]), "+f"(d[58]), "+f"(d[59]), "+f"(d[60]), "+f"(d[61]), "+f"(d[62]), "+f"(d[63]), "+f"(d[64]), "+f"(d[65]), "+f"(d[66]), "+f"(d[67]), "+f"(d[68]), "+f"(d[69]), "+f"(d[70]), "+f"(d[71]), "+f"(d[72]), "+f"(d[73]), "+f"(d[74]), "+f"(d[75]), "+f"(d[76]), "+f"(d[77]), "+f"(d[78]), "+f"(d[79]), "+f"(d[80]), "+f"(d[81]), "+f"(d[82]), "+f"(d[83]), "+f"(d[84]), "+f"(d[85]), "+f"(d[86]), "+f"(d[87]), "+f"(d[88]), "+f"(d[89]), "+f"(d[90]), "+f"(d[91]), "+f"(d[92]), "+f"(d[93]), "+f"(d[94]), "+f"(d[95]), "+f"(d[96]), "+f"(d[97]), "+f"(d[98]), "+f"(d[99]), "+f"(d[100]), "+f"(d[101]), "+f"(d[102]), "+f"(d[103]), "+f"(d[104]), "+f"(d[105]), "+f"(d[106]), "+f"(d[107]), "+f"(d[108]), "+f"(d[109]), "+f"(d[110]), "+f"(d[111])
    : "l"(descA), "l"(descB), "r"(scaleD));
}

__device__ __forceinline__ void wgmma_rs_n64(float (&d)[32], const uint32_t (&a)[4], uint64_t descB, int scaleD) {
  asm volatile("{\n.reg .pred p;\nsetp.ne.b32 p, %37, 0;\n"
    "wgmma.mma_async.sync.aligned.m64n64k16.f32.bf16.bf16 {%0, %1, %2, %3, %4, %5, %6, %7, %8, %9, %10, %11, %12, %13, %14, %15, %16, %17, %18, %19, %20, %21, %22, %23, %24, %25, %26, %27, %28, %29, %30, %31}, {%32, %33, %34, %35}, %36, p, 1, 1, 1;\n}\n"
    : "+f"(d[0]), "+f"(d[1]), "+f"(d[2]), "+f"(d[3]), "+f"(d[4]), "+f"(d[5]), "+f"(d[6]), "+f"(d[7]), "+f"(d[8]), "+f"(d[9]), "+f"(d[10]), "+f"(d[11]), "+f"(d[12]), "+f"(d[13]), "+f"(d[14]), "+f"(d[15]), "+f"(d[16]), "+f"(d[17]), "+f"(d[18]), "+f"(d[19]), "+f"(d[20]), "+f"(d[21]), "+f"(d[22]), "+f"(d[23]), "+f"(d[24]), "+f"(d[25]), "+f"(d[26]), "+f"(d[27]), "+f"(d[28]), "+f"(d[29]), "+f"(d[30]), "+f"(d[31])
    : "r"(a[0]), "r"(a[1]), "r"(a[2]), "r"(a[3]), "l"(descB), "r"(scaleD));
}

__host__ __device__ constexpr int step_kind(int i) { return (i == 0 || i == 1 || i == 3 || i == 6) ? 0 : (i == 7 ? 2 : 1); }
__host__ __device__ constexpr int step_k(int i) { return i == 0 ? 0 : i == 1 ? 1 : i == 2 ? 0 : i == 3 ? 2 : i == 4 ? 1 : i == 5 ? 2 : 3; }
__device__ __forceinline__ int step_slice(int i, int j) {
  const int kind = step_kind(i), k = step_k(i);
  const int base = (kind == 0) ? (j ^ 1) : j;
  return (k == 3) ? base : ((base + 2 * (k + 1)) & 7);
}

__global__ void __cluster_dims__(2, 1, 1) __launch_bounds__(NTHREADS, 1)
fused_mlp_kernel(const __grid_constant__ CUtensorMap tm_x, const __grid_constant__ CUtensorMap tm_w1, const __grid_constant__ CUtensorMap tm_w2,
                 const __nv_bfloat16* __restrict__ b1, const __nv_bfloat16* __restrict__ b2, __nv_bfloat16* __restrict__ out)
{
  extern __shared__ __align__(1024) unsigned char smem[];
  const uint32_t sbase = smem_u32(smem);
  const uint32_t bar_full = sbase + OFF_BAR;
  const uint32_t bar_cons = sbase + OFF_BAR + 128;
  const uint32_t bar_x = sbase + OFF_BAR + 256;
  const uint32_t bar_dfull = sbase + OFF_BAR + 272;
  const uint32_t bar_peer = sbase + OFF_BAR + 304;
  const int tid = threadIdx.x, warp = tid >> 5, lane = tid & 31;
  const int mb = blockIdx.x >> 3, j = blockIdx.x & 7;

  TSC(0);
  if (warp == 8 && lane == 0) {
    for (int i = 0; i < 16; i++) { mbar_init(bar_full + 8 * i, 1); mbar_init(bar_cons + 8 * i, 2); }
    for (int i = 0; i < 2; i++) mbar_init(bar_x + 8 * i, 1);
    for (int i = 0; i < 4; i++) mbar_init(bar_dfull + 8 * i, 1);
    mbar_init(bar_peer, 2);
    asm volatile("fence.mbarrier_init.release.cluster;" ::: "memory");
    asm volatile("fence.proxy.async.shared::cta;" ::: "memory");
    mbar_expect_tx(bar_x, 65536);
    tma_load_3d(sbase, &tm_x, 0, mb * BM, 0, bar_x);
    mbar_expect_tx(bar_full, STAGE_BYTES);
    tma_load_3d(sbase + OFF_RING, &tm_w1, 0, 0, j * 7, bar_full);
    mbar_expect_tx(bar_x + 8, 65536);
    tma_load_3d(sbase + 65536, &tm_x, 0, mb * BM + 64, 0, bar_x + 8);
    for (int i = 1; i < NRING; i++) {
      mbar_expect_tx(bar_full + 8 * i, STAGE_BYTES);
      tma_load_3d(sbase + OFF_RING + i * STAGE_BYTES, &tm_w1, 0, i * 64, j * 7, bar_full + 8 * i);
    }
    for (int i = 0; i < 4; i++) mbar_expect_tx(bar_dfull + 8 * i, DSLOT_BYTES);
    if (mb < 8) { if (mb >= NRING) tma_prefetch_3d(&tm_w1, 0, mb * 64, j * 7); }
    else tma_prefetch_2d(&tm_w2, (mb - 8) * 64, j * BF);
    TS(2, 1);
  }
  asm volatile("barrier.cluster.arrive.release.aligned;\nbarrier.cluster.wait.acquire.aligned;" ::: "memory");

  if (warp >= 8) {
    asm volatile("setmaxnreg.dec.sync.aligned.u32 40;");
    if (warp == 8 && lane == 0) {
      for (int i = NRING; i < 16; i++) {
        uint32_t dst;
        if (i < 11)      { mbar_wait(bar_cons + 8 * (i - NRING), 0); dst = sbase + OFF_RING + (i % NRING) * STAGE_BYTES; }
        else if (i < 13) { dst = sbase + (i - 11) * STAGE_BYTES; }
        else             { mbar_wait(bar_cons + 8 * (i - 5), 0); dst = sbase + OFF_RING + ((i - 5) % NRING) * STAGE_BYTES; }
        TS(2, i);
        mbar_expect_tx(bar_full + 8 * i, STAGE_BYTES);
        if (i < 8) tma_load_3d(dst, &tm_w1, 0, i * 64, j * 7, bar_full + 8 * i);
        else tma_load_2d(dst, &tm_w2, step_slice(i - 8, j) * BN2, j * BF, bar_full + 8 * i);
      }
    }
  } else {
    TSC(22);
    asm volatile("setmaxnreg.inc.sync.aligned.u32 232;");
    TSC(23);
    const int wg = warp >> 2, w4 = warp & 3, t128 = tid & 127;
    const int q = lane & 3, g = lane >> 2;
    float* rstd_s = reinterpret_cast<float*>(smem + OFF_RSTD);
    uint32_t* b1s = reinterpret_cast<uint32_t*>(smem + OFF_B1 + wg * 512);
    uint32_t* b2s = reinterpret_cast<uint32_t*>(smem + OFF_B2 + wg * 128);
    uint32_t bias_a = 0, bias_b = 0;
    if (t128 < BF / 2) bias_a = reinterpret_cast<const uint32_t*>(b1 + j * BF)[t128];
    if (t128 < BN2 / 2) bias_b = reinterpret_cast<const uint32_t*>(b2 + j * BN2)[t128];
    const uint32_t epoch = g_epoch[blockIdx.x];

    unsigned char* ywg = smem + wg * 65536;
    TSC(24);
    mbar_wait(bar_x + 8 * wg, 0);
    TSC(25);
#pragma unroll
    for (int bt = 0; bt < 2; bt++) {
      uint4 xa[8], xb[8];
      float s1[8], s2[8], pv[8];
#pragma unroll
      for (int r = 0; r < 8; r++) {
        const int row = w4 * 16 + bt * 8 + r;
        const uint32_t ad = (uint32_t)((lane >> 3) * 8192 + row * 128 + (((lane & 7) ^ r) << 4));
        xa[r] = *reinterpret_cast<const uint4*>(ywg + ad);
        xb[r] = *reinterpret_cast<const uint4*>(ywg + ad + 4 * 8192);
      }
#pragma unroll
      for (int r = 0; r < 8; r++) pv[r] = __shfl_sync(0xffffffffu, bf_lo(xa[r].x), 0);
#pragma unroll
      for (int r = 0; r < 8; r++) {
        const uint32_t w[8] = {xa[r].x, xa[r].y, xa[r].z, xa[r].w, xb[r].x, xb[r].y, xb[r].z, xb[r].w};
        float a0 = 0.f, a1 = 0.f, q0 = 0.f, q1 = 0.f;
#pragma unroll
        for (int e = 0; e < 8; e++) {
          const float p = bf_lo(w[e]) - pv[r], t = bf_hi(w[e]) - pv[r];
          a0 += p; a1 += t; q0 = fmaf(p, p, q0); q1 = fmaf(t, t, q1);
        }
        s1[r] = a0 + a1; s2[r] = q0 + q1;
      }
#pragma unroll
      for (int o = 16; o > 0; o >>= 1)
#pragma unroll
        for (int r = 0; r < 8; r++) { s1[r] += __shfl_xor_sync(0xffffffffu, s1[r], o); s2[r] += __shfl_xor_sync(0xffffffffu, s2[r], o); }
      float vs = 0.f;
#pragma unroll
      for (int r = 0; r < 8; r++) {
        const int row = w4 * 16 + bt * 8 + r;
        const uint32_t ad = (uint32_t)((lane >> 3) * 8192 + row * 128 + (((lane & 7) ^ r) << 4));
        const uint4 a = xa[r], b = xb[r];
        const float dm = s1[r] * (1.0f / D_MOD);
        const float mean = pv[r] + dm;
        const uint32_t m2 = pack_bf16(mean, mean);
        uint4 d0, d1;
        d0.x = hsub2_bf(a.x, m2); d0.y = hsub2_bf(a.y, m2); d0.z = hsub2_bf(a.z, m2); d0.w = hsub2_bf(a.w, m2);
        d1.x = hsub2_bf(b.x, m2); d1.y = hsub2_bf(b.y, m2); d1.z = hsub2_bf(b.z, m2); d1.w = hsub2_bf(b.w, m2);
        *reinterpret_cast<uint4*>(ywg + ad) = d0;
        *reinterpret_cast<uint4*>(ywg + ad + 4 * 8192) = d1;
        const float var = fmaxf(fmaf(-dm, dm, s2[r] * (1.0f / D_MOD)), 0.f);
        vs = (lane == r) ? var : vs;
      }
      const float vb = bf16r(vs);
      const float sd = bf16r(sqrtf(bf16r(vb + 1e-5f)));
      if (lane < 8) rstd_s[wg * 64 + w4 * 16 + bt * 8 + lane] = 1.0f / sd;
    }
    if (t128 < BF / 2) b1s[t128] = bias_a;
    if (t128 < BN2 / 2) b2s[t128] = bias_b;
    TSC(1);
    asm volatile("fence.proxy.async.shared::cta;" ::: "memory");
    if (wg == 0) asm volatile("bar.sync 1, 128;" ::: "memory"); else asm volatile("bar.sync 2, 128;" ::: "memory");
    TSC(2);

    uint32_t h[14][4];
    {
      float acc[112];
#pragma unroll
      for (int kb = 0; kb < 8; kb++) {
        mbar_wait(bar_full + 8 * kb, 0);
        TSC(3 + kb);
        wg_fence();
        const uint32_t abase = sbase + wg * 65536 + kb * 8192;
        const uint32_t bbase = sbase + OFF_RING + (kb % NRING) * STAGE_BYTES;
#pragma unroll
        for (int kk = 0; kk < 4; kk++) {
          wgmma_ss_n224(acc, make_desc(abase + kk * 32, 16, 1024, 1), make_desc(bbase + kk * 1024, 4096, 512, 2), (kb | kk) != 0);
        }
        wg_commit();
        if (kb > 0) { wg_wait<1>(); if (t128 == 0) mbar_arrive(bar_cons + 8 * (kb - 1)); }
      }
      wg_wait<0>();
      reg_fence(acc);
      if (t128 == 0) { mbar_arrive(bar_cons + 8 * 7); mbar_arrive_remote(mapa(bar_peer, (j & 1) ^ 1)); }
      TSC(11);

      const int row0 = wg * 64 + w4 * 16 + g;
      const float r0 = rstd_s[row0], r1 = rstd_s[row0 + 8];
#pragma unroll
      for (int i = 0; i < 28; i++) {
        const uint32_t bb = b1s[i * 4 + q];
        uint32_t p0 = hadd2_bf(pack_bf16(acc[4 * i] * r0, acc[4 * i + 1] * r0), bb);
        uint32_t p1 = hadd2_bf(pack_bf16(acc[4 * i + 2] * r1, acc[4 * i + 3] * r1), bb);
        h[i >> 1][(i & 1) * 2 + 0] = pack_bf16(gelu_tanh(bf_lo(p0)), gelu_tanh(bf_hi(p0)));
        h[i >> 1][(i & 1) * 2 + 1] = pack_bf16(gelu_tanh(bf_lo(p1)), gelu_tanh(bf_hi(p1)));
      }
    }

    const uint32_t par = (epoch + 1) & 1;
    float acc2[2][32];
    float sum[32];
#pragma unroll
    for (int i = 0; i < 32; i++) sum[i] = 0.f;
    uint4 pf[4];
    const uint32_t peer_slot = mapa(sbase + OFF_DSLOT + (wg * 512 + t128) * 16, (j & 1) ^ 1);
    const uint32_t peer_dfull = mapa(bar_dfull, (j & 1) ^ 1);
    const uint4* my_slot = reinterpret_cast<const uint4*>(smem + OFF_DSLOT) + wg * 512 + t128;
    const uint4* in_part = &g_part[(size_t)((mb * NSPLIT + j) * 3) * 1024 + wg * 512 + t128];
    auto ld_part = [&](const uint4* p) {
      uint4 v;
      asm volatile("ld.relaxed.gpu.global.v4.u32 {%0, %1, %2, %3}, [%4];" : "=r"(v.x), "=r"(v.y), "=r"(v.z), "=r"(v.w) : "l"(p) : "memory");
      return v;
    };
    auto prefetch = [&](int k) {
#pragma unroll
      for (int c = 0; c < 4; c++) pf[c] = ld_part(in_part + k * 1024 + c * 128);
    };
    auto consume = [&](int k) {
#pragma unroll
      for (int c = 0; c < 4; c++) {
        uint4 v = pf[c];
        uint32_t it = 0;
        while ((((v.x ^ par) | (v.y ^ par) | (v.z ^ par) | (v.w ^ par)) & 1u) != 0) {
          v = ld_part(in_part + k * 1024 + c * 128);
          if (++it > (1u << 20)) asm volatile("trap;");
        }
        sum[c * 8 + 0] += bf_lo(v.x & ~1u); sum[c * 8 + 1] += bf_hi(v.x);
        sum[c * 8 + 2] += bf_lo(v.y & ~1u); sum[c * 8 + 3] += bf_hi(v.y);
        sum[c * 8 + 4] += bf_lo(v.z & ~1u); sum[c * 8 + 5] += bf_hi(v.z);
        sum[c * 8 + 6] += bf_lo(v.w & ~1u); sum[c * 8 + 7] += bf_hi(v.w);
      }
    };
    auto post = [&](int st, float (&a)[32]) {
      const int kind = step_kind(st), k = step_k(st);
      if (kind == 0) {
        if (st == 0) mbar_wait_cluster(bar_peer, 0);
#pragma unroll
        for (int c = 0; c < 4; c++) {
          asm volatile("st.async.weak.shared::cluster.mbarrier::complete_tx::bytes.v4.b32 [%0], {%1,%2,%3,%4}, [%5];"
            :: "r"(peer_slot + k * DSLOT_BYTES + c * 2048),
               "r"(pack_bf16(a[c * 8 + 0], a[c * 8 + 1])), "r"(pack_bf16(a[c * 8 + 2], a[c * 8 + 3])),
               "r"(pack_bf16(a[c * 8 + 4], a[c * 8 + 5])), "r"(pack_bf16(a[c * 8 + 6], a[c * 8 + 7])),
               "r"(peer_dfull + 8 * k) : "memory");
        }
      } else {
        mbar_wait_cluster(bar_dfull + 8 * k, 0);
        const int dest = (j + 2 * (k + 1)) & 7;
        uint4* p = &g_part[(size_t)((mb * NSPLIT + dest) * 3 + k) * 1024 + wg * 512 + t128];
#pragma unroll
        for (int c = 0; c < 4; c++) {
          const uint4 d = my_slot[k * 1024 + c * 128];
          uint4 v;
          v.x = (pack_bf16(a[c * 8 + 0] + bf_lo(d.x), a[c * 8 + 1] + bf_hi(d.x)) & ~1u) | par;
          v.y = (pack_bf16(a[c * 8 + 2] + bf_lo(d.y), a[c * 8 + 3] + bf_hi(d.y)) & ~1u) | par;
          v.z = (pack_bf16(a[c * 8 + 4] + bf_lo(d.z), a[c * 8 + 5] + bf_hi(d.z)) & ~1u) | par;
          v.w = (pack_bf16(a[c * 8 + 6] + bf_lo(d.w), a[c * 8 + 7] + bf_hi(d.w)) & ~1u) | par;
          __stcg(p + c * 128, v);
        }
      }
    };
#pragma unroll
    for (int i = 0; i < 8; i++) {
      TSC(12 + i);
      mbar_wait(bar_full + 8 * (8 + i), 0);
      uint32_t bbase;
      if (i < 3) bbase = sbase + OFF_RING + ((8 + i) % NRING) * STAGE_BYTES;
      else if (i < 5) bbase = sbase + (i - 3) * STAGE_BYTES;
      else bbase = sbase + OFF_RING + ((8 + i - 5) % NRING) * STAGE_BYTES;
      wg_fence();
#pragma unroll
      for (int ks = 0; ks < 14; ks++) {
        wgmma_rs_n64(acc2[i & 1], h[ks], make_desc(bbase + ks * 2048, 16, 1024, 1), ks != 0);
      }
      wg_commit();
      if (i > 0) {
        wg_wait<1>();
        reg_fence(acc2[(i - 1) & 1]);
        if (i <= 3 && t128 == 0) mbar_arrive(bar_cons + 8 * (8 + i - 1));
        post(i - 1, acc2[(i - 1) & 1]);
      }
      if (i == 6) prefetch(0);
      if (i == 7) { consume(0); prefetch(1); }
    }
    consume(1);
    prefetch(2);
    mbar_wait_cluster(bar_dfull + 8 * 3, 0);
#pragma unroll
    for (int c = 0; c < 4; c++) {
      const uint4 d = my_slot[3 * 1024 + c * 128];
      sum[c * 8 + 0] += bf_lo(d.x); sum[c * 8 + 1] += bf_hi(d.x); sum[c * 8 + 2] += bf_lo(d.y); sum[c * 8 + 3] += bf_hi(d.y);
      sum[c * 8 + 4] += bf_lo(d.z); sum[c * 8 + 5] += bf_hi(d.z); sum[c * 8 + 6] += bf_lo(d.w); sum[c * 8 + 7] += bf_hi(d.w);
    }
    wg_wait<0>();
    reg_fence(acc2[1]);
    TSC(20);
    consume(2);
    TSC(21);
    if (tid == 0) g_epoch[blockIdx.x] = epoch + 1;

    {
      const int row0 = mb * BM + wg * 64 + w4 * 16 + g;
      uint32_t* o0 = reinterpret_cast<uint32_t*>(out + (size_t)row0 * D_MOD + j * BN2) + q;
      uint32_t* o1 = o0 + 8 * D_MOD / 2;
#pragma unroll
      for (int i = 0; i < 8; i++) {
        const uint32_t bb = b2s[i * 4 + q];
        o0[i * 4] = hadd2_bf(pack_bf16(acc2[1][4 * i] + sum[4 * i], acc2[1][4 * i + 1] + sum[4 * i + 1]), bb);
        o1[i * 4] = hadd2_bf(pack_bf16(acc2[1][4 * i + 2] + sum[4 * i + 2], acc2[1][4 * i + 3] + sum[4 * i + 3]), bb);
      }
    }
  }
}

typedef CUresult (*EncodeFn)(CUtensorMap*, CUtensorMapDataType, cuuint32_t, void*, const cuuint64_t*, const cuuint64_t*,
                             const cuuint32_t*, const cuuint32_t*, CUtensorMapInterleave, CUtensorMapSwizzle,
                             CUtensorMapL2promotion, CUtensorMapFloatOOBfill);

}

extern "C" void kernel_launch(void* const* d_in, const int* in_sizes, int n_in, void* d_out, int out_size) {
  (void)in_sizes; (void)n_in; (void)out_size;
  static CUtensorMap tm_x, tm_w1, tm_w2;
  static const void* cached_w1 = nullptr; static const void* cached_w2 = nullptr; static const void* cached_x = nullptr;
  const void* w1 = d_in[1]; const void* w2 = d_in[3]; const void* xp = d_in[0];
  if (cached_w1 != w1 || cached_w2 != w2 || cached_x != xp) {
    void* fn = nullptr; cudaDriverEntryPointQueryResult st;
    cudaGetDriverEntryPoint("cuTensorMapEncodeTiled", &fn, cudaEnableDefault, &st);
    EncodeFn enc = (EncodeFn)fn;
    {
      cuuint64_t dims[3] = {64, (cuuint64_t)S_TOK, (cuuint64_t)(D_MOD / 64)};
      cuuint64_t strides[2] = {(cuuint64_t)D_MOD * 2, 128};
      cuuint32_t box[3] = {64, 64, 8};
      cuuint32_t es[3] = {1, 1, 1};
      enc(&tm_x, CU_TENSOR_MAP_DATA_TYPE_BFLOAT16, 3, const_cast<void*>(xp), dims, strides, box, es,
          CU_TENSOR_MAP_INTERLEAVE_NONE, CU_TENSOR_MAP_SWIZZLE_128B, CU_TENSOR_MAP_L2_PROMOTION_L2_128B, CU_TENSOR_MAP_FLOAT_OOB_FILL_NONE);
    }
    {
      cuuint64_t dims[3] = {32, (cuuint64_t)D_MOD, (cuuint64_t)(F_HID / 32)};
      cuuint64_t strides[2] = {(cuuint64_t)F_HID * 2, 64};
      cuuint32_t box[3] = {32, 64, 7};
      cuuint32_t es[3] = {1, 1, 1};
      enc(&tm_w1, CU_TENSOR_MAP_DATA_TYPE_BFLOAT16, 3, const_cast<void*>(w1), dims, strides, box, es,
          CU_TENSOR_MAP_INTERLEAVE_NONE, CU_TENSOR_MAP_SWIZZLE_64B, CU_TENSOR_MAP_L2_PROMOTION_L2_128B, CU_TENSOR_MAP_FLOAT_OOB_FILL_NONE);
    }
    {
      cuuint64_t dims[2] = {(cuuint64_t)D_MOD, (cuuint64_t)F_HID};
      cuuint64_t strides[1] = {(cuuint64_t)D_MOD * 2};
      cuuint32_t box[2] = {64, 224};
      cuuint32_t es[2] = {1, 1};
      enc(&tm_w2, CU_TENSOR_MAP_DATA_TYPE_BFLOAT16, 2, const_cast<void*>(w2), dims, strides, box, es,
          CU_TENSOR_MAP_INTERLEAVE_NONE, CU_TENSOR_MAP_SWIZZLE_128B, CU_TENSOR_MAP_L2_PROMOTION_L2_128B, CU_TENSOR_MAP_FLOAT_OOB_FILL_NONE);
    }
    cudaFuncSetAttribute(fused_mlp_kernel, cudaFuncAttributeMaxDynamicSharedMemorySize, SMEM_TOTAL);
    cached_w1 = w1; cached_w2 = w2; cached_x = xp;
  }
  fused_mlp_kernel<<<NMB * NSPLIT, NTHREADS, SMEM_TOTAL>>>(tm_x, tm_w1, tm_w2,
      (const __nv_bfloat16*)d_in[2], (const __nv_bfloat16*)d_in[4], (__nv_bfloat16*)d_out);
}
```

```cpp
#include <cuda_runtime.h>
#include <cuda_bf16.h>
#include <cuda.h>
#include <stdint.h>

namespace {

constexpr int S_TOK = 2048, D_MOD = 512, F_HID = 1792;
constexpr int BM = 128, NSPLIT = 8, BF = F_HID / NSPLIT;
constexpr int BN2 = D_MOD / NSPLIT;
constexpr int NMB = S_TOK / BM;
constexpr int STAGE_BYTES = 14336;
constexpr int Y_BYTES = BM * D_MOD * 2;
constexpr int NRING = 6;
constexpr int NLOAD = 32;
constexpr int OFF_RING = Y_BYTES;
constexpr int OFF_DSLOT = 4 * STAGE_BYTES;
constexpr int DSLOT_BYTES = 16384;
constexpr int OFF_BAR = OFF_RING + NRING * STAGE_BYTES;
constexpr int OFF_MEAN = OFF_BAR + 1024;
constexpr int OFF_B1 = OFF_MEAN + 512;
constexpr int OFF_B2 = OFF_B1 + 1024;
constexpr int SMEM_TOTAL = OFF_B2 + 256;
constexpr int NTHREADS = 384;

__device__ uint4 g_part[(size_t)NMB * NSPLIT * 3 * 1024];
__device__ unsigned int g_epoch[NMB * NSPLIT];

#define TS(role, idx) do {} while (0)
#define TSC(idx) do {} while (0)

__device__ __forceinline__ uint32_t smem_u32(const void* p) { return (uint32_t)__cvta_generic_to_shared(p); }
__device__ __forceinline__ uint32_t mapa(uint32_t a, uint32_t r) {
  uint32_t d; asm volatile("mapa.shared::cluster.u32 %0, %1, %2;" : "=r"(d) : "r"(a), "r"(r)); return d;
}
__device__ __forceinline__ void mbar_init(uint32_t bar, uint32_t cnt) {
  asm volatile("mbarrier.init.shared::cta.b64 [%0], %1;" :: "r"(bar), "r"(cnt) : "memory");
}
__device__ __forceinline__ void mbar_expect_tx(uint32_t bar, uint32_t bytes) {
  asm volatile("mbarrier.arrive.expect_tx.shared::cta.b64 _, [%0], %1;" :: "r"(bar), "r"(bytes) : "memory");
}
__device__ __forceinline__ void mbar_arrive(uint32_t bar) {
  asm volatile("mbarrier.arrive.shared::cta.b64 _, [%0];" :: "r"(bar) : "memory");
}
__device__ __forceinline__ void mbar_arrive_remote(uint32_t rbar) {
  asm volatile("mbarrier.arrive.release.cluster.shared::cluster.b64 _, [%0];" :: "r"(rbar) : "memory");
}
__device__ __forceinline__ void mbar_wait(uint32_t bar, uint32_t parity) {
  uint32_t done = 0; uint32_t it = 0;
  while (true) {
    asm volatile("{\n.reg .pred p;\nmbarrier.try_wait.parity.shared::cta.b64 p, [%1], %2;\nselp.u32 %0, 1, 0, p;\n}"
                 : "=r"(done) : "r"(bar), "r"(parity) : "memory");
    if (done) break;
    if (++it > (1u << 22)) asm volatile("trap;");
  }
}
__device__ __forceinline__ void mbar_wait_cluster(uint32_t bar, uint32_t parity) {
  uint32_t done = 0; uint32_t it = 0;
  while (true) {
    asm volatile("{\n.reg .pred p;\nmbarrier.try_wait.parity.acquire.cluster.shared::cta.b64 p, [%1], %2;\nselp.u32 %0, 1, 0, p;\n}"
                 : "=r"(done) : "r"(bar), "r"(parity) : "memory");
    if (done) break;
    if (++it > (1u << 22)) asm volatile("trap;");
  }
}
__device__ __forceinline__ void tma_load_3d(uint32_t dst, const CUtensorMap* tm, int c0, int c1, int c2, uint32_t bar) {
  asm volatile("cp.async.bulk.tensor.3d.shared::cluster.global.mbarrier::complete_tx::bytes [%0], [%1, {%3, %4, %5}], [%2];"
               :: "r"(dst), "l"(tm), "r"(bar), "r"(c0), "r"(c1), "r"(c2) : "memory");
}
__device__ __forceinline__ void tma_load_2d(uint32_t dst, const CUtensorMap* tm, int c0, int c1, uint32_t bar) {
  asm volatile("cp.async.bulk.tensor.2d.shared::cluster.global.mbarrier::complete_tx::bytes [%0], [%1, {%3, %4}], [%2];"
               :: "r"(dst), "l"(tm), "r"(bar), "r"(c0), "r"(c1) : "memory");
}
__device__ __forceinline__ void tma_prefetch_3d(const CUtensorMap* tm, int c0, int c1, int c2) {
  asm volatile("cp.async.bulk.prefetch.tensor.3d.L2.global.tile [%0, {%1, %2, %3}];" :: "l"(tm), "r"(c0), "r"(c1), "r"(c2) : "memory");
}
__device__ __forceinline__ void tma_prefetch_2d(const CUtensorMap* tm, int c0, int c1) {
  asm volatile("cp.async.bulk.prefetch.tensor.2d.L2.global.tile [%0, {%1, %2}];" :: "l"(tm), "r"(c0), "r"(c1) : "memory");
}
__device__ __forceinline__ void wg_fence() { asm volatile("wgmma.fence.sync.aligned;" ::: "memory"); }
__device__ __forceinline__ void wg_commit() { asm volatile("wgmma.commit_group.sync.aligned;" ::: "memory"); }
template <int N> __device__ __forceinline__ void wg_wait() { asm volatile("wgmma.wait_group.sync.aligned %0;" :: "n"(N) : "memory"); }
template <int N> __device__ __forceinline__ void reg_fence(float (&d)[N]) {
#pragma unroll
  for (int i = 0; i < N; i++) asm volatile("" : "+f"(d[i]) :: "memory");
}
__device__ __forceinline__ uint64_t make_desc(uint32_t addr, uint32_t lbo, uint32_t sbo, uint32_t lt) {
  return (uint64_t)((addr & 0x3FFFF) >> 4) | ((uint64_t)(lbo >> 4) << 16) | ((uint64_t)(sbo >> 4) << 32) | ((uint64_t)lt << 62);
}
__device__ __forceinline__ uint32_t pack_bf16(float lo, float hi) {
  uint32_t r; asm("cvt.rn.bf16x2.f32 %0, %1, %2;" : "=r"(r) : "f"(hi), "f"(lo)); return r;
}
__device__ __forceinline__ float bf_lo(uint32_t v) { return __uint_as_float(v << 16); }
__device__ __forceinline__ float bf_hi(uint32_t v) { return __uint_as_float(v & 0xffff0000u); }
__device__ __forceinline__ float bf16r(float v) { return __bfloat162float(__float2bfloat16_rn(v)); }
__device__ __forceinline__ uint32_t hadd2_bf(uint32_t a, uint32_t b) {
  uint32_t r; asm("add.rn.bf16x2 %0, %1, %2;" : "=r"(r) : "r"(a), "r"(b)); return r;
}
__device__ __forceinline__ uint32_t hsub2_bf(uint32_t a, uint32_t b) {
  uint32_t r; asm("sub.rn.bf16x2 %0, %1, %2;" : "=r"(r) : "r"(a), "r"(b)); return r;
}
__device__ __forceinline__ float gelu_tanh(float u) {
  float inner = u * fmaf(0.035677408136300125f, u * u, 0.7978845608028654f);
  float th; asm("tanh.approx.f32 %0, %1;" : "=f"(th) : "f"(inner));
  float hu = 0.5f * u;
  return fmaf(hu, th, hu);
}

__device__ __forceinline__ void wgmma_ss_n224(float (&d)[112], uint64_t descA, uint64_t descB, int scaleD) {
  asm volatile("{\n.reg .pred p;\nsetp.ne.b32 p, %114, 0;\n"
    "wgmma.mma_async.sync.aligned.m64n224k16.f32.bf16.bf16 {%0, %1, %2, %3, %4, %5, %6, %7, %8, %9, %10, %11, %12, %13, %14, %15, %16, %17, %18, %19, %20, %21, %22, %23, %24, %25, %26, %27, %28, %29, %30, %31, %32, %33, %34, %35, %36, %37, %38, %39, %40, %41, %42, %43, %44, %45, %46, %47, %48, %49, %50, %51, %52, %53, %54, %55, %56, %57, %58, %59, %60, %61, %62, %63, %64, %65, %66, %67, %68, %69, %70, %71, %72, %73, %74, %75, %76, %77, %78, %79, %80, %81, %82, %83, %84, %85, %86, %87, %88, %89, %90, %91, %92, %93, %94, %95, %96, %97, %98, %99, %100, %101, %102, %103, %104, %105, %106, %107, %108, %109, %110, %111}, %112, %113, p, 1, 1, 0, 1;\n}\n"
    : "+f"(d[0]), "+f"(d[1]), "+f"(d[2]), "+f"(d[3]), "+f"(d[4]), "+f"(d[5]), "+f"(d[6]), "+f"(d[7]), "+f"(d[8]), "+f"(d[9]), "+f"(d[10]), "+f"(d[11]), "+f"(d[12]), "+f"(d[13]), "+f"(d[14]), "+f"(d[15]), "+f"(d[16]), "+f"(d[17]), "+f"(d[18]), "+f"(d[19]), "+f"(d[20]), "+f"(d[21]), "+f"(d[22]), "+f"(d[23]), "+f"(d[24]), "+f"(d[25]), "+f"(d[26]), "+f"(d[27]), "+f"(d[28]), "+f"(d[29]), "+f"(d[30]), "+f"(d[31]), "+f"(d[32]), "+f"(d[33]), "+f"(d[34]), "+f"(d[35]), "+f"(d[36]), "+f"(d[37]), "+f"(d[38]), "+f"(d[39]), "+f"(d[40]), "+f"(d[41]), "+f"(d[42]), "+f"(d[43]), "+f"(d[44]), "+f"(d[45]), "+f"(d[46]), "+f"(d[47]), "+f"(d[48]), "+f"(d[49]), "+f"(d[50]), "+f"(d[51]), "+f"(d[52]), "+f"(d[53]), "+f"(d[54]), "+f"(d[55]), "+f"(d[56]), "+f"(d[57]), "+f"(d[58]), "+f"(d[59]), "+f"(d[60]), "+f"(d[61]), "+f"(d[62]), "+f"(d[63]), "+f"(d[64]), "+f"(d[65]), "+f"(d[66]), "+f"(d[67]), "+f"(d[68]), "+f"(d[69]), "+f"(d[70]), "+f"(d[71]), "+f"(d[72]), "+f"(d[73]), "+f"(d[74]), "+f"(d[75]), "+f"(d[76]), "+f"(d[77]), "+f"(d[78]), "+f"(d[79]), "+f"(d[80]), "+f"(d[81]), "+f"(d[82]), "+f"(d[83]), "+f"(d[84]), "+f"(d[85]), "+f"(d[86]), "+f"(d[87]), "+f"(d[88]), "+f"(d[89]), "+f"(d[90]), "+f"(d[91]), "+f"(d[92]), "+f"(d[93]), "+f"(d[94]), "+f"(d[95]), "+f"(d[96]), "+f"(d[97]), "+f"(d[98]), "+f"(d[99]), "+f"(d[100]), "+f"(d[101]), "+f"(d[102]), "+f"(d[103]), "+f"(d[104]), "+f"(d[105]), "+f"(d[106]), "+f"(d[107]), "+f"(d[108]), "+f"(d[109]), "+f"(d[110]), "+f"(d[111])
    : "l"(descA), "l"(descB), "r"(scaleD));
}

__device__ __forceinline__ void wgmma_rs_n64(float (&d)[32], const uint32_t (&a)[4], uint64_t descB, int scaleD) {
  asm volatile("{\n.reg .pred p;\nsetp.ne.b32 p, %37, 0;\n"
    "wgmma.mma_async.sync.aligned.m64n64k16.f32.bf16.bf16 {%0, %1, %2, %3, %4, %5, %6, %7, %8, %9, %10, %11, %12, %13, %14, %15, %16, %17, %18, %19, %20, %21, %22, %23, %24, %25, %26, %27, %28, %29, %30, %31}, {%32, %33, %34, %35}, %36, p, 1, 1, 1;\n}\n"
    : "+f"(d[0]), "+f"(d[1]), "+f"(d[2]), "+f"(d[3]), "+f"(d[4]), "+f"(d[5]), "+f"(d[6]), "+f"(d[7]), "+f"(d[8]), "+f"(d[9]), "+f"(d[10]), "+f"(d[11]), "+f"(d[12]), "+f"(d[13]), "+f"(d[14]), "+f"(d[15]), "+f"(d[16]), "+f"(d[17]), "+f"(d[18]), "+f"(d[19]), "+f"(d[20]), "+f"(d[21]), "+f"(d[22]), "+f"(d[23]), "+f"(d[24]), "+f"(d[25]), "+f"(d[26]), "+f"(d[27]), "+f"(d[28]), "+f"(d[29]), "+f"(d[30]), "+f"(d[31])
    : "r"(a[0]), "r"(a[1]), "r"(a[2]), "r"(a[3]), "l"(descB), "r"(scaleD));
}

__host__ __device__ constexpr int step_kind(int i) { return (i == 0 || i == 1 || i == 3 || i == 6) ? 0 : (i == 7 ? 2 : 1); }
__host__ __device__ constexpr int step_k(int i) { return i == 0 ? 0 : i == 1 ? 1 : i == 2 ? 0 : i == 3 ? 2 : i == 4 ? 1 : i == 5 ? 2 : 3; }
__device__ __forceinline__ int step_slice(int i, int j) {
  const int kind = step_kind(i), k = step_k(i);
  const int base = (kind == 0) ? (j ^ 1) : j;
  return (k == 3) ? base : ((base + 2 * (k + 1)) & 7);
}

__host__ __device__ constexpr int load_off(int i) {
  return i < 22 ? OFF_RING + (i % NRING) * STAGE_BYTES : (i < 26 ? (i - 22) * STAGE_BYTES : OFF_RING + ((i - 10) % NRING) * STAGE_BYTES);
}
__host__ __device__ constexpr int load_dep(int i) { return i < NRING ? -1 : (i < 22 ? i - NRING : (i < 26 ? 15 : i - 10)); }

__global__ void __cluster_dims__(2, 1, 1) __launch_bounds__(NTHREADS, 1)
fused_mlp_kernel(const __grid_constant__ CUtensorMap tm_x, const __grid_constant__ CUtensorMap tm_w1, const __grid_constant__ CUtensorMap tm_w2,
                 const __nv_bfloat16* __restrict__ b1, const __nv_bfloat16* __restrict__ b2, __nv_bfloat16* __restrict__ out)
{
  extern __shared__ __align__(1024) unsigned char smem[];
  const uint32_t sbase = smem_u32(smem);
  const uint32_t bar_full = sbase + OFF_BAR;
  const uint32_t bar_cons = sbase + OFF_BAR + 256;
  const uint32_t bar_x = sbase + OFF_BAR + 512;
  const uint32_t bar_dfull = sbase + OFF_BAR + 528;
  const uint32_t bar_peer = sbase + OFF_BAR + 560;
  const int tid = threadIdx.x, warp = tid >> 5, lane = tid & 31;
  const int mb = blockIdx.x >> 3, j = blockIdx.x & 7;

  TSC(0);
  if (warp == 8 && lane == 0) {
    for (int i = 0; i < NLOAD; i++) { mbar_init(bar_full + 8 * i, 1); mbar_init(bar_cons + 8 * i, 2); }
    for (int i = 0; i < 2; i++) mbar_init(bar_x + 8 * i, 1);
    for (int i = 0; i < 4; i++) mbar_init(bar_dfull + 8 * i, 1);
    mbar_init(bar_peer, 2);
    asm volatile("fence.mbarrier_init.release.cluster;" ::: "memory");
    asm volatile("fence.proxy.async.shared::cta;" ::: "memory");
    mbar_expect_tx(bar_x, 65536);
    tma_load_3d(sbase, &tm_x, 0, mb * BM, 0, bar_x);
    mbar_expect_tx(bar_x + 8, 65536);
    tma_load_3d(sbase + 65536, &tm_x, 0, mb * BM + 64, 0, bar_x + 8);
    for (int i = 0; i < NRING; i++) {
      mbar_expect_tx(bar_full + 8 * i, STAGE_BYTES);
      tma_load_3d(sbase + OFF_RING + i * STAGE_BYTES, &tm_w1, 0, i * 32, j * 7, bar_full + 8 * i);
    }
    for (int i = 0; i < 4; i++) mbar_expect_tx(bar_dfull + 8 * i, DSLOT_BYTES);
    for (int t = 2 * mb; t < 2 * mb + 2; t++) {
      if (t < 16) { if (t >= NRING) tma_prefetch_3d(&tm_w1, 0, t * 32, j * 7); }
      else tma_prefetch_2d(&tm_w2, ((t - 16) >> 1) * 64, j * BF + ((t - 16) & 1) * 112);
    }
    TS(2, 1);
  }
  asm volatile("barrier.cluster.arrive.relaxed.aligned;\nbarrier.cluster.wait.aligned;" ::: "memory");

  if (warp >= 8) {
    asm volatile("setmaxnreg.dec.sync.aligned.u32 40;");
    if (warp == 8 && lane == 0) {
#pragma unroll
      for (int i = NRING; i < NLOAD; i++) {
        if (i < 23 || i >= 26) mbar_wait(bar_cons + 8 * load_dep(i), 0);
        mbar_expect_tx(bar_full + 8 * i, STAGE_BYTES);
        if (i < 16) tma_load_3d(sbase + load_off(i), &tm_w1, 0, i * 32, j * 7, bar_full + 8 * i);
        else tma_load_2d(sbase + load_off(i), &tm_w2, step_slice((i - 16) >> 1, j) * BN2, j * BF + ((i - 16) & 1) * 112, bar_full + 8 * i);
      }
    }
  } else {
    TSC(22);
    asm volatile("setmaxnreg.inc.sync.aligned.u32 232;");
    TSC(23);
    const int wg = warp >> 2, w4 = warp & 3, t128 = tid & 127;
    const int q = lane & 3, g = lane >> 2;
    uint32_t* mean_s = reinterpret_cast<uint32_t*>(smem + OFF_MEAN) + wg * 64 + w4 * 16;
    uint32_t* b1s = reinterpret_cast<uint32_t*>(smem + OFF_B1 + wg * 512);
    uint32_t* b2s = reinterpret_cast<uint32_t*>(smem + OFF_B2 + wg * 128);
    uint32_t bias_a = 0, bias_b = 0;
    if (t128 < BF / 2) bias_a = reinterpret_cast<const uint32_t*>(b1 + j * BF)[t128];
    if (t128 < BN2 / 2) bias_b = reinterpret_cast<const uint32_t*>(b2 + j * BN2)[t128];
    const uint32_t epoch = g_epoch[blockIdx.x];

    unsigned char* ywg = smem + wg * 65536;
    float r0, r1;
    TSC(24);
    mbar_wait(bar_x + 8 * wg, 0);
    TSC(25);
    {
      float cs[4] = {0.f, 0.f, 0.f, 0.f}, c0[4] = {0.f, 0.f, 0.f, 0.f}, c1[4] = {0.f, 0.f, 0.f, 0.f};
      const int lrow = w4 * 16 + (lane & 7) + ((lane >> 3) & 1) * 8;
      const uint32_t lbase = sbase + wg * 65536 + lrow * 128;
      const uint32_t ones = 0x3F803F80u;
#pragma unroll
      for (int kb = 0; kb < 8; kb++) {
#pragma unroll
        for (int ks = 0; ks < 4; ks++) {
          uint32_t a0, a1, a2, a3;
          const uint32_t addr = lbase + kb * 8192 + (((2 * ks + (lane >> 4)) ^ (lane & 7)) << 4);
          asm volatile("ldmatrix.sync.aligned.m8n8.x4.shared.b16 {%0,%1,%2,%3}, [%4];" : "=r"(a0), "=r"(a1), "=r"(a2), "=r"(a3) : "r"(addr));
          asm volatile("mma.sync.aligned.m16n8k16.row.col.f32.bf16.bf16.f32 {%0,%1,%2,%3}, {%4,%5,%6,%7}, {%8,%9}, {%0,%1,%2,%3};"
                       : "+f"(cs[0]), "+f"(cs[1]), "+f"(cs[2]), "+f"(cs[3]) : "r"(a0), "r"(a1), "r"(a2), "r"(a3), "r"(ones), "r"(ones));
          asm volatile("mma.sync.aligned.m16n8k16.row.col.f32.bf16.bf16.f32 {%0,%1,%2,%3}, {%4,%5,%6,%7}, {%8,%9}, {%0,%1,%2,%3};"
                       : "+f"(c0[0]), "+f"(c0[1]), "+f"(c0[2]), "+f"(c0[3]) : "r"(a0), "r"(a1), "r"(a2), "r"(a3), "r"(a0), "r"(a2));
          asm volatile("mma.sync.aligned.m16n8k16.row.col.f32.bf16.bf16.f32 {%0,%1,%2,%3}, {%4,%5,%6,%7}, {%8,%9}, {%0,%1,%2,%3};"
                       : "+f"(c1[0]), "+f"(c1[1]), "+f"(c1[2]), "+f"(c1[3]) : "r"(a0), "r"(a1), "r"(a2), "r"(a3), "r"(a1), "r"(a3));
        }
      }
      const int dsrc = g * 4 + (g >> 1);
      const float q0 = __shfl_sync(0xffffffffu, (g & 1) ? c0[1] : c0[0], dsrc);
      const float q1 = __shfl_sync(0xffffffffu, (g & 1) ? c1[3] : c1[2], dsrc);
      const float m0 = cs[0] * (1.0f / D_MOD), m1 = cs[2] * (1.0f / D_MOD);
      const float v0 = fmaxf(fmaf(-m0, m0, q0 * (1.0f / D_MOD)), 0.f), v1 = fmaxf(fmaf(-m1, m1, q1 * (1.0f / D_MOD)), 0.f);
      if (q == 0) { mean_s[g] = pack_bf16(m0, m0); mean_s[g + 8] = pack_bf16(m1, m1); }
      r0 = 1.0f / bf16r(sqrtf(bf16r(bf16r(v0) + 1e-5f)));
      r1 = 1.0f / bf16r(sqrtf(bf16r(bf16r(v1) + 1e-5f)));
      __syncwarp();
#pragma unroll
      for (int r = 0; r < 16; r++) {
        const uint32_t ad = (uint32_t)((lane >> 3) * 8192 + (w4 * 16 + r) * 128 + (((lane & 7) ^ (r & 7)) << 4));
        const uint32_t m2 = mean_s[r];
        uint4 a = *reinterpret_cast<const uint4*>(ywg + ad), b = *reinterpret_cast<const uint4*>(ywg + ad + 4 * 8192);
        a.x = hsub2_bf(a.x, m2); a.y = hsub2_bf(a.y, m2); a.z = hsub2_bf(a.z, m2); a.w = hsub2_bf(a.w, m2);
        b.x = hsub2_bf(b.x, m2); b.y = hsub2_bf(b.y, m2); b.z = hsub2_bf(b.z, m2); b.w = hsub2_bf(b.w, m2);
        *reinterpret_cast<uint4*>(ywg + ad) = a;
        *reinterpret_cast<uint4*>(ywg + ad + 4 * 8192) = b;
      }
    }
    if (t128 < BF / 2) b1s[t128] = bias_a;
    if (t128 < BN2 / 2) b2s[t128] = bias_b;
    TSC(1);
    asm volatile("fence.proxy.async.shared::cta;" ::: "memory");
    if (wg == 0) asm volatile("bar.sync 1, 128;" ::: "memory"); else asm volatile("bar.sync 2, 128;" ::: "memory");
    TSC(2);

    uint32_t h[14][4];
    {
      float acc[112];
#pragma unroll
      for (int kb = 0; kb < 16; kb++) {
        mbar_wait(bar_full + 8 * kb, 0);
        if ((kb & 1) == 0) TSC(3 + (kb >> 1));
        wg_fence();
        const uint32_t abase = sbase + wg * 65536 + (kb >> 1) * 8192 + (kb & 1) * 64;
        const uint32_t bbase = sbase + load_off(kb);
#pragma unroll
        for (int kk = 0; kk < 2; kk++) {
          wgmma_ss_n224(acc, make_desc(abase + kk * 32, 16, 1024, 1), make_desc(bbase + kk * 1024, 2048, 512, 2), (kb | kk) != 0);
        }
        wg_commit();
        if (kb > 0) { wg_wait<1>(); if (t128 == 0) mbar_arrive(bar_cons + 8 * (kb - 1)); }
      }
      wg_wait<0>();
      reg_fence(acc);
      if (t128 == 0) { mbar_arrive(bar_cons + 8 * 15); mbar_arrive_remote(mapa(bar_peer, (j & 1) ^ 1)); }
      TSC(11);

#pragma unroll
      for (int i = 0; i < 28; i++) {
        const uint32_t bb = b1s[i * 4 + q];
        uint32_t p0 = hadd2_bf(pack_bf16(acc[4 * i] * r0, acc[4 * i + 1] * r0), bb);
        uint32_t p1 = hadd2_bf(pack_bf16(acc[4 * i + 2] * r1, acc[4 * i + 3] * r1), bb);
        h[i >> 1][(i & 1) * 2 + 0] = pack_bf16(gelu_tanh(bf_lo(p0)), gelu_tanh(bf_hi(p0)));
        h[i >> 1][(i & 1) * 2 + 1] = pack_bf16(gelu_tanh(bf_lo(p1)), gelu_tanh(bf_hi(p1)));
      }
    }

    const uint32_t par = (epoch + 1) & 1;
    float acc2[2][32];
    float sum[32];
#pragma unroll
    for (int i = 0; i < 32; i++) sum[i] = 0.f;
    uint4 pf[4];
    const uint32_t peer_slot = mapa(sbase + OFF_DSLOT + (wg * 512 + t128) * 16, (j & 1) ^ 1);
    const uint32_t peer_dfull = mapa(bar_dfull, (j & 1) ^ 1);
    const uint4* my_slot = reinterpret_cast<const uint4*>(smem + OFF_DSLOT) + wg * 512 + t128;
    const uint4* in_part = &g_part[(size_t)((mb * NSPLIT + j) * 3) * 1024 + wg * 512 + t128];
    auto ld_part = [&](const uint4* p) {
      uint4 v;
      asm volatile("ld.relaxed.gpu.global.v4.u32 {%0, %1, %2, %3}, [%4];" : "=r"(v.x), "=r"(v.y), "=r"(v.z), "=r"(v.w) : "l"(p) : "memory");
      return v;
    };
    auto prefetch = [&](int k) {
#pragma unroll
      for (int c = 0; c < 4; c++) pf[c] = ld_part(in_part + k * 1024 + c * 128);
    };
    auto consume = [&](int k) {
#pragma unroll
      for (int c = 0; c < 4; c++) {
        uint4 v = pf[c];
        uint32_t it = 0;
        while ((((v.x ^ par) | (v.y ^ par) | (v.z ^ par) | (v.w ^ par)) & 1u) != 0) {
          v = ld_part(in_part + k * 1024 + c * 128);
          if (++it > (1u << 20)) asm volatile("trap;");
        }
        sum[c * 8 + 0] += bf_lo(v.x & ~1u); sum[c * 8 + 1] += bf_hi(v.x);
        sum[c * 8 + 2] += bf_lo(v.y & ~1u); sum[c * 8 + 3] += bf_hi(v.y);
        sum[c * 8 + 4] += bf_lo(v.z & ~1u); sum[c * 8 + 5] += bf_hi(v.z);
        sum[c * 8 + 6] += bf_lo(v.w & ~1u); sum[c * 8 + 7] += bf_hi(v.w);
      }
    };
    auto post = [&](int st, float (&a)[32]) {
      const int kind = step_kind(st), k = step_k(st);
      if (kind == 0) {
        if (st == 0) mbar_wait_cluster(bar_peer, 0);
#pragma unroll
        for (int c = 0; c < 4; c++) {
          asm volatile("st.async.weak.shared::cluster.mbarrier::complete_tx::bytes.v4.b32 [%0], {%1,%2,%3,%4}, [%5];"
            :: "r"(peer_slot + k * DSLOT_BYTES + c * 2048),
               "r"(pack_bf16(a[c * 8 + 0], a[c * 8 + 1])), "r"(pack_bf16(a[c * 8 + 2], a[c * 8 + 3])),
               "r"(pack_bf16(a[c * 8 + 4], a[c * 8 + 5])), "r"(pack_bf16(a[c * 8 + 6], a[c * 8 + 7])),
               "r"(peer_dfull + 8 * k) : "memory");
        }
      } else {
        mbar_wait_cluster(bar_dfull + 8 * k, 0);
        const int dest = (j + 2 * (k + 1)) & 7;
        uint4* p = &g_part[(size_t)((mb * NSPLIT + dest) * 3 + k) * 1024 + wg * 512 + t128];
#pragma unroll
        for (int c = 0; c < 4; c++) {
          const uint4 d = my_slot[k * 1024 + c * 128];
          uint4 v;
          v.x = (pack_bf16(a[c * 8 + 0] + bf_lo(d.x), a[c * 8 + 1] + bf_hi(d.x)) & ~1u) | par;
          v.y = (pack_bf16(a[c * 8 + 2] + bf_lo(d.y), a[c * 8 + 3] + bf_hi(d.y)) & ~1u) | par;
          v.z = (pack_bf16(a[c * 8 + 4] + bf_lo(d.z), a[c * 8 + 5] + bf_hi(d.z)) & ~1u) | par;
          v.w = (pack_bf16(a[c * 8 + 6] + bf_lo(d.w), a[c * 8 + 7] + bf_hi(d.w)) & ~1u) | par;
          __stcg(p + c * 128, v);
        }
      }
    };
#pragma unroll
    for (int i = 0; i < 8; i++) {
      TSC(12 + i);
      mbar_wait(bar_full + 8 * (16 + 2 * i), 0);
      wg_fence();
#pragma unroll
      for (int ks = 0; ks < 7; ks++) {
        wgmma_rs_n64(acc2[i & 1], h[ks], make_desc(sbase + load_off(16 + 2 * i) + ks * 2048, 16, 1024, 1), ks != 0);
      }
      mbar_wait(bar_full + 8 * (17 + 2 * i), 0);
      wg_fence();
#pragma unroll
      for (int ks = 0; ks < 7; ks++) {
        wgmma_rs_n64(acc2[i & 1], h[7 + ks], make_desc(sbase + load_off(17 + 2 * i) + ks * 2048, 16, 1024, 1), 1);
      }
      wg_commit();
      if (i > 0) {
        wg_wait<1>();
        reg_fence(acc2[(i - 1) & 1]);
        if (i <= 3 && t128 == 0) { mbar_arrive(bar_cons + 8 * (16 + 2 * (i - 1))); mbar_arrive(bar_cons + 8 * (17 + 2 * (i - 1))); }
        post(i - 1, acc2[(i - 1) & 1]);
      }
      if (i == 6) prefetch(0);
      if (i == 7) { consume(0); prefetch(1); }
    }
    consume(1);
    prefetch(2);
    mbar_wait_cluster(bar_dfull + 8 * 3, 0);
#pragma unroll
    for (int c = 0; c < 4; c++) {
      const uint4 d = my_slot[3 * 1024 + c * 128];
      sum[c * 8 + 0] += bf_lo(d.x); sum[c * 8 + 1] += bf_hi(d.x); sum[c * 8 + 2] += bf_lo(d.y); sum[c * 8 + 3] += bf_hi(d.y);
      sum[c * 8 + 4] += bf_lo(d.z); sum[c * 8 + 5] += bf_hi(d.z); sum[c * 8 + 6] += bf_lo(d.w); sum[c * 8 + 7] += bf_hi(d.w);
    }
    wg_wait<0>();
    reg_fence(acc2[1]);
    TSC(20);
    consume(2);
    TSC(21);
    if (tid == 0) g_epoch[blockIdx.x] = epoch + 1;

    {
      const int row0 = mb * BM + wg * 64 + w4 * 16 + g;
      uint32_t* o0 = reinterpret_cast<uint32_t*>(out + (size_t)row0 * D_MOD + j * BN2) + q;
      uint32_t* o1 = o0 + 8 * D_MOD / 2;
#pragma unroll
      for (int i = 0; i < 8; i++) {
        const uint32_t bb = b2s[i * 4 + q];
        o0[i * 4] = hadd2_bf(pack_bf16(acc2[1][4 * i] + sum[4 * i], acc2[1][4 * i + 1] + sum[4 * i + 1]), bb);
        o1[i * 4] = hadd2_bf(pack_bf16(acc2[1][4 * i + 2] + sum[4 * i + 2], acc2[1][4 * i + 3] + sum[4 * i + 3]), bb);
      }
    }
  }
}

typedef CUresult (*EncodeFn)(CUtensorMap*, CUtensorMapDataType, cuuint32_t, void*, const cuuint64_t*, const cuuint64_t*,
                             const cuuint32_t*, const cuuint32_t*, CUtensorMapInterleave, CUtensorMapSwizzle,
                             CUtensorMapL2promotion, CUtensorMapFloatOOBfill);

}

extern "C" void kernel_launch(void* const* d_in, const int* in_sizes, int n_in, void* d_out, int out_size) {
  (void)in_sizes; (void)n_in; (void)out_size;
  static CUtensorMap tm_x, tm_w1, tm_w2;
  static const void* cached_w1 = nullptr; static const void* cached_w2 = nullptr; static const void* cached_x = nullptr;
  const void* w1 = d_in[1]; const void* w2 = d_in[3]; const void* xp = d_in[0];
  if (cached_w1 != w1 || cached_w2 != w2 || cached_x != xp) {
    void* fn = nullptr; cudaDriverEntryPointQueryResult st;
    cudaGetDriverEntryPoint("cuTensorMapEncodeTiled", &fn, cudaEnableDefault, &st);
    EncodeFn enc = (EncodeFn)fn;
    {
      cuuint64_t dims[3] = {64, (cuuint64_t)S_TOK, (cuuint64_t)(D_MOD / 64)};
      cuuint64_t strides[2] = {(cuuint64_t)D_MOD * 2, 128};
      cuuint32_t box[3] = {64, 64, 8};
      cuuint32_t es[3] = {1, 1, 1};
      enc(&tm_x, CU_TENSOR_MAP_DATA_TYPE_BFLOAT16, 3, const_cast<void*>(xp), dims, strides, box, es,
          CU_TENSOR_MAP_INTERLEAVE_NONE, CU_TENSOR_MAP_SWIZZLE_128B, CU_TENSOR_MAP_L2_PROMOTION_L2_128B, CU_TENSOR_MAP_FLOAT_OOB_FILL_NONE);
    }
    {
      cuuint64_t dims[3] = {32, (cuuint64_t)D_MOD, (cuuint64_t)(F_HID / 32)};
      cuuint64_t strides[2] = {(cuuint64_t)F_HID * 2, 64};
      cuuint32_t box[3] = {32, 32, 7};
      cuuint32_t es[3] = {1, 1, 1};
      enc(&tm_w1, CU_TENSOR_MAP_DATA_TYPE_BFLOAT16, 3, const_cast<void*>(w1), dims, strides, box, es,
          CU_TENSOR_MAP_INTERLEAVE_NONE, CU_TENSOR_MAP_SWIZZLE_64B, CU_TENSOR_MAP_L2_PROMOTION_L2_128B, CU_TENSOR_MAP_FLOAT_OOB_FILL_NONE);
    }
    {
      cuuint64_t dims[2] = {(cuuint64_t)D_MOD, (cuuint64_t)F_HID};
      cuuint64_t strides[1] = {(cuuint64_t)D_MOD * 2};
      cuuint32_t box[2] = {64, 112};
      cuuint32_t es[2] = {1, 1};
      enc(&tm_w2, CU_TENSOR_MAP_DATA_TYPE_BFLOAT16, 2, const_cast<void*>(w2), dims, strides, box, es,
          CU_TENSOR_MAP_INTERLEAVE_NONE, CU_TENSOR_MAP_SWIZZLE_128B, CU_TENSOR_MAP_L2_PROMOTION_L2_128B, CU_TENSOR_MAP_FLOAT_OOB_FILL_NONE);
    }
    cudaFuncSetAttribute(fused_mlp_kernel, cudaFuncAttributeMaxDynamicSharedMemorySize, SMEM_TOTAL);
    cached_w1 = w1; cached_w2 = w2; cached_x = xp;
  }
  fused_mlp_kernel<<<NMB * NSPLIT, NTHREADS, SMEM_TOTAL>>>(tm_x, tm_w1, tm_w2,
      (const __nv_bfloat16*)d_in[2], (const __nv_bfloat16*)d_in[4], (__nv_bfloat16*)d_out);
}
```

```cpp
#include <cuda_runtime.h>
#include <cuda_bf16.h>
#include <cuda.h>
#include <stdint.h>

namespace {

constexpr int S_TOK = 2048, D_MOD = 512, F_HID = 1792;
constexpr int BM = 128, NSPLIT = 8, BF = F_HID / NSPLIT;
constexpr int BN2 = D_MOD / NSPLIT;
constexpr int NMB = S_TOK / BM;
constexpr int SLOT_BYTES = 16384;
constexpr int W1_BYTES = 16384;
constexpr int W2_BYTES = 14336;
constexpr int Y_BYTES = BM * D_MOD * 2;
constexpr int NRING = 6;
constexpr int NLOAD = 32;
constexpr int OFF_RING = Y_BYTES;
constexpr int OFF_DIN = 0;
constexpr int OFF_DOUT = 65536;
constexpr int DSLOT_BYTES = 16384;
constexpr int OFF_BAR = OFF_RING + NRING * SLOT_BYTES;
constexpr int OFF_MEAN = OFF_BAR + 640;
constexpr int OFF_B1 = OFF_MEAN + 512;
constexpr int OFF_B2 = OFF_B1 + 1024;
constexpr int SMEM_TOTAL = OFF_B2 + 256;
constexpr int NTHREADS = 288;
static_assert(SMEM_TOTAL <= 232448, "smem");

__device__ uint4 g_part[(size_t)NMB * NSPLIT * 3 * 1024];
__device__ unsigned int g_epoch[NMB * NSPLIT];

#define TS(role, idx) do {} while (0)
#define TSC(idx) do {} while (0)

__device__ __forceinline__ uint32_t smem_u32(const void* p) { return (uint32_t)__cvta_generic_to_shared(p); }
__device__ __forceinline__ uint32_t mapa(uint32_t a, uint32_t r) {
  uint32_t d; asm volatile("mapa.shared::cluster.u32 %0, %1, %2;" : "=r"(d) : "r"(a), "r"(r)); return d;
}
__device__ __forceinline__ void mbar_init(uint32_t bar, uint32_t cnt) {
  asm volatile("mbarrier.init.shared::cta.b64 [%0], %1;" :: "r"(bar), "r"(cnt) : "memory");
}
__device__ __forceinline__ void mbar_expect_tx(uint32_t bar, uint32_t bytes) {
  asm volatile("mbarrier.arrive.expect_tx.shared::cta.b64 _, [%0], %1;" :: "r"(bar), "r"(bytes) : "memory");
}
__device__ __forceinline__ void mbar_arrive(uint32_t bar) {
  asm volatile("mbarrier.arrive.shared::cta.b64 _, [%0];" :: "r"(bar) : "memory");
}
__device__ __forceinline__ void mbar_arrive_remote(uint32_t rbar) {
  asm volatile("mbarrier.arrive.release.cluster.shared::cluster.b64 _, [%0];" :: "r"(rbar) : "memory");
}
__device__ __forceinline__ void mbar_wait(uint32_t bar, uint32_t parity) {
  uint32_t done = 0; uint32_t it = 0;
  while (true) {
    asm volatile("{\n.reg .pred p;\nmbarrier.try_wait.parity.shared::cta.b64 p, [%1], %2;\nselp.u32 %0, 1, 0, p;\n}"
                 : "=r"(done) : "r"(bar), "r"(parity) : "memory");
    if (done) break;
    if (++it > (1u << 22)) asm volatile("trap;");
  }
}
__device__ __forceinline__ void mbar_wait_cluster(uint32_t bar, uint32_t parity) {
  uint32_t done = 0; uint32_t it = 0;
  while (true) {
    asm volatile("{\n.reg .pred p;\nmbarrier.try_wait.parity.acquire.cluster.shared::cta.b64 p, [%1], %2;\nselp.u32 %0, 1, 0, p;\n}"
                 : "=r"(done) : "r"(bar), "r"(parity) : "memory");
    if (done) break;
    if (++it > (1u << 22)) asm volatile("trap;");
  }
}
__device__ __forceinline__ void tma_load_3d(uint32_t dst, const CUtensorMap* tm, int c0, int c1, int c2, uint32_t bar) {
  asm volatile("cp.async.bulk.tensor.3d.shared::cluster.global.mbarrier::complete_tx::bytes [%0], [%1, {%3, %4, %5}], [%2];"
               :: "r"(dst), "l"(tm), "r"(bar), "r"(c0), "r"(c1), "r"(c2) : "memory");
}
__device__ __forceinline__ void tma_load_2d(uint32_t dst, const CUtensorMap* tm, int c0, int c1, uint32_t bar) {
  asm volatile("cp.async.bulk.tensor.2d.shared::cluster.global.mbarrier::complete_tx::bytes [%0], [%1, {%3, %4}], [%2];"
               :: "r"(dst), "l"(tm), "r"(bar), "r"(c0), "r"(c1) : "memory");
}
__device__ __forceinline__ void tma_prefetch_2d(const CUtensorMap* tm, int c0, int c1) {
  asm volatile("cp.async.bulk.prefetch.tensor.2d.L2.global.tile [%0, {%1, %2}];" :: "l"(tm), "r"(c0), "r"(c1) : "memory");
}
__device__ __forceinline__ void fence_async_smem() { asm volatile("fence.proxy.async.shared::cta;" ::: "memory"); }
__device__ __forceinline__ void wg_bar(int wg) {
  if (wg == 0) asm volatile("bar.sync 1, 128;" ::: "memory"); else asm volatile("bar.sync 2, 128;" ::: "memory");
}
__device__ __forceinline__ void wg_fence() { asm volatile("wgmma.fence.sync.aligned;" ::: "memory"); }
__device__ __forceinline__ void wg_commit() { asm volatile("wgmma.commit_group.sync.aligned;" ::: "memory"); }
template <int N> __device__ __forceinline__ void wg_wait() { asm volatile("wgmma.wait_group.sync.aligned %0;" :: "n"(N) : "memory"); }
template <int N> __device__ __forceinline__ void reg_fence(float (&d)[N]) {
#pragma unroll
  for (int i = 0; i < N; i++) asm volatile("" : "+f"(d[i]) :: "memory");
}
__device__ __forceinline__ uint64_t make_desc(uint32_t addr, uint32_t lbo, uint32_t sbo, uint32_t lt) {
  return (uint64_t)((addr & 0x3FFFF) >> 4) | ((uint64_t)(lbo >> 4) << 16) | ((uint64_t)(sbo >> 4) << 32) | ((uint64_t)lt << 62);
}
__device__ __forceinline__ uint32_t pack_bf16(float lo, float hi) {
  uint32_t r; asm("cvt.rn.bf16x2.f32 %0, %1, %2;" : "=r"(r) : "f"(hi), "f"(lo)); return r;
}
__device__ __forceinline__ float bf_lo(uint32_t v) { return __uint_as_float(v << 16); }
__device__ __forceinline__ float bf_hi(uint32_t v) { return __uint_as_float(v & 0xffff0000u); }
__device__ __forceinline__ float bf16r(float v) { return __bfloat162float(__float2bfloat16_rn(v)); }
__device__ __forceinline__ uint32_t hadd2_bf(uint32_t a, uint32_t b) {
  uint32_t r; asm("add.rn.bf16x2 %0, %1, %2;" : "=r"(r) : "r"(a), "r"(b)); return r;
}
__device__ __forceinline__ uint32_t hsub2_bf(uint32_t a, uint32_t b) {
  uint32_t r; asm("sub.rn.bf16x2 %0, %1, %2;" : "=r"(r) : "r"(a), "r"(b)); return r;
}
__device__ __forceinline__ float gelu_tanh(float u) {
  float inner = u * fmaf(0.035677408136300125f, u * u, 0.7978845608028654f);
  float th; asm("tanh.approx.f32 %0, %1;" : "=f"(th) : "f"(inner));
  float hu = 0.5f * u;
  return fmaf(hu, th, hu);
}
__device__ __forceinline__ void mma16816(float (&c)[4], uint32_t a0, uint32_t a1, uint32_t a2, uint32_t a3, uint32_t b0, uint32_t b1) {
  asm volatile("mma.sync.aligned.m16n8k16.row.col.f32.bf16.bf16.f32 {%0,%1,%2,%3}, {%4,%5,%6,%7}, {%8,%9}, {%0,%1,%2,%3};"
               : "+f"(c[0]), "+f"(c[1]), "+f"(c[2]), "+f"(c[3]) : "r"(a0), "r"(a1), "r"(a2), "r"(a3), "r"(b0), "r"(b1));
}

__device__ __forceinline__ void wgmma_ss_n224(float (&d)[112], uint64_t descA, uint64_t descB, int scaleD) {
  asm volatile("{\n.reg .pred p;\nsetp.ne.b32 p, %114, 0;\n"
    "wgmma.mma_async.sync.aligned.m64n224k16.f32.bf16.bf16 {%0, %1, %2, %3, %4, %5, %6, %7, %8, %9, %10, %11, %12, %13, %14, %15, %16, %17, %18, %19, %20, %21, %22, %23, %24, %25, %26, %27, %28, %29, %30, %31, %32, %33, %34, %35, %36, %37, %38, %39, %40, %41, %42, %43, %44, %45, %46, %47, %48, %49, %50, %51, %52, %53, %54, %55, %56, %57, %58, %59, %60, %61, %62, %63, %64, %65, %66, %67, %68, %69, %70, %71, %72, %73, %74, %75, %76, %77, %78, %79, %80, %81, %82, %83, %84, %85, %86, %87, %88, %89, %90, %91, %92, %93, %94, %95, %96, %97, %98, %99, %100, %101, %102, %103, %104, %105, %106, %107, %108, %109, %110, %111}, %112, %113, p, 1, 1, 0, 1;\n}\n"
    : "+f"(d[0]), "+f"(d[1]), "+f"(d[2]), "+f"(d[3]), "+f"(d[4]), "+f"(d[5]), "+f"(d[6]), "+f"(d[7]), "+f"(d[8]), "+f"(d[9]), "+f"(d[10]), "+f"(d[11]), "+f"(d[12]), "+f"(d[13]), "+f"(d[14]), "+f"(d[15]), "+f"(d[16]), "+f"(d[17]), "+f"(d[18]), "+f"(d[19]), "+f"(d[20]), "+f"(d[21]), "+f"(d[22]), "+f"(d[23]), "+f"(d[24]), "+f"(d[25]), "+f"(d[26]), "+f"(d[27]), "+f"(d[28]), "+f"(d[29]), "+f"(d[30]), "+f"(d[31]), "+f"(d[32]), "+f"(d[33]), "+f"(d[34]), "+f"(d[35]), "+f"(d[36]), "+f"(d[37]), "+f"(d[38]), "+f"(d[39]), "+f"(d[40]), "+f"(d[41]), "+f"(d[42]), "+f"(d[43]), "+f"(d[44]), "+f"(d[45]), "+f"(d[46]), "+f"(d[47]), "+f"(d[48]), "+f"(d[49]), "+f"(d[50]), "+f"(d[51]), "+f"(d[52]), "+f"(d[53]), "+f"(d[54]), "+f"(d[55]), "+f"(d[56]), "+f"(d[57]), "+f"(d[58]), "+f"(d[59]), "+f"(d[60]), "+f"(d[61]), "+f"(d[62]), "+f"(d[63]), "+f"(d[64]), "+f"(d[65]), "+f"(d[66]), "+f"(d[67]), "+f"(d[68]), "+f"(d[69]), "+f"(d[70]), "+f"(d[71]), "+f"(d[72]), "+f"(d[73]), "+f"(d[74]), "+f"(d[75]), "+f"(d[76]), "+f"(d[77]), "+f"(d[78]), "+f"(d[79]), "+f"(d[80]), "+f"(d[81]), "+f"(d[82]), "+f"(d[83]), "+f"(d[84]), "+f"(d[85]), "+f"(d[86]), "+f"(d[87]), "+f"(d[88]), "+f"(d[89]), "+f"(d[90]), "+f"(d[91]), "+f"(d[92]), "+f"(d[93]), "+f"(d[94]), "+f"(d[95]), "+f"(d[96]), "+f"(d[97]), "+f"(d[98]), "+f"(d[99]), "+f"(d[100]), "+f"(d[101]), "+f"(d[102]), "+f"(d[103]), "+f"(d[104]), "+f"(d[105]), "+f"(d[106]), "+f"(d[107]), "+f"(d[108]), "+f"(d[109]), "+f"(d[110]), "+f"(d[111])
    : "l"(descA), "l"(descB), "r"(scaleD));
}

__device__ __forceinline__ void wgmma_rs_n64(float (&d)[32], const uint32_t (&a)[4], uint64_t descB, int scaleD) {
  asm volatile("{\n.reg .pred p;\nsetp.ne.b32 p, %37, 0;\n"
    "wgmma.mma_async.sync.aligned.m64n64k16.f32.bf16.bf16 {%0, %1, %2, %3, %4, %5, %6, %7, %8, %9, %10, %11, %12, %13, %14, %15, %16, %17, %18, %19, %20, %21, %22, %23, %24, %25, %26, %27, %28, %29, %30, %31}, {%32, %33, %34, %35}, %36, p, 1, 1, 1;\n}\n"
    : "+f"(d[0]), "+f"(d[1]), "+f"(d[2]), "+f"(d[3]), "+f"(d[4]), "+f"(d[5]), "+f"(d[6]), "+f"(d[7]), "+f"(d[8]), "+f"(d[9]), "+f"(d[10]), "+f"(d[11]), "+f"(d[12]), "+f"(d[13]), "+f"(d[14]), "+f"(d[15]), "+f"(d[16]), "+f"(d[17]), "+f"(d[18]), "+f"(d[19]), "+f"(d[20]), "+f"(d[21]), "+f"(d[22]), "+f"(d[23]), "+f"(d[24]), "+f"(d[25]), "+f"(d[26]), "+f"(d[27]), "+f"(d[28]), "+f"(d[29]), "+f"(d[30]), "+f"(d[31])
    : "r"(a[0]), "r"(a[1]), "r"(a[2]), "r"(a[3]), "l"(descB), "r"(scaleD));
}

__host__ __device__ constexpr int step_kind(int i) { return (i == 0 || i == 1 || i == 3 || i == 6) ? 0 : (i == 7 ? 2 : 1); }
__host__ __device__ constexpr int step_k(int i) { return i == 0 ? 0 : i == 1 ? 1 : i == 2 ? 0 : i == 3 ? 2 : i == 4 ? 1 : i == 5 ? 2 : 3; }
__device__ __forceinline__ int step_slice(int i, int j) {
  const int kind = step_kind(i), k = step_k(i);
  const int base = (kind == 0) ? (j ^ 1) : j;
  return (k == 3) ? base : ((base + 2 * (k + 1)) & 7);
}

__global__ void __cluster_dims__(2, 1, 1) __launch_bounds__(NTHREADS, 1)
fused_mlp_kernel(const __grid_constant__ CUtensorMap tm_x, const __grid_constant__ CUtensorMap tm_w1, const __grid_constant__ CUtensorMap tm_w2,
                 const __nv_bfloat16* __restrict__ b1, const __nv_bfloat16* __restrict__ b2, __nv_bfloat16* __restrict__ out)
{
  extern __shared__ __align__(1024) unsigned char smem[];
  const uint32_t sbase = smem_u32(smem);
  const uint32_t bar_full = sbase + OFF_BAR;
  const uint32_t bar_cons = sbase + OFF_BAR + 256;
  const uint32_t bar_x = sbase + OFF_BAR + 512;
  const uint32_t bar_dfull = sbase + OFF_BAR + 528;
  const uint32_t bar_peer = sbase + OFF_BAR + 560;
  const int tid = threadIdx.x, warp = tid >> 5, lane = tid & 31;
  const int mb = blockIdx.x >> 3, j = blockIdx.x & 7;

  TSC(0);
  if (warp == 8) {
    if (lane == 0) {
      mbar_init(bar_x, 1); mbar_init(bar_x + 8, 1);
      asm volatile("fence.mbarrier_init.release.cluster;" ::: "memory");
      fence_async_smem();
      mbar_expect_tx(bar_x, 65536);
      tma_load_3d(sbase, &tm_x, 0, mb * BM, 0, bar_x);
      mbar_expect_tx(bar_x + 8, 65536);
      tma_load_3d(sbase + 65536, &tm_x, 0, mb * BM + 64, 0, bar_x + 8);
    }
    mbar_init(bar_full + 8 * lane, 1); mbar_init(bar_cons + 8 * lane, 2);
    if (lane < 4) mbar_init(bar_dfull + 8 * lane, 1);
    if (lane == 4) mbar_init(bar_peer, 2);
    asm volatile("fence.mbarrier_init.release.cluster;" ::: "memory");
    __syncwarp();
    if (lane < 4) mbar_expect_tx(bar_dfull + 8 * lane, DSLOT_BYTES);
    if (lane == 0) {
      fence_async_smem();
      for (int i = 0; i < NRING; i++) {
        mbar_expect_tx(bar_full + 8 * i, W1_BYTES);
        for (int a = 0; a < 4; a++)
          tma_load_2d(sbase + OFF_RING + i * SLOT_BYTES + a * 4096, &tm_w1, j * BF + a * 64, i * 32, bar_full + 8 * i);
      }
      TS(2, 1);
    }
    __syncwarp();
  }
  asm volatile("barrier.cluster.arrive.relaxed.aligned;" ::: "memory");
  __syncthreads();

  if (warp == 8) {
    if (lane == 0) {
      for (int t = 2 * mb; t < 2 * mb + 2; t++) {
        if (t < 16) { if (t >= NRING) for (int a = 0; a < 4; a++) tma_prefetch_2d(&tm_w1, j * BF + a * 64, t * 32); }
        else tma_prefetch_2d(&tm_w2, ((t - 16) >> 1) * 64, j * BF + ((t - 16) & 1) * 112);
      }
      int slot = 0;
      for (int i = NRING; i < NLOAD; i++) {
        mbar_wait(bar_cons + 8 * (i - NRING), 0);
        const uint32_t dst = sbase + OFF_RING + slot * SLOT_BYTES;
        if (++slot == NRING) slot = 0;
        if (i < 16) {
          mbar_expect_tx(bar_full + 8 * i, W1_BYTES);
          for (int a = 0; a < 4; a++) tma_load_2d(dst + a * 4096, &tm_w1, j * BF + a * 64, i * 32, bar_full + 8 * i);
        } else {
          mbar_expect_tx(bar_full + 8 * i, W2_BYTES);
          tma_load_2d(dst, &tm_w2, step_slice((i - 16) >> 1, j) * BN2, j * BF + ((i - 16) & 1) * 112, bar_full + 8 * i);
        }
      }
    }
    __syncwarp();
    asm volatile("barrier.cluster.wait.aligned;" ::: "memory");
  } else {
    const int wg = warp >> 2, w4 = warp & 3, t128 = tid & 127;
    const int q = lane & 3, g = lane >> 2;
    uint32_t* mean_s = reinterpret_cast<uint32_t*>(smem + OFF_MEAN) + wg * 64 + w4 * 16;
    uint32_t* b1s = reinterpret_cast<uint32_t*>(smem + OFF_B1 + wg * 512);
    uint32_t* b2s = reinterpret_cast<uint32_t*>(smem + OFF_B2 + wg * 128);
    uint32_t bias_a = 0, bias_b = 0;
    if (t128 < BF / 2) bias_a = reinterpret_cast<const uint32_t*>(b1 + j * BF)[t128];
    if (t128 < BN2 / 2) bias_b = reinterpret_cast<const uint32_t*>(b2 + j * BN2)[t128];
    const uint32_t epoch = g_epoch[blockIdx.x];

    unsigned char* ywg = smem + wg * 65536;
    float r0, r1;
    TSC(24);
    mbar_wait(bar_x + 8 * wg, 0);
    TSC(25);
    {
      float cs[2][4], c0[2][4], c1[2][4];
#pragma unroll
      for (int u = 0; u < 2; u++)
#pragma unroll
        for (int e = 0; e < 4; e++) { cs[u][e] = 0.f; c0[u][e] = 0.f; c1[u][e] = 0.f; }
      const int lrow = w4 * 16 + (lane & 7) + ((lane >> 3) & 1) * 8;
      const uint32_t lbase = sbase + wg * 65536 + lrow * 128;
      const uint32_t ones = 0x3F803F80u;
#pragma unroll 2
      for (int kb = 0; kb < 8; kb++) {
#pragma unroll
        for (int ks = 0; ks < 4; ks++) {
          uint32_t a0, a1, a2, a3;
          const uint32_t addr = lbase + kb * 8192 + (((2 * ks + (lane >> 4)) ^ (lane & 7)) << 4);
          asm volatile("ldmatrix.sync.aligned.m8n8.x4.shared.b16 {%0,%1,%2,%3}, [%4];" : "=r"(a0), "=r"(a1), "=r"(a2), "=r"(a3) : "r"(addr));
          mma16816(cs[ks & 1], a0, a1, a2, a3, ones, ones);
          mma16816(c0[ks & 1], a0, a1, a2, a3, a0, a2);
          mma16816(c1[ks & 1], a0, a1, a2, a3, a1, a3);
        }
      }
      const int dsrc = g * 4 + (g >> 1);
      const float q0 = __shfl_sync(0xffffffffu, (g & 1) ? c0[0][1] + c0[1][1] : c0[0][0] + c0[1][0], dsrc);
      const float q1 = __shfl_sync(0xffffffffu, (g & 1) ? c1[0][3] + c1[1][3] : c1[0][2] + c1[1][2], dsrc);
      const float m0 = (cs[0][0] + cs[1][0]) * (1.0f / D_MOD), m1 = (cs[0][2] + cs[1][2]) * (1.0f / D_MOD);
      const float v0 = fmaxf(fmaf(-m0, m0, q0 * (1.0f / D_MOD)), 0.f), v1 = fmaxf(fmaf(-m1, m1, q1 * (1.0f / D_MOD)), 0.f);
      if (q == 0) { mean_s[g] = pack_bf16(m0, m0); mean_s[g + 8] = pack_bf16(m1, m1); }
      __syncwarp();
#pragma unroll 4
      for (int r = 0; r < 16; r++) {
        const uint32_t ad = (uint32_t)((lane >> 3) * 8192 + (w4 * 16 + r) * 128 + (((lane & 7) ^ (r & 7)) << 4));
        const uint32_t m2 = mean_s[r];
        uint4 a = *reinterpret_cast<const uint4*>(ywg + ad), b = *reinterpret_cast<const uint4*>(ywg + ad + 4 * 8192);
        a.x = hsub2_bf(a.x, m2); a.y = hsub2_bf(a.y, m2); a.z = hsub2_bf(a.z, m2); a.w = hsub2_bf(a.w, m2);
        b.x = hsub2_bf(b.x, m2); b.y = hsub2_bf(b.y, m2); b.z = hsub2_bf(b.z, m2); b.w = hsub2_bf(b.w, m2);
        *reinterpret_cast<uint4*>(ywg + ad) = a;
        *reinterpret_cast<uint4*>(ywg + ad + 4 * 8192) = b;
      }
      r0 = 1.0f / bf16r(sqrtf(bf16r(bf16r(v0) + 1e-5f)));
      r1 = 1.0f / bf16r(sqrtf(bf16r(bf16r(v1) + 1e-5f)));
    }
    if (t128 < BF / 2) b1s[t128] = bias_a;
    if (t128 < BN2 / 2) b2s[t128] = bias_b;
    TSC(1);
    fence_async_smem();
    wg_bar(wg);
    TSC(2);

    uint32_t h[14][4];
    {
      float acc[112];
      int slot = 0;
#pragma unroll 2
      for (int kb = 0; kb < 16; kb++) {
        mbar_wait(bar_full + 8 * kb, 0);
        wg_fence();
        const uint32_t abase = sbase + wg * 65536 + (kb >> 1) * 8192 + (kb & 1) * 64;
        const uint32_t bbase = sbase + OFF_RING + slot * SLOT_BYTES;
        if (++slot == NRING) slot = 0;
#pragma unroll
        for (int kk = 0; kk < 2; kk++) {
          wgmma_ss_n224(acc, make_desc(abase + kk * 32, 16, 1024, 1), make_desc(bbase + kk * 2048, 4096, 1024, 1), (kb | kk) != 0);
        }
        wg_commit();
        if (kb > 0) { wg_wait<1>(); if (t128 == 0) mbar_arrive(bar_cons + 8 * (kb - 1)); }
      }
      wg_wait<0>();
      reg_fence(acc);
      asm volatile("barrier.cluster.wait.aligned;" ::: "memory");
      if (t128 == 0) { mbar_arrive(bar_cons + 8 * 15); mbar_arrive_remote(mapa(bar_peer, (j & 1) ^ 1)); }
      TSC(11);

#pragma unroll
      for (int i = 0; i < 28; i++) {
        const uint32_t bb = b1s[i * 4 + q];
        uint32_t p0 = hadd2_bf(pack_bf16(acc[4 * i] * r0, acc[4 * i + 1] * r0), bb);
        uint32_t p1 = hadd2_bf(pack_bf16(acc[4 * i + 2] * r1, acc[4 * i + 3] * r1), bb);
        h[i >> 1][(i & 1) * 2 + 0] = pack_bf16(gelu_tanh(bf_lo(p0)), gelu_tanh(bf_hi(p0)));
        h[i >> 1][(i & 1) * 2 + 1] = pack_bf16(gelu_tanh(bf_lo(p1)), gelu_tanh(bf_hi(p1)));
      }
    }

    const uint32_t par = (epoch + 1) & 1;
    float acc2[2][32];
    float sum[32];
#pragma unroll
    for (int i = 0; i < 32; i++) sum[i] = 0.f;
    uint4 pf[4];
    const uint32_t peer_din = mapa(sbase + OFF_DIN + wg * 8192, (j & 1) ^ 1);
    const uint32_t peer_dfull = mapa(bar_dfull, (j & 1) ^ 1);
    uint4* my_din = reinterpret_cast<uint4*>(smem + OFF_DIN) + wg * 512 + t128;
    uint4* my_dout = reinterpret_cast<uint4*>(smem + OFF_DOUT) + wg * 512 + t128;
    const uint4* in_part = &g_part[(size_t)((mb * NSPLIT + j) * 3) * 1024 + wg * 512 + t128];
    auto ld_part = [&](const uint4* p) {
      uint4 v;
      asm volatile("ld.relaxed.gpu.global.v4.u32 {%0, %1, %2, %3}, [%4];" : "=r"(v.x), "=r"(v.y), "=r"(v.z), "=r"(v.w) : "l"(p) : "memory");
      return v;
    };
    auto prefetch = [&](int k) {
#pragma unroll
      for (int c = 0; c < 4; c++) pf[c] = ld_part(in_part + k * 1024 + c * 128);
    };
    auto consume = [&](int k) {
#pragma unroll
      for (int c = 0; c < 4; c++) {
        uint4 v = pf[c];
        uint32_t it = 0;
        while ((((v.x ^ par) | (v.y ^ par) | (v.z ^ par) | (v.w ^ par)) & 1u) != 0) {
          v = ld_part(in_part + k * 1024 + c * 128);
          if (++it > (1u << 20)) asm volatile("trap;");
        }
        sum[c * 8 + 0] += bf_lo(v.x & ~1u); sum[c * 8 + 1] += bf_hi(v.x);
        sum[c * 8 + 2] += bf_lo(v.y & ~1u); sum[c * 8 + 3] += bf_hi(v.y);
        sum[c * 8 + 4] += bf_lo(v.z & ~1u); sum[c * 8 + 5] += bf_hi(v.z);
        sum[c * 8 + 6] += bf_lo(v.w & ~1u); sum[c * 8 + 7] += bf_hi(v.w);
      }
    };
    auto post = [&](int st, float (&a)[32]) {
      const int kind = step_kind(st), k = step_k(st);
      if (kind == 0) {
        if (st == 0) mbar_wait(bar_cons + 8 * 15, 0);
#pragma unroll
        for (int c = 0; c < 4; c++) {
          uint4 v;
          v.x = pack_bf16(a[c * 8 + 0], a[c * 8 + 1]); v.y = pack_bf16(a[c * 8 + 2], a[c * 8 + 3]);
          v.z = pack_bf16(a[c * 8 + 4], a[c * 8 + 5]); v.w = pack_bf16(a[c * 8 + 6], a[c * 8 + 7]);
          my_dout[k * 1024 + c * 128] = v;
        }
        fence_async_smem();
        wg_bar(wg);
        if (t128 == 0) {
          if (st == 0) mbar_wait_cluster(bar_peer, 0);
          asm volatile("cp.async.bulk.shared::cluster.shared::cta.mbarrier::complete_tx::bytes [%0], [%1], %2, [%3];"
                       :: "r"(peer_din + k * DSLOT_BYTES), "r"(sbase + OFF_DOUT + k * DSLOT_BYTES + wg * 8192), "r"(8192), "r"(peer_dfull + 8 * k) : "memory");
        }
      } else {
        mbar_wait_cluster(bar_dfull + 8 * k, 0);
#pragma unroll
        for (int c = 0; c < 4; c++) {
          const uint4 d = my_din[k * 1024 + c * 128];
          uint4 v;
          v.x = (pack_bf16(a[c * 8 + 0] + bf_lo(d.x), a[c * 8 + 1] + bf_hi(d.x)) & ~1u) | par;
          v.y = (pack_bf16(a[c * 8 + 2] + bf_lo(d.y), a[c * 8 + 3] + bf_hi(d.y)) & ~1u) | par;
          v.z = (pack_bf16(a[c * 8 + 4] + bf_lo(d.z), a[c * 8 + 5] + bf_hi(d.z)) & ~1u) | par;
          v.w = (pack_bf16(a[c * 8 + 6] + bf_lo(d.w), a[c * 8 + 7] + bf_hi(d.w)) & ~1u) | par;
          my_din[k * 1024 + c * 128] = v;
        }
        fence_async_smem();
        wg_bar(wg);
        if (t128 == 0) {
          const int dest = (j + 2 * (k + 1)) & 7;
          const uint4* p = &g_part[(size_t)((mb * NSPLIT + dest) * 3 + k) * 1024 + wg * 512];
          asm volatile("cp.async.bulk.global.shared::cta.bulk_group [%0], [%1], %2;"
                       :: "l"(p), "r"(sbase + OFF_DIN + k * DSLOT_BYTES + wg * 8192), "r"(8192) : "memory");
          asm volatile("cp.async.bulk.commit_group;" ::: "memory");
        }
      }
    };
#pragma unroll
    for (int i = 0; i < 8; i++) {
      TSC(12 + i);
      mbar_wait(bar_full + 8 * (16 + 2 * i), 0);
      wg_fence();
#pragma unroll
      for (int ks = 0; ks < 7; ks++) {
        wgmma_rs_n64(acc2[i & 1], h[ks], make_desc(sbase + OFF_RING + ((16 + 2 * i) % NRING) * SLOT_BYTES + ks * 2048, 16, 1024, 1), ks != 0);
      }
      mbar_wait(bar_full + 8 * (17 + 2 * i), 0);
      wg_fence();
#pragma unroll
      for (int ks = 0; ks < 7; ks++) {
        wgmma_rs_n64(acc2[i & 1], h[7 + ks], make_desc(sbase + OFF_RING + ((17 + 2 * i) % NRING) * SLOT_BYTES + ks * 2048, 16, 1024, 1), 1);
      }
      wg_commit();
      if (i > 0) {
        wg_wait<1>();
        reg_fence(acc2[(i - 1) & 1]);
        if (i <= 5 && t128 == 0) { mbar_arrive(bar_cons + 8 * (16 + 2 * (i - 1))); mbar_arrive(bar_cons + 8 * (17 + 2 * (i - 1))); }
        post(i - 1, acc2[(i - 1) & 1]);
      }
      if (i == 6) prefetch(0);
      if (i == 7) { consume(0); prefetch(1); }
    }
    consume(1);
    prefetch(2);
    mbar_wait_cluster(bar_dfull + 8 * 3, 0);
#pragma unroll
    for (int c = 0; c < 4; c++) {
      const uint4 d = my_din[3 * 1024 + c * 128];
      sum[c * 8 + 0] += bf_lo(d.x); sum[c * 8 + 1] += bf_hi(d.x); sum[c * 8 + 2] += bf_lo(d.y); sum[c * 8 + 3] += bf_hi(d.y);
      sum[c * 8 + 4] += bf_lo(d.z); sum[c * 8 + 5] += bf_hi(d.z); sum[c * 8 + 6] += bf_lo(d.w); sum[c * 8 + 7] += bf_hi(d.w);
    }
    wg_wait<0>();
    reg_fence(acc2[1]);
    TSC(20);
    consume(2);
    TSC(21);
    if (tid == 0) g_epoch[blockIdx.x] = epoch + 1;

    {
      const int row0 = mb * BM + wg * 64 + w4 * 16 + g;
      uint32_t* o0 = reinterpret_cast<uint32_t*>(out + (size_t)row0 * D_MOD + j * BN2) + q;
      uint32_t* o1 = o0 + 8 * D_MOD / 2;
#pragma unroll
      for (int i = 0; i < 8; i++) {
        const uint32_t bb = b2s[i * 4 + q];
        o0[i * 4] = hadd2_bf(pack_bf16(acc2[1][4 * i] + sum[4 * i], acc2[1][4 * i + 1] + sum[4 * i + 1]), bb);
        o1[i * 4] = hadd2_bf(pack_bf16(acc2[1][4 * i + 2] + sum[4 * i + 2], acc2[1][4 * i + 3] + sum[4 * i + 3]), bb);
      }
    }
    if (t128 == 0) asm volatile("cp.async.bulk.wait_group 0;" ::: "memory");
    TSC(26);
  }
  asm volatile("barrier.cluster.arrive.relaxed.aligned;\nbarrier.cluster.wait.aligned;" ::: "memory");
}

typedef CUresult (*EncodeFn)(CUtensorMap*, CUtensorMapDataType, cuuint32_t, void*, const cuuint64_t*, const cuuint64_t*,
                             const cuuint32_t*, const cuuint32_t*, CUtensorMapInterleave, CUtensorMapSwizzle,
                             CUtensorMapL2promotion, CUtensorMapFloatOOBfill);

}

extern "C" void kernel_launch(void* const* d_in, const int* in_sizes, int n_in, void* d_out, int out_size) {
  (void)in_sizes; (void)n_in; (void)out_size;
  static CUtensorMap tm_x, tm_w1, tm_w2;
  static const void* cached_w1 = nullptr; static const void* cached_w2 = nullptr; static const void* cached_x = nullptr;
  const void* w1 = d_in[1]; const void* w2 = d_in[3]; const void* xp = d_in[0];
  if (cached_w1 != w1 || cached_w2 != w2 || cached_x != xp) {
    void* fn = nullptr; cudaDriverEntryPointQueryResult st;
    cudaGetDriverEntryPoint("cuTensorMapEncodeTiled", &fn, cudaEnableDefault, &st);
    EncodeFn enc = (EncodeFn)fn;
    {
      cuuint64_t dims[3] = {64, (cuuint64_t)S_TOK, (cuuint64_t)(D_MOD / 64)};
      cuuint64_t strides[2] = {(cuuint64_t)D_MOD * 2, 128};
      cuuint32_t box[3] = {64, 64, 8};
      cuuint32_t es[3] = {1, 1, 1};
      enc(&tm_x, CU_TENSOR_MAP_DATA_TYPE_BFLOAT16, 3, const_cast<void*>(xp), dims, strides, box, es,
          CU_TENSOR_MAP_INTERLEAVE_NONE, CU_TENSOR_MAP_SWIZZLE_128B, CU_TENSOR_MAP_L2_PROMOTION_L2_128B, CU_TENSOR_MAP_FLOAT_OOB_FILL_NONE);
    }
    {
      cuuint64_t dims[2] = {(cuuint64_t)F_HID, (cuuint64_t)D_MOD};
      cuuint64_t strides[1] = {(cuuint64_t)F_HID * 2};
      cuuint32_t box[2] = {64, 32};
      cuuint32_t es[2] = {1, 1};
      enc(&tm_w1, CU_TENSOR_MAP_DATA_TYPE_BFLOAT16, 2, const_cast<void*>(w1), dims, strides, box, es,
          CU_TENSOR_MAP_INTERLEAVE_NONE, CU_TENSOR_MAP_SWIZZLE_128B, CU_TENSOR_MAP_L2_PROMOTION_L2_128B, CU_TENSOR_MAP_FLOAT_OOB_FILL_NONE);
    }
    {
      cuuint64_t dims[2] = {(cuuint64_t)D_MOD, (cuuint64_t)F_HID};
      cuuint64_t strides[1] = {(cuuint64_t)D_MOD * 2};
      cuuint32_t box[2] = {64, 112};
      cuuint32_t es[2] = {1, 1};
      enc(&tm_w2, CU_TENSOR_MAP_DATA_TYPE_BFLOAT16, 2, const_cast<void*>(w2), dims, strides, box, es,
          CU_TENSOR_MAP_INTERLEAVE_NONE, CU_TENSOR_MAP_SWIZZLE_128B, CU_TENSOR_MAP_L2_PROMOTION_L2_128B, CU_TENSOR_MAP_FLOAT_OOB_FILL_NONE);
    }
    cudaFuncSetAttribute(fused_mlp_kernel, cudaFuncAttributeMaxDynamicSharedMemorySize, SMEM_TOTAL);
    cached_w1 = w1; cached_w2 = w2; cached_x = xp;
  }
  fused_mlp_kernel<<<NMB * NSPLIT, NTHREADS, SMEM_TOTAL>>>(tm_x, tm_w1, tm_w2,
      (const __nv_bfloat16*)d_in[2], (const __nv_bfloat16*)d_in[4], (__nv_bfloat16*)d_out);
}
```

```cpp
#include <cuda_runtime.h>
#include <cuda_bf16.h>
#include <cuda.h>
#include <stdint.h>

namespace {

constexpr int S_TOK = 2048, D_MOD = 512, F_HID = 1792;
constexpr int BM = 128, NSPLIT = 8, BF = F_HID / NSPLIT;
constexpr int BN2 = D_MOD / NSPLIT;
constexpr int NMB = S_TOK / BM;
constexpr int SLOT_BYTES = 16384;
constexpr int W1_BYTES = 16384;
constexpr int W2_BYTES = 14336;
constexpr int Y_BYTES = BM * D_MOD * 2;
constexpr int NRING = 6;
constexpr int NLOAD = 32;
constexpr int OFF_RING = Y_BYTES;
__host__ __device__ constexpr int yslot_off(int s) { return (s >> 1) * 65536 + (s & 1) * 16384; }
__host__ __device__ constexpr int uslot_off(int s) { return (s >> 1) * 65536 + 32768 + (s & 1) * 16384; }
constexpr int DSLOT_BYTES = 16384;
constexpr int OFF_BAR = OFF_RING + NRING * SLOT_BYTES;
constexpr int OFF_MEAN = OFF_BAR + 640;
constexpr int OFF_B1 = OFF_MEAN + 512;
constexpr int OFF_B2 = OFF_B1 + 1024;
constexpr int SMEM_TOTAL = OFF_B2 + 256;
constexpr int NTHREADS = 384;
static_assert(SMEM_TOTAL <= 232448, "smem");

__device__ uint4 g_part[(size_t)NMB * NSPLIT * 3 * 1024];
__device__ unsigned int g_epoch[NMB * NSPLIT];

#define TS_DECL
#define TS_FLUSH do {} while (0)
#define TS(role, idx) do {} while (0)
#define TSC(idx) do {} while (0)

__device__ __forceinline__ uint32_t smem_u32(const void* p) { return (uint32_t)__cvta_generic_to_shared(p); }
__device__ __forceinline__ uint32_t mapa(uint32_t a, uint32_t r) {
  uint32_t d; asm volatile("mapa.shared::cluster.u32 %0, %1, %2;" : "=r"(d) : "r"(a), "r"(r)); return d;
}
__device__ __forceinline__ void mbar_init(uint32_t bar, uint32_t cnt) {
  asm volatile("mbarrier.init.shared::cta.b64 [%0], %1;" :: "r"(bar), "r"(cnt) : "memory");
}
__device__ __forceinline__ void mbar_expect_tx(uint32_t bar, uint32_t bytes) {
  asm volatile("mbarrier.arrive.expect_tx.shared::cta.b64 _, [%0], %1;" :: "r"(bar), "r"(bytes) : "memory");
}
__device__ __forceinline__ void mbar_arrive(uint32_t bar) {
  asm volatile("mbarrier.arrive.shared::cta.b64 _, [%0];" :: "r"(bar) : "memory");
}
__device__ __forceinline__ void mbar_arrive_remote(uint32_t rbar) {
  asm volatile("mbarrier.arrive.release.cluster.shared::cluster.b64 _, [%0];" :: "r"(rbar) : "memory");
}
__device__ __forceinline__ void mbar_wait(uint32_t bar, uint32_t parity) {
  uint32_t done = 0; uint32_t it = 0;
  while (true) {
    asm volatile("{\n.reg .pred p;\nmbarrier.try_wait.parity.shared::cta.b64 p, [%1], %2;\nselp.u32 %0, 1, 0, p;\n}"
                 : "=r"(done) : "r"(bar), "r"(parity) : "memory");
    if (done) break;
    if (++it > (1u << 22)) asm volatile("trap;");
  }
}
__device__ __forceinline__ void mbar_wait_cluster(uint32_t bar, uint32_t parity) {
  uint32_t done = 0; uint32_t it = 0;
  while (true) {
    asm volatile("{\n.reg .pred p;\nmbarrier.try_wait.parity.acquire.cluster.shared::cta.b64 p, [%1], %2;\nselp.u32 %0, 1, 0, p;\n}"
                 : "=r"(done) : "r"(bar), "r"(parity) : "memory");
    if (done) break;
    if (++it > (1u << 22)) asm volatile("trap;");
  }
}
__device__ __forceinline__ void tma_load_3d(uint32_t dst, const CUtensorMap* tm, int c0, int c1, int c2, uint32_t bar) {
  asm volatile("cp.async.bulk.tensor.3d.shared::cluster.global.mbarrier::complete_tx::bytes [%0], [%1, {%3, %4, %5}], [%2];"
               :: "r"(dst), "l"(tm), "r"(bar), "r"(c0), "r"(c1), "r"(c2) : "memory");
}
__device__ __forceinline__ void tma_load_2d(uint32_t dst, const CUtensorMap* tm, int c0, int c1, uint32_t bar) {
  asm volatile("cp.async.bulk.tensor.2d.shared::cluster.global.mbarrier::complete_tx::bytes [%0], [%1, {%3, %4}], [%2];"
               :: "r"(dst), "l"(tm), "r"(bar), "r"(c0), "r"(c1) : "memory");
}
__device__ __forceinline__ void tma_prefetch_2d(const CUtensorMap* tm, int c0, int c1) {
  asm volatile("cp.async.bulk.prefetch.tensor.2d.L2.global.tile [%0, {%1, %2}];" :: "l"(tm), "r"(c0), "r"(c1) : "memory");
}
__device__ __forceinline__ void fence_async_smem() { asm volatile("fence.proxy.async.shared::cta;" ::: "memory"); }
__device__ __forceinline__ void wg_bar(int wg) {
  if (wg == 0) asm volatile("bar.sync 1, 128;" ::: "memory"); else asm volatile("bar.sync 2, 128;" ::: "memory");
}
__device__ __forceinline__ void wg_fence() { asm volatile("wgmma.fence.sync.aligned;" ::: "memory"); }
__device__ __forceinline__ void wg_commit() { asm volatile("wgmma.commit_group.sync.aligned;" ::: "memory"); }
template <int N> __device__ __forceinline__ void wg_wait() { asm volatile("wgmma.wait_group.sync.aligned %0;" :: "n"(N) : "memory"); }
template <int N> __device__ __forceinline__ void reg_fence(float (&d)[N]) {
#pragma unroll
  for (int i = 0; i < N; i++) asm volatile("" : "+f"(d[i]) :: "memory");
}
__device__ __forceinline__ uint64_t make_desc(uint32_t addr, uint32_t lbo, uint32_t sbo, uint32_t lt) {
  return (uint64_t)((addr & 0x3FFFF) >> 4) | ((uint64_t)(lbo >> 4) << 16) | ((uint64_t)(sbo >> 4) << 32) | ((uint64_t)lt << 62);
}
__device__ __forceinline__ uint32_t pack_bf16(float lo, float hi) {
  uint32_t r; asm("cvt.rn.bf16x2.f32 %0, %1, %2;" : "=r"(r) : "f"(hi), "f"(lo)); return r;
}
__device__ __forceinline__ float bf_lo(uint32_t v) { return __uint_as_float(v << 16); }
__device__ __forceinline__ float bf_hi(uint32_t v) { return __uint_as_float(v & 0xffff0000u); }
__device__ __forceinline__ float bf16r(float v) { return __bfloat162float(__float2bfloat16_rn(v)); }
__device__ __forceinline__ uint32_t hadd2_bf(uint32_t a, uint32_t b) {
  uint32_t r; asm("add.rn.bf16x2 %0, %1, %2;" : "=r"(r) : "r"(a), "r"(b)); return r;
}
__device__ __forceinline__ uint32_t hsub2_bf(uint32_t a, uint32_t b) {
  uint32_t r; asm("sub.rn.bf16x2 %0, %1, %2;" : "=r"(r) : "r"(a), "r"(b)); return r;
}
__device__ __forceinline__ float gelu_tanh(float u) {
  float inner = u * fmaf(0.035677408136300125f, u * u, 0.7978845608028654f);
  float th; asm("tanh.approx.f32 %0, %1;" : "=f"(th) : "f"(inner));
  float hu = 0.5f * u;
  return fmaf(hu, th, hu);
}
__device__ __forceinline__ void mma16816(float (&c)[4], uint32_t a0, uint32_t a1, uint32_t a2, uint32_t a3, uint32_t b0, uint32_t b1) {
  asm volatile("mma.sync.aligned.m16n8k16.row.col.f32.bf16.bf16.f32 {%0,%1,%2,%3}, {%4,%5,%6,%7}, {%8,%9}, {%0,%1,%2,%3};"
               : "+f"(c[0]), "+f"(c[1]), "+f"(c[2]), "+f"(c[3]) : "r"(a0), "r"(a1), "r"(a2), "r"(a3), "r"(b0), "r"(b1));
}

__device__ __forceinline__ void wgmma_ss_n224(float (&d)[112], uint64_t descA, uint64_t descB, int scaleD) {
  asm volatile("{\n.reg .pred p;\nsetp.ne.b32 p, %114, 0;\n"
    "wgmma.mma_async.sync.aligned.m64n224k16.f32.bf16.bf16 {%0, %1, %2, %3, %4, %5, %6, %7, %8, %9, %10, %11, %12, %13, %14, %15, %16, %17, %18, %19, %20, %21, %22, %23, %24, %25, %26, %27, %28, %29, %30, %31, %32, %33, %34, %35, %36, %37, %38, %39, %40, %41, %42, %43, %44, %45, %46, %47, %48, %49, %50, %51, %52, %53, %54, %55, %56, %57, %58, %59, %60, %61, %62, %63, %64, %65, %66, %67, %68, %69, %70, %71, %72, %73, %74, %75, %76, %77, %78, %79, %80, %81, %82, %83, %84, %85, %86, %87, %88, %89, %90, %91, %92, %93, %94, %95, %96, %97, %98, %99, %100, %101, %102, %103, %104, %105, %106, %107, %108, %109, %110, %111}, %112, %113, p, 1, 1, 0, 1;\n}\n"
    : "+f"(d[0]), "+f"(d[1]), "+f"(d[2]), "+f"(d[3]), "+f"(d[4]), "+f"(d[5]), "+f"(d[6]), "+f"(d[7]), "+f"(d[8]), "+f"(d[9]), "+f"(d[10]), "+f"(d[11]), "+f"(d[12]), "+f"(d[13]), "+f"(d[14]), "+f"(d[15]), "+f"(d[16]), "+f"(d[17]), "+f"(d[18]), "+f"(d[19]), "+f"(d[20]), "+f"(d[21]), "+f"(d[22]), "+f"(d[23]), "+f"(d[24]), "+f"(d[25]), "+f"(d[26]), "+f"(d[27]), "+f"(d[28]), "+f"(d[29]), "+f"(d[30]), "+f"(d[31]), "+f"(d[32]), "+f"(d[33]), "+f"(d[34]), "+f"(d[35]), "+f"(d[36]), "+f"(d[37]), "+f"(d[38]), "+f"(d[39]), "+f"(d[40]), "+f"(d[41]), "+f"(d[42]), "+f"(d[43]), "+f"(d[44]), "+f"(d[45]), "+f"(d[46]), "+f"(d[47]), "+f"(d[48]), "+f"(d[49]), "+f"(d[50]), "+f"(d[51]), "+f"(d[52]), "+f"(d[53]), "+f"(d[54]), "+f"(d[55]), "+f"(d[56]), "+f"(d[57]), "+f"(d[58]), "+f"(d[59]), "+f"(d[60]), "+f"(d[61]), "+f"(d[62]), "+f"(d[63]), "+f"(d[64]), "+f"(d[65]), "+f"(d[66]), "+f"(d[67]), "+f"(d[68]), "+f"(d[69]), "+f"(d[70]), "+f"(d[71]), "+f"(d[72]), "+f"(d[73]), "+f"(d[74]), "+f"(d[75]), "+f"(d[76]), "+f"(d[77]), "+f"(d[78]), "+f"(d[79]), "+f"(d[80]), "+f"(d[81]), "+f"(d[82]), "+f"(d[83]), "+f"(d[84]), "+f"(d[85]), "+f"(d[86]), "+f"(d[87]), "+f"(d[88]), "+f"(d[89]), "+f"(d[90]), "+f"(d[91]), "+f"(d[92]), "+f"(d[93]), "+f"(d[94]), "+f"(d[95]), "+f"(d[96]), "+f"(d[97]), "+f"(d[98]), "+f"(d[99]), "+f"(d[100]), "+f"(d[101]), "+f"(d[102]), "+f"(d[103]), "+f"(d[104]), "+f"(d[105]), "+f"(d[106]), "+f"(d[107]), "+f"(d[108]), "+f"(d[109]), "+f"(d[110]), "+f"(d[111])
    : "l"(descA), "l"(descB), "r"(scaleD));
}

__device__ __forceinline__ void wgmma_rs_n64(float (&d)[32], const uint32_t (&a)[4], uint64_t descB, int scaleD) {
  asm volatile("{\n.reg .pred p;\nsetp.ne.b32 p, %37, 0;\n"
    "wgmma.mma_async.sync.aligned.m64n64k16.f32.bf16.bf16 {%0, %1, %2, %3, %4, %5, %6, %7, %8, %9, %10, %11, %12, %13, %14, %15, %16, %17, %18, %19, %20, %21, %22, %23, %24, %25, %26, %27, %28, %29, %30, %31}, {%32, %33, %34, %35}, %36, p, 1, 1, 1;\n}\n"
    : "+f"(d[0]), "+f"(d[1]), "+f"(d[2]), "+f"(d[3]), "+f"(d[4]), "+f"(d[5]), "+f"(d[6]), "+f"(d[7]), "+f"(d[8]), "+f"(d[9]), "+f"(d[10]), "+f"(d[11]), "+f"(d[12]), "+f"(d[13]), "+f"(d[14]), "+f"(d[15]), "+f"(d[16]), "+f"(d[17]), "+f"(d[18]), "+f"(d[19]), "+f"(d[20]), "+f"(d[21]), "+f"(d[22]), "+f"(d[23]), "+f"(d[24]), "+f"(d[25]), "+f"(d[26]), "+f"(d[27]), "+f"(d[28]), "+f"(d[29]), "+f"(d[30]), "+f"(d[31])
    : "r"(a[0]), "r"(a[1]), "r"(a[2]), "r"(a[3]), "l"(descB), "r"(scaleD));
}

__device__ __forceinline__ void wgmma_rs_n224(float (&d)[112], const uint32_t (&a)[4], uint64_t descB, int scaleD) {
  asm volatile("{\n.reg .pred p;\nsetp.ne.b32 p, %117, 0;\n"
    "wgmma.mma_async.sync.aligned.m64n224k16.f32.bf16.bf16 {%0, %1, %2, %3, %4, %5, %6, %7, %8, %9, %10, %11, %12, %13, %14, %15, %16, %17, %18, %19, %20, %21, %22, %23, %24, %25, %26, %27, %28, %29, %30, %31, %32, %33, %34, %35, %36, %37, %38, %39, %40, %41, %42, %43, %44, %45, %46, %47, %48, %49, %50, %51, %52, %53, %54, %55, %56, %57, %58, %59, %60, %61, %62, %63, %64, %65, %66, %67, %68, %69, %70, %71, %72, %73, %74, %75, %76, %77, %78, %79, %80, %81, %82, %83, %84, %85, %86, %87, %88, %89, %90, %91, %92, %93, %94, %95, %96, %97, %98, %99, %100, %101, %102, %103, %104, %105, %106, %107, %108, %109, %110, %111}, {%112, %113, %114, %115}, %116, p, 1, 1, 1;\n}\n"
    : "+f"(d[0]), "+f"(d[1]), "+f"(d[2]), "+f"(d[3]), "+f"(d[4]), "+f"(d[5]), "+f"(d[6]), "+f"(d[7]), "+f"(d[8]), "+f"(d[9]), "+f"(d[10]), "+f"(d[11]), "+f"(d[12]), "+f"(d[13]), "+f"(d[14]), "+f"(d[15]), "+f"(d[16]), "+f"(d[17]), "+f"(d[18]), "+f"(d[19]), "+f"(d[20]), "+f"(d[21]), "+f"(d[22]), "+f"(d[23]), "+f"(d[24]), "+f"(d[25]), "+f"(d[26]), "+f"(d[27]), "+f"(d[28]), "+f"(d[29]), "+f"(d[30]), "+f"(d[31]), "+f"(d[32]), "+f"(d[33]), "+f"(d[34]), "+f"(d[35]), "+f"(d[36]), "+f"(d[37]), "+f"(d[38]), "+f"(d[39]), "+f"(d[40]), "+f"(d[41]), "+f"(d[42]), "+f"(d[43]), "+f"(d[44]), "+f"(d[45]), "+f"(d[46]), "+f"(d[47]), "+f"(d[48]), "+f"(d[49]), "+f"(d[50]), "+f"(d[51]), "+f"(d[52]), "+f"(d[53]), "+f"(d[54]), "+f"(d[55]), "+f"(d[56]), "+f"(d[57]), "+f"(d[58]), "+f"(d[59]), "+f"(d[60]), "+f"(d[61]), "+f"(d[62]), "+f"(d[63]), "+f"(d[64]), "+f"(d[65]), "+f"(d[66]), "+f"(d[67]), "+f"(d[68]), "+f"(d[69]), "+f"(d[70]), "+f"(d[71]), "+f"(d[72]), "+f"(d[73]), "+f"(d[74]), "+f"(d[75]), "+f"(d[76]), "+f"(d[77]), "+f"(d[78]), "+f"(d[79]), "+f"(d[80]), "+f"(d[81]), "+f"(d[82]), "+f"(d[83]), "+f"(d[84]), "+f"(d[85]), "+f"(d[86]), "+f"(d[87]), "+f"(d[88]), "+f"(d[89]), "+f"(d[90]), "+f"(d[91]), "+f"(d[92]), "+f"(d[93]), "+f"(d[94]), "+f"(d[95]), "+f"(d[96]), "+f"(d[97]), "+f"(d[98]), "+f"(d[99]), "+f"(d[100]), "+f"(d[101]), "+f"(d[102]), "+f"(d[103]), "+f"(d[104]), "+f"(d[105]), "+f"(d[106]), "+f"(d[107]), "+f"(d[108]), "+f"(d[109]), "+f"(d[110]), "+f"(d[111])
    : "r"(a[0]), "r"(a[1]), "r"(a[2]), "r"(a[3]), "l"(descB), "r"(scaleD));
}

__host__ __device__ constexpr int step_kind(int i) { return (i == 0 || i == 1 || i == 3 || i == 6) ? 0 : (i == 7 ? 2 : 1); }
__host__ __device__ constexpr int step_k(int i) { return i == 0 ? 0 : i == 1 ? 1 : i == 2 ? 0 : i == 3 ? 2 : i == 4 ? 1 : i == 5 ? 2 : 3; }
__device__ __forceinline__ int step_slice(int i, int j) {
  const int kind = step_kind(i), k = step_k(i);
  const int base = (kind == 0) ? (j ^ 1) : j;
  return (k == 3) ? base : ((base + 2 * (k + 1)) & 7);
}

__host__ __device__ constexpr int load_off(int i) {
  return i < 6 ? OFF_RING + i * SLOT_BYTES : (i < 10 ? yslot_off(i - 6) : OFF_RING + ((i - 10) % NRING) * SLOT_BYTES);
}
__host__ __device__ constexpr int load_dep(int i) { return i < 6 ? -1 : (i < 10 ? -2 : (i < 16 ? i - 10 : i - 6)); }

__global__ void __cluster_dims__(2, 1, 1) __launch_bounds__(NTHREADS, 1)
fused_mlp_kernel(const __grid_constant__ CUtensorMap tm_x, const __grid_constant__ CUtensorMap tm_w1, const __grid_constant__ CUtensorMap tm_w2,
                 const __nv_bfloat16* __restrict__ b1, const __nv_bfloat16* __restrict__ b2, __nv_bfloat16* __restrict__ out)
{
  extern __shared__ __align__(1024) unsigned char smem[];
  const uint32_t sbase = smem_u32(smem);
  const uint32_t bar_full = sbase + OFF_BAR;
  const uint32_t bar_cons = sbase + OFF_BAR + 256;
  const uint32_t bar_x = sbase + OFF_BAR + 512;
  const uint32_t bar_dfull = sbase + OFF_BAR + 528;
  const uint32_t bar_peer = sbase + OFF_BAR + 560;
  const uint32_t bar_ln = sbase + OFF_BAR + 568;
  const int tid = threadIdx.x, warp = tid >> 5, lane = tid & 31;
  const int mb = blockIdx.x >> 3, j = blockIdx.x & 7;

  TS_DECL
  TSC(0);
  if (warp == 8) {
    if (lane == 0) {
      mbar_init(bar_x, 1);
      asm volatile("fence.mbarrier_init.release.cluster;" ::: "memory");
      fence_async_smem();
      mbar_expect_tx(bar_x, 131072);
      tma_load_3d(sbase, &tm_x, 0, mb * BM, 0, bar_x);
      tma_load_3d(sbase + 65536, &tm_x, 0, mb * BM + 64, 0, bar_x);
    }
    if (lane == 1) asm volatile("prefetch.tensormap [%0];" :: "l"(&tm_w1) : "memory");
    if (lane == 2) asm volatile("prefetch.tensormap [%0];" :: "l"(&tm_w2) : "memory");
    mbar_init(bar_full + 8 * lane, 1); mbar_init(bar_cons + 8 * lane, 2);
    if (lane < 4) mbar_init(bar_dfull + 8 * lane, 1);
    if (lane == 4) mbar_init(bar_peer, 2);
    if (lane == 5) mbar_init(bar_ln, 2);
    asm volatile("fence.mbarrier_init.release.cluster;" ::: "memory");
    fence_async_smem();
    __syncwarp();
    if (lane < 4) mbar_expect_tx(bar_dfull + 8 * lane, DSLOT_BYTES);
    __syncwarp();
  }
  asm volatile("barrier.cluster.arrive.relaxed.aligned;" ::: "memory");
  __syncthreads();

  if (warp >= 8) {
    asm volatile("setmaxnreg.dec.sync.aligned.u32 40;");
    if (warp == 8 && lane == 0) {
      for (int i = 0; i < NRING; i++) {
        mbar_expect_tx(bar_full + 8 * i, W1_BYTES);
        for (int a = 0; a < 4; a++)
          tma_load_2d(sbase + OFF_RING + i * SLOT_BYTES + a * 4096, &tm_w1, j * BF + a * 64, i * 32, bar_full + 8 * i);
      }
      TS(2, 1);
      for (int t = 2 * mb; t < 2 * mb + 2; t++) {
        if (t < 16) { if (t >= NRING) for (int a = 0; a < 4; a++) tma_prefetch_2d(&tm_w1, j * BF + a * 64, t * 32); }
        else tma_prefetch_2d(&tm_w2, ((t - 16) >> 1) * 64, j * BF + ((t - 16) & 1) * 112);
      }
#pragma unroll
      for (int i = NRING; i < NLOAD; i++) {
        if (load_dep(i) >= 0) mbar_wait(bar_cons + 8 * load_dep(i), 0); else if (i == NRING) mbar_wait(bar_ln, 0);
        TS(2, i);
        const uint32_t dst = sbase + load_off(i);
        if (i < 16) {
          mbar_expect_tx(bar_full + 8 * i, W1_BYTES);
          for (int a = 0; a < 4; a++) tma_load_2d(dst + a * 4096, &tm_w1, j * BF + a * 64, i * 32, bar_full + 8 * i);
        } else {
          mbar_expect_tx(bar_full + 8 * i, W2_BYTES);
          tma_load_2d(dst, &tm_w2, step_slice((i - 16) >> 1, j) * BN2, j * BF + ((i - 16) & 1) * 112, bar_full + 8 * i);
        }
      }
    }
    __syncwarp();
    asm volatile("barrier.cluster.wait.aligned;" ::: "memory");
  } else {
    asm volatile("setmaxnreg.inc.sync.aligned.u32 232;");
    const int wg = warp >> 2, w4 = warp & 3, t128 = tid & 127;
    const int q = lane & 3, g = lane >> 2;
    uint32_t* b1s = reinterpret_cast<uint32_t*>(smem + OFF_B1 + wg * 512);
    uint32_t* b2s = reinterpret_cast<uint32_t*>(smem + OFF_B2 + wg * 128);
    uint32_t bias_a = 0, bias_b = 0;
    if (t128 < BF / 2) bias_a = reinterpret_cast<const uint32_t*>(b1 + j * BF)[t128];
    if (t128 < BN2 / 2) bias_b = reinterpret_cast<const uint32_t*>(b2 + j * BN2)[t128];
    const uint32_t epoch = g_epoch[blockIdx.x];

    float r0, r1;
    uint32_t xa[16][4];
    TSC(24);
    mbar_wait(bar_x, 0);
    TSC(25);
    {
      uint32_t xb[16][4];
      float cs[2][4], c0[2][4], c1[2][4];
#pragma unroll
      for (int u = 0; u < 2; u++)
#pragma unroll
        for (int e = 0; e < 4; e++) { cs[u][e] = 0.f; c0[u][e] = 0.f; c1[u][e] = 0.f; }
      const int lrow = w4 * 16 + (lane & 7) + ((lane >> 3) & 1) * 8;
      const uint32_t lbase = sbase + wg * 65536 + lrow * 128;
      const uint32_t ones = 0x3F803F80u;
#pragma unroll
      for (int ks = 0; ks < 32; ks++) {
        uint32_t (&a)[4] = ks < 16 ? xa[ks] : xb[ks - 16];
        const uint32_t addr = lbase + (ks >> 2) * 8192 + (((2 * (ks & 3) + (lane >> 4)) ^ (lane & 7)) << 4);
        asm volatile("ldmatrix.sync.aligned.m8n8.x4.shared.b16 {%0,%1,%2,%3}, [%4];" : "=r"(a[0]), "=r"(a[1]), "=r"(a[2]), "=r"(a[3]) : "r"(addr));
        mma16816(cs[ks & 1], a[0], a[1], a[2], a[3], ones, ones);
        mma16816(c0[ks & 1], a[0], a[1], a[2], a[3], a[0], a[2]);
        mma16816(c1[ks & 1], a[0], a[1], a[2], a[3], a[1], a[3]);
      }
      TSC(27);
      const int dsrc = g * 4 + (g >> 1);
      const float q0 = __shfl_sync(0xffffffffu, (g & 1) ? c0[0][1] + c0[1][1] : c0[0][0] + c0[1][0], dsrc);
      const float q1 = __shfl_sync(0xffffffffu, (g & 1) ? c1[0][3] + c1[1][3] : c1[0][2] + c1[1][2], dsrc);
      const float m0 = (cs[0][0] + cs[1][0]) * (1.0f / D_MOD), m1 = (cs[0][2] + cs[1][2]) * (1.0f / D_MOD);
      const uint32_t mm0 = pack_bf16(m0, m0), mm1 = pack_bf16(m1, m1);
#pragma unroll
      for (int ks = 16; ks < 32; ks++) {
        const uint32_t addr = lbase + (ks >> 2) * 8192 + (((2 * (ks & 3) + (lane >> 4)) ^ (lane & 7)) << 4);
        asm volatile("stmatrix.sync.aligned.m8n8.x4.shared.b16 [%0], {%1,%2,%3,%4};" :: "r"(addr),
                     "r"(hsub2_bf(xb[ks - 16][0], mm0)), "r"(hsub2_bf(xb[ks - 16][1], mm1)),
                     "r"(hsub2_bf(xb[ks - 16][2], mm0)), "r"(hsub2_bf(xb[ks - 16][3], mm1)) : "memory");
      }
#pragma unroll
      for (int ks = 0; ks < 16; ks++) {
        xa[ks][0] = hsub2_bf(xa[ks][0], mm0); xa[ks][1] = hsub2_bf(xa[ks][1], mm1);
        xa[ks][2] = hsub2_bf(xa[ks][2], mm0); xa[ks][3] = hsub2_bf(xa[ks][3], mm1);
      }
      const float v0 = fmaxf(fmaf(-m0, m0, q0 * (1.0f / D_MOD)), 0.f), v1 = fmaxf(fmaf(-m1, m1, q1 * (1.0f / D_MOD)), 0.f);
      r0 = 1.0f / bf16r(sqrtf(bf16r(bf16r(v0) + 1e-5f)));
      r1 = 1.0f / bf16r(sqrtf(bf16r(bf16r(v1) + 1e-5f)));
    }
    if (t128 < BF / 2) b1s[t128] = bias_a;
    if (t128 < BN2 / 2) b2s[t128] = bias_b;
    TSC(1);
    fence_async_smem();
    wg_bar(wg);
    if (t128 == 0) mbar_arrive(bar_ln);
    TSC(2);

    uint32_t h[14][4];
    {
      float acc[112];
#pragma unroll
      for (int kb = 0; kb < 16; kb++) {
        mbar_wait(bar_full + 8 * kb, 0);
        wg_fence();
        const uint32_t abase = sbase + wg * 65536 + (kb >> 1) * 8192 + (kb & 1) * 64;
        const uint32_t bbase = sbase + load_off(kb);
#pragma unroll
        for (int kk = 0; kk < 2; kk++) {
          if (kb < 8) wgmma_rs_n224(acc, xa[2 * kb + kk], make_desc(bbase + kk * 2048, 4096, 1024, 1), (kb | kk) != 0);
          else wgmma_ss_n224(acc, make_desc(abase + kk * 32, 16, 1024, 1), make_desc(bbase + kk * 2048, 4096, 1024, 1), 1);
        }
        wg_commit();
        if (kb > 0) { wg_wait<1>(); if (t128 == 0) mbar_arrive(bar_cons + 8 * (kb - 1)); }
      }
      wg_wait<0>();
      reg_fence(acc);
      asm volatile("barrier.cluster.wait.aligned;" ::: "memory");
      if (t128 == 0) { mbar_arrive(bar_cons + 8 * 15); mbar_arrive_remote(mapa(bar_peer, (j & 1) ^ 1)); }
      TSC(11);

#pragma unroll
      for (int i = 0; i < 28; i++) {
        const uint32_t bb = b1s[i * 4 + q];
        uint32_t p0 = hadd2_bf(pack_bf16(acc[4 * i] * r0, acc[4 * i + 1] * r0), bb);
        uint32_t p1 = hadd2_bf(pack_bf16(acc[4 * i + 2] * r1, acc[4 * i + 3] * r1), bb);
        h[i >> 1][(i & 1) * 2 + 0] = pack_bf16(gelu_tanh(bf_lo(p0)), gelu_tanh(bf_hi(p0)));
        h[i >> 1][(i & 1) * 2 + 1] = pack_bf16(gelu_tanh(bf_lo(p1)), gelu_tanh(bf_hi(p1)));
      }
    }

    const uint32_t par = (epoch + 1) & 1;
    float acc2[2][32];
    float sum[32];
#pragma unroll
    for (int i = 0; i < 32; i++) sum[i] = 0.f;
    uint4 pf[4];
    const uint32_t peer_base = mapa(sbase + wg * 8192, (j & 1) ^ 1);
    const uint32_t peer_dfull = mapa(bar_dfull, (j & 1) ^ 1);
    uint4* my_base = reinterpret_cast<uint4*>(smem) + wg * 512 + t128;
    const uint4* in_part = &g_part[(size_t)((mb * NSPLIT + j) * 3) * 1024 + wg * 512 + t128];
    auto ld_part = [&](const uint4* p) {
      uint4 v;
      asm volatile("ld.relaxed.gpu.global.v4.u32 {%0, %1, %2, %3}, [%4];" : "=r"(v.x), "=r"(v.y), "=r"(v.z), "=r"(v.w) : "l"(p) : "memory");
      return v;
    };
    auto prefetch = [&](int k) {
#pragma unroll
      for (int c = 0; c < 4; c++) pf[c] = ld_part(in_part + k * 1024 + c * 128);
    };
    auto consume = [&](int k) {
#pragma unroll
      for (int c = 0; c < 4; c++) {
        uint4 v = pf[c];
        uint32_t it = 0;
        while ((((v.x ^ par) | (v.y ^ par) | (v.z ^ par) | (v.w ^ par)) & 1u) != 0) {
          v = ld_part(in_part + k * 1024 + c * 128);
          if (++it > (1u << 20)) asm volatile("trap;");
        }
        sum[c * 8 + 0] += bf_lo(v.x & ~1u); sum[c * 8 + 1] += bf_hi(v.x);
        sum[c * 8 + 2] += bf_lo(v.y & ~1u); sum[c * 8 + 3] += bf_hi(v.y);
        sum[c * 8 + 4] += bf_lo(v.z & ~1u); sum[c * 8 + 5] += bf_hi(v.z);
        sum[c * 8 + 6] += bf_lo(v.w & ~1u); sum[c * 8 + 7] += bf_hi(v.w);
      }
    };
    auto post = [&](int st, float (&a)[32]) {
      const int kind = step_kind(st), k = step_k(st);
      if (kind == 0) {
        if (st == 0) mbar_wait(bar_cons + 8 * 15, 0);
#pragma unroll
        for (int c = 0; c < 4; c++) {
          uint4 v;
          v.x = pack_bf16(a[c * 8 + 0], a[c * 8 + 1]); v.y = pack_bf16(a[c * 8 + 2], a[c * 8 + 3]);
          v.z = pack_bf16(a[c * 8 + 4], a[c * 8 + 5]); v.w = pack_bf16(a[c * 8 + 6], a[c * 8 + 7]);
          my_base[yslot_off(k) / 16 + c * 128] = v;
        }
        fence_async_smem();
        wg_bar(wg);
        if (t128 == 0) {
          if (st == 0) mbar_wait_cluster(bar_peer, 0);
          asm volatile("cp.async.bulk.shared::cluster.shared::cta.mbarrier::complete_tx::bytes [%0], [%1], %2, [%3];"
                       :: "r"(peer_base + uslot_off(k)), "r"(sbase + yslot_off(k) + wg * 8192), "r"(8192), "r"(peer_dfull + 8 * k) : "memory");
        }
      } else {
        mbar_wait_cluster(bar_dfull + 8 * k, 0);
#pragma unroll
        for (int c = 0; c < 4; c++) {
          const uint4 d = my_base[uslot_off(k) / 16 + c * 128];
          uint4 v;
          v.x = (pack_bf16(a[c * 8 + 0] + bf_lo(d.x), a[c * 8 + 1] + bf_hi(d.x)) & ~1u) | par;
          v.y = (pack_bf16(a[c * 8 + 2] + bf_lo(d.y), a[c * 8 + 3] + bf_hi(d.y)) & ~1u) | par;
          v.z = (pack_bf16(a[c * 8 + 4] + bf_lo(d.z), a[c * 8 + 5] + bf_hi(d.z)) & ~1u) | par;
          v.w = (pack_bf16(a[c * 8 + 6] + bf_lo(d.w), a[c * 8 + 7] + bf_hi(d.w)) & ~1u) | par;
          my_base[uslot_off(k) / 16 + c * 128] = v;
        }
        fence_async_smem();
        wg_bar(wg);
        if (t128 == 0) {
          const int dest = (j + 2 * (k + 1)) & 7;
          const uint4* p = &g_part[(size_t)((mb * NSPLIT + dest) * 3 + k) * 1024 + wg * 512];
          asm volatile("cp.async.bulk.global.shared::cta.bulk_group [%0], [%1], %2;"
                       :: "l"(p), "r"(sbase + uslot_off(k) + wg * 8192), "r"(8192) : "memory");
          asm volatile("cp.async.bulk.commit_group;" ::: "memory");
        }
      }
    };
#pragma unroll
    for (int i = 0; i < 8; i++) {
      TSC(12 + i);
      mbar_wait(bar_full + 8 * (16 + 2 * i), 0);
      wg_fence();
#pragma unroll
      for (int ks = 0; ks < 7; ks++) {
        wgmma_rs_n64(acc2[i & 1], h[ks], make_desc(sbase + load_off(16 + 2 * i) + ks * 2048, 16, 1024, 1), ks != 0);
      }
      mbar_wait(bar_full + 8 * (17 + 2 * i), 0);
      wg_fence();
#pragma unroll
      for (int ks = 0; ks < 7; ks++) {
        wgmma_rs_n64(acc2[i & 1], h[7 + ks], make_desc(sbase + load_off(17 + 2 * i) + ks * 2048, 16, 1024, 1), 1);
      }
      wg_commit();
      if (i > 0) {
        wg_wait<1>();
        reg_fence(acc2[(i - 1) & 1]);
        if (i <= 5 && t128 == 0) { mbar_arrive(bar_cons + 8 * (16 + 2 * (i - 1))); mbar_arrive(bar_cons + 8 * (17 + 2 * (i - 1))); }
        post(i - 1, acc2[(i - 1) & 1]);
      }
      if (i == 6) prefetch(0);
      if (i == 7) { consume(0); prefetch(1); }
    }
    consume(1);
    prefetch(2);
    mbar_wait_cluster(bar_dfull + 8 * 3, 0);
#pragma unroll
    for (int c = 0; c < 4; c++) {
      const uint4 d = my_base[uslot_off(3) / 16 + c * 128];
      sum[c * 8 + 0] += bf_lo(d.x); sum[c * 8 + 1] += bf_hi(d.x); sum[c * 8 + 2] += bf_lo(d.y); sum[c * 8 + 3] += bf_hi(d.y);
      sum[c * 8 + 4] += bf_lo(d.z); sum[c * 8 + 5] += bf_hi(d.z); sum[c * 8 + 6] += bf_lo(d.w); sum[c * 8 + 7] += bf_hi(d.w);
    }
    wg_wait<0>();
    reg_fence(acc2[1]);
    TSC(20);
    consume(2);
    TSC(21);
    if (tid == 0) g_epoch[blockIdx.x] = epoch + 1;

    {
      const int row0 = mb * BM + wg * 64 + w4 * 16 + g;
      uint32_t* o0 = reinterpret_cast<uint32_t*>(out + (size_t)row0 * D_MOD + j * BN2) + q;
      uint32_t* o1 = o0 + 8 * D_MOD / 2;
#pragma unroll
      for (int i = 0; i < 8; i++) {
        const uint32_t bb = b2s[i * 4 + q];
        o0[i * 4] = hadd2_bf(pack_bf16(acc2[1][4 * i] + sum[4 * i], acc2[1][4 * i + 1] + sum[4 * i + 1]), bb);
        o1[i * 4] = hadd2_bf(pack_bf16(acc2[1][4 * i + 2] + sum[4 * i + 2], acc2[1][4 * i + 3] + sum[4 * i + 3]), bb);
      }
    }
    if (t128 == 0) asm volatile("cp.async.bulk.wait_group 0;" ::: "memory");
    TSC(26);
    TS_FLUSH;
  }
  asm volatile("barrier.cluster.arrive.relaxed.aligned;\nbarrier.cluster.wait.aligned;" ::: "memory");
}

typedef CUresult (*EncodeFn)(CUtensorMap*, CUtensorMapDataType, cuuint32_t, void*, const cuuint64_t*, const cuuint64_t*,
                             const cuuint32_t*, const cuuint32_t*, CUtensorMapInterleave, CUtensorMapSwizzle,
                             CUtensorMapL2promotion, CUtensorMapFloatOOBfill);

}

extern "C" void kernel_launch(void* const* d_in, const int* in_sizes, int n_in, void* d_out, int out_size) {
  (void)in_sizes; (void)n_in; (void)out_size;
  static CUtensorMap tm_x, tm_w1, tm_w2;
  static const void* cached_w1 = nullptr; static const void* cached_w2 = nullptr; static const void* cached_x = nullptr;
  const void* w1 = d_in[1]; const void* w2 = d_in[3]; const void* xp = d_in[0];
  if (cached_w1 != w1 || cached_w2 != w2 || cached_x != xp) {
    void* fn = nullptr; cudaDriverEntryPointQueryResult st;
    cudaGetDriverEntryPoint("cuTensorMapEncodeTiled", &fn, cudaEnableDefault, &st);
    EncodeFn enc = (EncodeFn)fn;
    {
      cuuint64_t dims[3] = {64, (cuuint64_t)S_TOK, (cuuint64_t)(D_MOD / 64)};
      cuuint64_t strides[2] = {(cuuint64_t)D_MOD * 2, 128};
      cuuint32_t box[3] = {64, 64, 8};
      cuuint32_t es[3] = {1, 1, 1};
      enc(&tm_x, CU_TENSOR_MAP_DATA_TYPE_BFLOAT16, 3, const_cast<void*>(xp), dims, strides, box, es,
          CU_TENSOR_MAP_INTERLEAVE_NONE, CU_TENSOR_MAP_SWIZZLE_128B, CU_TENSOR_MAP_L2_PROMOTION_L2_128B, CU_TENSOR_MAP_FLOAT_OOB_FILL_NONE);
    }
    {
      cuuint64_t dims[2] = {(cuuint64_t)F_HID, (cuuint64_t)D_MOD};
      cuuint64_t strides[1] = {(cuuint64_t)F_HID * 2};
      cuuint32_t box[2] = {64, 32};
      cuuint32_t es[2] = {1, 1};
      enc(&tm_w1, CU_TENSOR_MAP_DATA_TYPE_BFLOAT16, 2, const_cast<void*>(w1), dims, strides, box, es,
          CU_TENSOR_MAP_INTERLEAVE_NONE, CU_TENSOR_MAP_SWIZZLE_128B, CU_TENSOR_MAP_L2_PROMOTION_L2_128B, CU_TENSOR_MAP_FLOAT_OOB_FILL_NONE);
    }
    {
      cuuint64_t dims[2] = {(cuuint64_t)D_MOD, (cuuint64_t)F_HID};
      cuuint64_t strides[1] = {(cuuint64_t)D_MOD * 2};
      cuuint32_t box[2] = {64, 112};
      cuuint32_t es[2] = {1, 1};
      enc(&tm_w2, CU_TENSOR_MAP_DATA_TYPE_BFLOAT16, 2, const_cast<void*>(w2), dims, strides, box, es,
          CU_TENSOR_MAP_INTERLEAVE_NONE, CU_TENSOR_MAP_SWIZZLE_128B, CU_TENSOR_MAP_L2_PROMOTION_L2_128B, CU_TENSOR_MAP_FLOAT_OOB_FILL_NONE);
    }
    cudaFuncSetAttribute(fused_mlp_kernel, cudaFuncAttributeMaxDynamicSharedMemorySize, SMEM_TOTAL);
    cached_w1 = w1; cached_w2 = w2; cached_x = xp;
  }
  fused_mlp_kernel<<<NMB * NSPLIT, NTHREADS, SMEM_TOTAL>>>(tm_x, tm_w1, tm_w2,
      (const __nv_bfloat16*)d_in[2], (const __nv_bfloat16*)d_in[4], (__nv_bfloat16*)d_out);
}
```

```cpp
#include <cuda_runtime.h>
#include <cuda_bf16.h>
#include <cuda.h>
#include <stdint.h>

namespace {

constexpr int S_TOK = 2048, D_MOD = 512, F_HID = 1792;
constexpr int BM = 128, NSPLIT = 8, BF = F_HID / NSPLIT;
constexpr int BN2 = D_MOD / NSPLIT;
constexpr int NMB = S_TOK / BM;
constexpr int SLOT_BYTES = 16384;
constexpr int W1_BYTES = 16384;
constexpr int W2_BYTES = 14336;
constexpr int Y_BYTES = BM * D_MOD * 2;
constexpr int NRING = 6;
constexpr int NLOAD = 32;
constexpr int OFF_RING = Y_BYTES;
__host__ __device__ constexpr int yslot_off(int s) { return (s >> 1) * 65536 + (s & 1) * 16384; }
__host__ __device__ constexpr int uslot_off(int s) { return (s >> 1) * 65536 + 32768 + (s & 1) * 16384; }
constexpr int DSLOT_BYTES = 16384;
constexpr int OFF_BAR = OFF_RING + NRING * SLOT_BYTES;
constexpr int OFF_MEAN = OFF_BAR + 640;
constexpr int OFF_B1 = OFF_MEAN + 512;
constexpr int OFF_B2 = OFF_B1 + 1024;
constexpr int SMEM_TOTAL = OFF_B2 + 256;
constexpr int NTHREADS = 384;
static_assert(SMEM_TOTAL <= 232448, "smem");

__device__ uint4 g_part[(size_t)NMB * NSPLIT * 3 * 1024];
__device__ unsigned int g_epoch[NMB * NSPLIT];

#define TS_DECL
#define TS_FLUSH do {} while (0)
#define TS(role, idx) do {} while (0)
#define TSC(idx) do {} while (0)

__device__ __forceinline__ uint32_t smem_u32(const void* p) { return (uint32_t)__cvta_generic_to_shared(p); }
__device__ __forceinline__ uint32_t mapa(uint32_t a, uint32_t r) {
  uint32_t d; asm volatile("mapa.shared::cluster.u32 %0, %1, %2;" : "=r"(d) : "r"(a), "r"(r)); return d;
}
__device__ __forceinline__ void mbar_init(uint32_t bar, uint32_t cnt) {
  asm volatile("mbarrier.init.shared::cta.b64 [%0], %1;" :: "r"(bar), "r"(cnt) : "memory");
}
__device__ __forceinline__ void mbar_expect_tx(uint32_t bar, uint32_t bytes) {
  asm volatile("mbarrier.arrive.expect_tx.shared::cta.b64 _, [%0], %1;" :: "r"(bar), "r"(bytes) : "memory");
}
__device__ __forceinline__ void mbar_arrive(uint32_t bar) {
  asm volatile("mbarrier.arrive.shared::cta.b64 _, [%0];" :: "r"(bar) : "memory");
}
__device__ __forceinline__ void mbar_arrive_remote(uint32_t rbar) {
  asm volatile("mbarrier.arrive.release.cluster.shared::cluster.b64 _, [%0];" :: "r"(rbar) : "memory");
}
__device__ __forceinline__ void mbar_wait(uint32_t bar, uint32_t parity) {
  uint32_t done = 0; uint32_t it = 0;
  while (true) {
    asm volatile("{\n.reg .pred p;\nmbarrier.try_wait.parity.shared::cta.b64 p, [%1], %2;\nselp.u32 %0, 1, 0, p;\n}"
                 : "=r"(done) : "r"(bar), "r"(parity) : "memory");
    if (done) break;
    if (++it > (1u << 22)) asm volatile("trap;");
  }
}
__device__ __forceinline__ void mbar_wait_cluster(uint32_t bar, uint32_t parity) {
  uint32_t done = 0; uint32_t it = 0;
  while (true) {
    asm volatile("{\n.reg .pred p;\nmbarrier.try_wait.parity.acquire.cluster.shared::cta.b64 p, [%1], %2;\nselp.u32 %0, 1, 0, p;\n}"
                 : "=r"(done) : "r"(bar), "r"(parity) : "memory");
    if (done) break;
    if (++it > (1u << 22)) asm volatile("trap;");
  }
}
__device__ __forceinline__ void tma_load_3d(uint32_t dst, const CUtensorMap* tm, int c0, int c1, int c2, uint32_t bar) {
  asm volatile("cp.async.bulk.tensor.3d.shared::cluster.global.mbarrier::complete_tx::bytes [%0], [%1, {%3, %4, %5}], [%2];"
               :: "r"(dst), "l"(tm), "r"(bar), "r"(c0), "r"(c1), "r"(c2) : "memory");
}
__device__ __forceinline__ void tma_load_2d(uint32_t dst, const CUtensorMap* tm, int c0, int c1, uint32_t bar) {
  asm volatile("cp.async.bulk.tensor.2d.shared::cluster.global.mbarrier::complete_tx::bytes [%0], [%1, {%3, %4}], [%2];"
               :: "r"(dst), "l"(tm), "r"(bar), "r"(c0), "r"(c1) : "memory");
}
__device__ __forceinline__ void tma_prefetch_2d(const CUtensorMap* tm, int c0, int c1) {
  asm volatile("cp.async.bulk.prefetch.tensor.2d.L2.global.tile [%0, {%1, %2}];" :: "l"(tm), "r"(c0), "r"(c1) : "memory");
}
__device__ __forceinline__ void fence_async_smem() { asm volatile("fence.proxy.async.shared::cta;" ::: "memory"); }
__device__ __forceinline__ void wg_bar(int wg) {
  if (wg == 0) asm volatile("bar.sync 1, 128;" ::: "memory"); else asm volatile("bar.sync 2, 128;" ::: "memory");
}
__device__ __forceinline__ void wg_fence() { asm volatile("wgmma.fence.sync.aligned;" ::: "memory"); }
__device__ __forceinline__ void wg_commit() { asm volatile("wgmma.commit_group.sync.aligned;" ::: "memory"); }
template <int N> __device__ __forceinline__ void wg_wait() { asm volatile("wgmma.wait_group.sync.aligned %0;" :: "n"(N) : "memory"); }
template <int N> __device__ __forceinline__ void reg_fence(float (&d)[N]) {
#pragma unroll
  for (int i = 0; i < N; i++) asm volatile("" : "+f"(d[i]) :: "memory");
}
__device__ __forceinline__ uint64_t make_desc(uint32_t addr, uint32_t lbo, uint32_t sbo, uint32_t lt) {
  return (uint64_t)((addr & 0x3FFFF) >> 4) | ((uint64_t)(lbo >> 4) << 16) | ((uint64_t)(sbo >> 4) << 32) | ((uint64_t)lt << 62);
}
__device__ __forceinline__ uint32_t pack_bf16(float lo, float hi) {
  uint32_t r; asm("cvt.rn.bf16x2.f32 %0, %1, %2;" : "=r"(r) : "f"(hi), "f"(lo)); return r;
}
__device__ __forceinline__ float bf_lo(uint32_t v) { return __uint_as_float(v << 16); }
__device__ __forceinline__ float bf_hi(uint32_t v) { return __uint_as_float(v & 0xffff0000u); }
__device__ __forceinline__ float bf16r(float v) { return __bfloat162float(__float2bfloat16_rn(v)); }
__device__ __forceinline__ uint32_t hadd2_bf(uint32_t a, uint32_t b) {
  uint32_t r; asm("add.rn.bf16x2 %0, %1, %2;" : "=r"(r) : "r"(a), "r"(b)); return r;
}
__device__ __forceinline__ uint32_t hsub2_bf(uint32_t a, uint32_t b) {
  uint32_t r; asm("sub.rn.bf16x2 %0, %1, %2;" : "=r"(r) : "r"(a), "r"(b)); return r;
}
__device__ __forceinline__ float gelu_tanh(float u) {
  float inner = u * fmaf(0.035677408136300125f, u * u, 0.7978845608028654f);
  float th; asm("tanh.approx.f32 %0, %1;" : "=f"(th) : "f"(inner));
  float hu = 0.5f * u;
  return fmaf(hu, th, hu);
}
__device__ __forceinline__ void mma16816(float (&c)[4], uint32_t a0, uint32_t a1, uint32_t a2, uint32_t a3, uint32_t b0, uint32_t b1) {
  asm volatile("mma.sync.aligned.m16n8k16.row.col.f32.bf16.bf16.f32 {%0,%1,%2,%3}, {%4,%5,%6,%7}, {%8,%9}, {%0,%1,%2,%3};"
               : "+f"(c[0]), "+f"(c[1]), "+f"(c[2]), "+f"(c[3]) : "r"(a0), "r"(a1), "r"(a2), "r"(a3), "r"(b0), "r"(b1));
}

__device__ __forceinline__ void wgmma_ss_n224(float (&d)[112], uint64_t descA, uint64_t descB, int scaleD) {
  asm volatile("{\n.reg .pred p;\nsetp.ne.b32 p, %114, 0;\n"
    "wgmma.mma_async.sync.aligned.m64n224k16.f32.bf16.bf16 {%0, %1, %2, %3, %4, %5, %6, %7, %8, %9, %10, %11, %12, %13, %14, %15, %16, %17, %18, %19, %20, %21, %22, %23, %24, %25, %26, %27, %28, %29, %30, %31, %32, %33, %34, %35, %36, %37, %38, %39, %40, %41, %42, %43, %44, %45, %46, %47, %48, %49, %50, %51, %52, %53, %54, %55, %56, %57, %58, %59, %60, %61, %62, %63, %64, %65, %66, %67, %68, %69, %70, %71, %72, %73, %74, %75, %76, %77, %78, %79, %80, %81, %82, %83, %84, %85, %86, %87, %88, %89, %90, %91, %92, %93, %94, %95, %96, %97, %98, %99, %100, %101, %102, %103, %104, %105, %106, %107, %108, %109, %110, %111}, %112, %113, p, 1, 1, 0, 1;\n}\n"
    : "+f"(d[0]), "+f"(d[1]), "+f"(d[2]), "+f"(d[3]), "+f"(d[4]), "+f"(d[5]), "+f"(d[6]), "+f"(d[7]), "+f"(d[8]), "+f"(d[9]), "+f"(d[10]), "+f"(d[11]), "+f"(d[12]), "+f"(d[13]), "+f"(d[14]), "+f"(d[15]), "+f"(d[16]), "+f"(d[17]), "+f"(d[18]), "+f"(d[19]), "+f"(d[20]), "+f"(d[21]), "+f"(d[22]), "+f"(d[23]), "+f"(d[24]), "+f"(d[25]), "+f"(d[26]), "+f"(d[27]), "+f"(d[28]), "+f"(d[29]), "+f"(d[30]), "+f"(d[31]), "+f"(d[32]), "+f"(d[33]), "+f"(d[34]), "+f"(d[35]), "+f"(d[36]), "+f"(d[37]), "+f"(d[38]), "+f"(d[39]), "+f"(d[40]), "+f"(d[41]), "+f"(d[42]), "+f"(d[43]), "+f"(d[44]), "+f"(d[45]), "+f"(d[46]), "+f"(d[47]), "+f"(d[48]), "+f"(d[49]), "+f"(d[50]), "+f"(d[51]), "+f"(d[52]), "+f"(d[53]), "+f"(d[54]), "+f"(d[55]), "+f"(d[56]), "+f"(d[57]), "+f"(d[58]), "+f"(d[59]), "+f"(d[60]), "+f"(d[61]), "+f"(d[62]), "+f"(d[63]), "+f"(d[64]), "+f"(d[65]), "+f"(d[66]), "+f"(d[67]), "+f"(d[68]), "+f"(d[69]), "+f"(d[70]), "+f"(d[71]), "+f"(d[72]), "+f"(d[73]), "+f"(d[74]), "+f"(d[75]), "+f"(d[76]), "+f"(d[77]), "+f"(d[78]), "+f"(d[79]), "+f"(d[80]), "+f"(d[81]), "+f"(d[82]), "+f"(d[83]), "+f"(d[84]), "+f"(d[85]), "+f"(d[86]), "+f"(d[87]), "+f"(d[88]), "+f"(d[89]), "+f"(d[90]), "+f"(d[91]), "+f"(d[92]), "+f"(d[93]), "+f"(d[94]), "+f"(d[95]), "+f"(d[96]), "+f"(d[97]), "+f"(d[98]), "+f"(d[99]), "+f"(d[100]), "+f"(d[101]), "+f"(d[102]), "+f"(d[103]), "+f"(d[104]), "+f"(d[105]), "+f"(d[106]), "+f"(d[107]), "+f"(d[108]), "+f"(d[109]), "+f"(d[110]), "+f"(d[111])
    : "l"(descA), "l"(descB), "r"(scaleD));
}

__device__ __forceinline__ void wgmma_rs_n64(float (&d)[32], const uint32_t (&a)[4], uint64_t descB, int scaleD) {
  asm volatile("{\n.reg .pred p;\nsetp.ne.b32 p, %37, 0;\n"
    "wgmma.mma_async.sync.aligned.m64n64k16.f32.bf16.bf16 {%0, %1, %2, %3, %4, %5, %6, %7, %8, %9, %10, %11, %12, %13, %14, %15, %16, %17, %18, %19, %20, %21, %22, %23, %24, %25, %26, %27, %28, %29, %30, %31}, {%32, %33, %34, %35}, %36, p, 1, 1, 1;\n}\n"
    : "+f"(d[0]), "+f"(d[1]), "+f"(d[2]), "+f"(d[3]), "+f"(d[4]), "+f"(d[5]), "+f"(d[6]), "+f"(d[7]), "+f"(d[8]), "+f"(d[9]), "+f"(d[10]), "+f"(d[11]), "+f"(d[12]), "+f"(d[13]), "+f"(d[14]), "+f"(d[15]), "+f"(d[16]), "+f"(d[17]), "+f"(d[18]), "+f"(d[19]), "+f"(d[20]), "+f"(d[21]), "+f"(d[22]), "+f"(d[23]), "+f"(d[24]), "+f"(d[25]), "+f"(d[26]), "+f"(d[27]), "+f"(d[28]), "+f"(d[29]), "+f"(d[30]), "+f"(d[31])
    : "r"(a[0]), "r"(a[1]), "r"(a[2]), "r"(a[3]), "l"(descB), "r"(scaleD));
}

__device__ __forceinline__ void wgmma_rs_n224(float (&d)[112], const uint32_t (&a)[4], uint64_t descB, int scaleD) {
  asm volatile("{\n.reg .pred p;\nsetp.ne.b32 p, %117, 0;\n"
    "wgmma.mma_async.sync.aligned.m64n224k16.f32.bf16.bf16 {%0, %1, %2, %3, %4, %5, %6, %7, %8, %9, %10, %11, %12, %13, %14, %15, %16, %17, %18, %19, %20, %21, %22, %23, %24, %25, %26, %27, %28, %29, %30, %31, %32, %33, %34, %35, %36, %37, %38, %39, %40, %41, %42, %43, %44, %45, %46, %47, %48, %49, %50, %51, %52, %53, %54, %55, %56, %57, %58, %59, %60, %61, %62, %63, %64, %65, %66, %67, %68, %69, %70, %71, %72, %73, %74, %75, %76, %77, %78, %79, %80, %81, %82, %83, %84, %85, %86, %87, %88, %89, %90, %91, %92, %93, %94, %95, %96, %97, %98, %99, %100, %101, %102, %103, %104, %105, %106, %107, %108, %109, %110, %111}, {%112, %113, %114, %115}, %116, p, 1, 1, 1;\n}\n"
    : "+f"(d[0]), "+f"(d[1]), "+f"(d[2]), "+f"(d[3]), "+f"(d[4]), "+f"(d[5]), "+f"(d[6]), "+f"(d[7]), "+f"(d[8]), "+f"(d[9]), "+f"(d[10]), "+f"(d[11]), "+f"(d[12]), "+f"(d[13]), "+f"(d[14]), "+f"(d[15]), "+f"(d[16]), "+f"(d[17]), "+f"(d[18]), "+f"(d[19]), "+f"(d[20]), "+f"(d[21]), "+f"(d[22]), "+f"(d[23]), "+f"(d[24]), "+f"(d[25]), "+f"(d[26]), "+f"(d[27]), "+f"(d[28]), "+f"(d[29]), "+f"(d[30]), "+f"(d[31]), "+f"(d[32]), "+f"(d[33]), "+f"(d[34]), "+f"(d[35]), "+f"(d[36]), "+f"(d[37]), "+f"(d[38]), "+f"(d[39]), "+f"(d[40]), "+f"(d[41]), "+f"(d[42]), "+f"(d[43]), "+f"(d[44]), "+f"(d[45]), "+f"(d[46]), "+f"(d[47]), "+f"(d[48]), "+f"(d[49]), "+f"(d[50]), "+f"(d[51]), "+f"(d[52]), "+f"(d[53]), "+f"(d[54]), "+f"(d[55]), "+f"(d[56]), "+f"(d[57]), "+f"(d[58]), "+f"(d[59]), "+f"(d[60]), "+f"(d[61]), "+f"(d[62]), "+f"(d[63]), "+f"(d[64]), "+f"(d[65]), "+f"(d[66]), "+f"(d[67]), "+f"(d[68]), "+f"(d[69]), "+f"(d[70]), "+f"(d[71]), "+f"(d[72]), "+f"(d[73]), "+f"(d[74]), "+f"(d[75]), "+f"(d[76]), "+f"(d[77]), "+f"(d[78]), "+f"(d[79]), "+f"(d[80]), "+f"(d[81]), "+f"(d[82]), "+f"(d[83]), "+f"(d[84]), "+f"(d[85]), "+f"(d[86]), "+f"(d[87]), "+f"(d[88]), "+f"(d[89]), "+f"(d[90]), "+f"(d[91]), "+f"(d[92]), "+f"(d[93]), "+f"(d[94]), "+f"(d[95]), "+f"(d[96]), "+f"(d[97]), "+f"(d[98]), "+f"(d[99]), "+f"(d[100]), "+f"(d[101]), "+f"(d[102]), "+f"(d[103]), "+f"(d[104]), "+f"(d[105]), "+f"(d[106]), "+f"(d[107]), "+f"(d[108]), "+f"(d[109]), "+f"(d[110]), "+f"(d[111])
    : "r"(a[0]), "r"(a[1]), "r"(a[2]), "r"(a[3]), "l"(descB), "r"(scaleD));
}

__host__ __device__ constexpr int step_kind(int i) { return (i == 0 || i == 1 || i == 3 || i == 6) ? 0 : (i == 7 ? 2 : 1); }
__host__ __device__ constexpr int step_k(int i) { return i == 0 ? 0 : i == 1 ? 1 : i == 2 ? 0 : i == 3 ? 2 : i == 4 ? 1 : i == 5 ? 2 : 3; }
__device__ __forceinline__ int step_slice(int i, int j) {
  const int kind = step_kind(i), k = step_k(i);
  const int base = (kind == 0) ? (j ^ 1) : j;
  return (k == 3) ? base : ((base + 2 * (k + 1)) & 7);
}

__host__ __device__ constexpr int load_off(int i) {
  return i < 6 ? OFF_RING + i * SLOT_BYTES : (i < 10 ? yslot_off(i - 6) : OFF_RING + ((i - 10) % NRING) * SLOT_BYTES);
}
__host__ __device__ constexpr int load_dep(int i) { return i < 6 ? -1 : (i < 10 ? -2 : (i < 16 ? i - 10 : i - 6)); }

__global__ void __cluster_dims__(2, 1, 1) __launch_bounds__(NTHREADS, 1)
fused_mlp_kernel(const __grid_constant__ CUtensorMap tm_x, const __grid_constant__ CUtensorMap tm_w1, const __grid_constant__ CUtensorMap tm_w2,
                 const __nv_bfloat16* __restrict__ b1, const __nv_bfloat16* __restrict__ b2, __nv_bfloat16* __restrict__ out)
{
  extern __shared__ __align__(1024) unsigned char smem[];
  const uint32_t sbase = smem_u32(smem);
  const uint32_t bar_full = sbase + OFF_BAR;
  const uint32_t bar_cons = sbase + OFF_BAR + 256;
  const uint32_t bar_x = sbase + OFF_BAR + 512;
  const uint32_t bar_dfull = sbase + OFF_BAR + 528;
  const uint32_t bar_peer = sbase + OFF_BAR + 560;
  const uint32_t bar_ln = sbase + OFF_BAR + 568;
  const int tid = threadIdx.x, warp = tid >> 5, lane = tid & 31;
  const int mb = blockIdx.x >> 3, j = blockIdx.x & 7;

  TS_DECL
  TSC(0);
  if (warp == 8) {
    mbar_init(bar_full + 8 * lane, 1); mbar_init(bar_cons + 8 * lane, 2);
    if (lane < 4) mbar_init(bar_dfull + 8 * lane, 1);
    if (lane == 4) mbar_init(bar_peer, 2);
    if (lane == 5) mbar_init(bar_ln, 2);
    if (lane == 6) mbar_init(bar_x, 1);
    if (lane == 7) mbar_init(bar_x + 8, 1);
    asm volatile("fence.mbarrier_init.release.cluster;" ::: "memory");
    fence_async_smem();
    __syncwarp();
    if (lane < 4) mbar_expect_tx(bar_dfull + 8 * lane, DSLOT_BYTES);
    __syncwarp();
  }
  asm volatile("barrier.cluster.arrive.relaxed.aligned;" ::: "memory");
  __syncthreads();

  if (warp >= 8) {
    asm volatile("setmaxnreg.dec.sync.aligned.u32 40;");
    if (warp == 8 && lane == 0) {
      mbar_expect_tx(bar_x, 65536);
      tma_load_3d(sbase, &tm_x, 0, mb * BM, 0, bar_x);
      for (int i = 0; i < NRING; i++) {
        if (i == 2) {
          mbar_expect_tx(bar_x + 8, 65536);
          tma_load_3d(sbase + 65536, &tm_x, 0, mb * BM + 64, 0, bar_x + 8);
        }
        mbar_expect_tx(bar_full + 8 * i, W1_BYTES);
        for (int a = 0; a < 4; a++)
          tma_load_2d(sbase + OFF_RING + i * SLOT_BYTES + a * 4096, &tm_w1, j * BF + a * 64, i * 32, bar_full + 8 * i);
      }
      TS(2, 1);
      for (int t = 2 * mb; t < 2 * mb + 2; t++) {
        if (t < 16) { if (t >= NRING) for (int a = 0; a < 4; a++) tma_prefetch_2d(&tm_w1, j * BF + a * 64, t * 32); }
        else tma_prefetch_2d(&tm_w2, ((t - 16) >> 1) * 64, j * BF + ((t - 16) & 1) * 112);
      }
#pragma unroll
      for (int i = NRING; i < NLOAD; i++) {
        if (load_dep(i) >= 0) mbar_wait(bar_cons + 8 * load_dep(i), 0); else if (i == NRING) mbar_wait(bar_ln, 0);
        TS(2, i);
        const uint32_t dst = sbase + load_off(i);
        if (i < 16) {
          mbar_expect_tx(bar_full + 8 * i, W1_BYTES);
          for (int a = 0; a < 4; a++) tma_load_2d(dst + a * 4096, &tm_w1, j * BF + a * 64, i * 32, bar_full + 8 * i);
        } else {
          mbar_expect_tx(bar_full + 8 * i, W2_BYTES);
          tma_load_2d(dst, &tm_w2, step_slice((i - 16) >> 1, j) * BN2, j * BF + ((i - 16) & 1) * 112, bar_full + 8 * i);
        }
      }
    }
    __syncwarp();
    asm volatile("barrier.cluster.wait.aligned;" ::: "memory");
    asm volatile("barrier.cluster.arrive.relaxed.aligned;\nbarrier.cluster.wait.aligned;" ::: "memory");
  } else {
    asm volatile("setmaxnreg.inc.sync.aligned.u32 232;");
    const int wg = warp >> 2, w4 = warp & 3, t128 = tid & 127;
    const int q = lane & 3, g = lane >> 2;
    uint32_t* b1s = reinterpret_cast<uint32_t*>(smem + OFF_B1 + wg * 512);
    uint32_t* b2s = reinterpret_cast<uint32_t*>(smem + OFF_B2 + wg * 128);
    uint32_t bias_a = 0, bias_b = 0;
    if (t128 < BF / 2) bias_a = reinterpret_cast<const uint32_t*>(b1 + j * BF)[t128];
    if (t128 < BN2 / 2) bias_b = reinterpret_cast<const uint32_t*>(b2 + j * BN2)[t128];
    const uint32_t epoch = g_epoch[blockIdx.x];

    float r0, r1;
    uint32_t xa[16][4];
    TSC(24);
    mbar_wait(bar_x + 8 * wg, 0);
    TSC(25);
    {
      uint32_t xb[16][4];
      float cs[2][4], c0[2][4], c1[2][4];
#pragma unroll
      for (int u = 0; u < 2; u++)
#pragma unroll
        for (int e = 0; e < 4; e++) { cs[u][e] = 0.f; c0[u][e] = 0.f; c1[u][e] = 0.f; }
      const int lrow = w4 * 16 + (lane & 7) + ((lane >> 3) & 1) * 8;
      const uint32_t lbase = sbase + wg * 65536 + lrow * 128;
      const uint32_t ones = 0x3F803F80u;
#pragma unroll
      for (int ks = 0; ks < 32; ks++) {
        uint32_t (&a)[4] = ks < 16 ? xa[ks] : xb[ks - 16];
        const uint32_t addr = lbase + (ks >> 2) * 8192 + (((2 * (ks & 3) + (lane >> 4)) ^ (lane & 7)) << 4);
        asm volatile("ldmatrix.sync.aligned.m8n8.x4.shared.b16 {%0,%1,%2,%3}, [%4];" : "=r"(a[0]), "=r"(a[1]), "=r"(a[2]), "=r"(a[3]) : "r"(addr));
        mma16816(cs[ks & 1], a[0], a[1], a[2], a[3], ones, ones);
        mma16816(c0[ks & 1], a[0], a[1], a[2], a[3], a[0], a[2]);
        mma16816(c1[ks & 1], a[0], a[1], a[2], a[3], a[1], a[3]);
      }
      TSC(27);
      const int dsrc = g * 4 + (g >> 1);
      const float q0 = __shfl_sync(0xffffffffu, (g & 1) ? c0[0][1] + c0[1][1] : c0[0][0] + c0[1][0], dsrc);
      const float q1 = __shfl_sync(0xffffffffu, (g & 1) ? c1[0][3] + c1[1][3] : c1[0][2] + c1[1][2], dsrc);
      const float m0 = (cs[0][0] + cs[1][0]) * (1.0f / D_MOD), m1 = (cs[0][2] + cs[1][2]) * (1.0f / D_MOD);
      const uint32_t mm0 = pack_bf16(m0, m0), mm1 = pack_bf16(m1, m1);
#pragma unroll
      for (int ks = 16; ks < 32; ks++) {
        const uint32_t addr = lbase + (ks >> 2) * 8192 + (((2 * (ks & 3) + (lane >> 4)) ^ (lane & 7)) << 4);
        asm volatile("stmatrix.sync.aligned.m8n8.x4.shared.b16 [%0], {%1,%2,%3,%4};" :: "r"(addr),
                     "r"(hsub2_bf(xb[ks - 16][0], mm0)), "r"(hsub2_bf(xb[ks - 16][1], mm1)),
                     "r"(hsub2_bf(xb[ks - 16][2], mm0)), "r"(hsub2_bf(xb[ks - 16][3], mm1)) : "memory");
      }
#pragma unroll
      for (int ks = 0; ks < 16; ks++) {
        xa[ks][0] = hsub2_bf(xa[ks][0], mm0); xa[ks][1] = hsub2_bf(xa[ks][1], mm1);
        xa[ks][2] = hsub2_bf(xa[ks][2], mm0); xa[ks][3] = hsub2_bf(xa[ks][3], mm1);
      }
      const float v0 = fmaxf(fmaf(-m0, m0, q0 * (1.0f / D_MOD)), 0.f), v1 = fmaxf(fmaf(-m1, m1, q1 * (1.0f / D_MOD)), 0.f);
      r0 = 1.0f / bf16r(sqrtf(bf16r(bf16r(v0) + 1e-5f)));
      r1 = 1.0f / bf16r(sqrtf(bf16r(bf16r(v1) + 1e-5f)));
    }
    if (t128 < BF / 2) b1s[t128] = bias_a;
    if (t128 < BN2 / 2) b2s[t128] = bias_b;
    TSC(1);
    fence_async_smem();
    wg_bar(wg);
    if (t128 == 0) mbar_arrive(bar_ln);
    TSC(2);

    uint32_t h[14][4];
    {
      float acc[112];
#pragma unroll
      for (int kb = 0; kb < 16; kb++) {
        mbar_wait(bar_full + 8 * kb, 0);
        wg_fence();
        const uint32_t abase = sbase + wg * 65536 + (kb >> 1) * 8192 + (kb & 1) * 64;
        const uint32_t bbase = sbase + load_off(kb);
#pragma unroll
        for (int kk = 0; kk < 2; kk++) {
          if (kb < 8) wgmma_rs_n224(acc, xa[2 * kb + kk], make_desc(bbase + kk * 2048, 4096, 1024, 1), (kb | kk) != 0);
          else wgmma_ss_n224(acc, make_desc(abase + kk * 32, 16, 1024, 1), make_desc(bbase + kk * 2048, 4096, 1024, 1), 1);
        }
        wg_commit();
        if (kb > 0) { wg_wait<1>(); if (t128 == 0) mbar_arrive(bar_cons + 8 * (kb - 1)); }
      }
      wg_wait<0>();
      reg_fence(acc);
      asm volatile("barrier.cluster.wait.aligned;" ::: "memory");
      if (t128 == 0) { mbar_arrive(bar_cons + 8 * 15); mbar_arrive_remote(mapa(bar_peer, (j & 1) ^ 1)); }
      TSC(11);

#pragma unroll
      for (int i = 0; i < 28; i++) {
        const uint32_t bb = b1s[i * 4 + q];
        uint32_t p0 = hadd2_bf(pack_bf16(acc[4 * i] * r0, acc[4 * i + 1] * r0), bb);
        uint32_t p1 = hadd2_bf(pack_bf16(acc[4 * i + 2] * r1, acc[4 * i + 3] * r1), bb);
        h[i >> 1][(i & 1) * 2 + 0] = pack_bf16(gelu_tanh(bf_lo(p0)), gelu_tanh(bf_hi(p0)));
        h[i >> 1][(i & 1) * 2 + 1] = pack_bf16(gelu_tanh(bf_lo(p1)), gelu_tanh(bf_hi(p1)));
      }
    }

    const uint32_t par = (epoch + 1) & 1;
    float acc2[3][32];
    float sum[32];
    uint4 pf[3][4];
    const uint32_t peer_base = mapa(sbase + wg * 8192, (j & 1) ^ 1);
    const uint32_t peer_dfull = mapa(bar_dfull, (j & 1) ^ 1);
    uint4* my_base = reinterpret_cast<uint4*>(smem) + wg * 512 + t128;
    const uint4* in_part = &g_part[(size_t)((mb * NSPLIT + j) * 3) * 1024 + wg * 512 + t128];
    auto ld_part = [&](const uint4* p) {
      uint4 v;
      asm volatile("ld.relaxed.gpu.global.v4.u32 {%0, %1, %2, %3}, [%4];" : "=r"(v.x), "=r"(v.y), "=r"(v.z), "=r"(v.w) : "l"(p) : "memory");
      return v;
    };
    auto prefetch = [&](int k) {
#pragma unroll
      for (int c = 0; c < 4; c++) pf[k][c] = ld_part(in_part + k * 1024 + c * 128);
    };
    auto consume = [&](int k) {
#pragma unroll
      for (int c = 0; c < 4; c++) {
        uint4 v = pf[k][c];
        uint32_t it = 0;
        while ((((v.x ^ par) | (v.y ^ par) | (v.z ^ par) | (v.w ^ par)) & 1u) != 0) {
          v = ld_part(in_part + k * 1024 + c * 128);
          if (++it > (1u << 20)) asm volatile("trap;");
        }
        sum[c * 8 + 0] += bf_lo(v.x & ~1u); sum[c * 8 + 1] += bf_hi(v.x);
        sum[c * 8 + 2] += bf_lo(v.y & ~1u); sum[c * 8 + 3] += bf_hi(v.y);
        sum[c * 8 + 4] += bf_lo(v.z & ~1u); sum[c * 8 + 5] += bf_hi(v.z);
        sum[c * 8 + 6] += bf_lo(v.w & ~1u); sum[c * 8 + 7] += bf_hi(v.w);
      }
    };
    auto post = [&](int st, float (&a)[32]) {
      const int kind = step_kind(st), k = step_k(st);
      if (kind == 0) {
        if (st == 0) mbar_wait(bar_cons + 8 * 15, 0);
#pragma unroll
        for (int c = 0; c < 4; c++) {
          uint4 v;
          v.x = pack_bf16(a[c * 8 + 0], a[c * 8 + 1]); v.y = pack_bf16(a[c * 8 + 2], a[c * 8 + 3]);
          v.z = pack_bf16(a[c * 8 + 4], a[c * 8 + 5]); v.w = pack_bf16(a[c * 8 + 6], a[c * 8 + 7]);
          my_base[yslot_off(k) / 16 + c * 128] = v;
        }
        fence_async_smem();
        wg_bar(wg);
        if (t128 == 0) {
          if (st == 0) mbar_wait_cluster(bar_peer, 0);
          asm volatile("cp.async.bulk.shared::cluster.shared::cta.mbarrier::complete_tx::bytes [%0], [%1], %2, [%3];"
                       :: "r"(peer_base + uslot_off(k)), "r"(sbase + yslot_off(k) + wg * 8192), "r"(8192), "r"(peer_dfull + 8 * k) : "memory");
        }
      } else {
        mbar_wait_cluster(bar_dfull + 8 * k, 0);
#pragma unroll
        for (int c = 0; c < 4; c++) {
          const uint4 d = my_base[uslot_off(k) / 16 + c * 128];
          uint4 v;
          v.x = (pack_bf16(a[c * 8 + 0] + bf_lo(d.x), a[c * 8 + 1] + bf_hi(d.x)) & ~1u) | par;
          v.y = (pack_bf16(a[c * 8 + 2] + bf_lo(d.y), a[c * 8 + 3] + bf_hi(d.y)) & ~1u) | par;
          v.z = (pack_bf16(a[c * 8 + 4] + bf_lo(d.z), a[c * 8 + 5] + bf_hi(d.z)) & ~1u) | par;
          v.w = (pack_bf16(a[c * 8 + 6] + bf_lo(d.w), a[c * 8 + 7] + bf_hi(d.w)) & ~1u) | par;
          my_base[uslot_off(k) / 16 + c * 128] = v;
        }
        fence_async_smem();
        wg_bar(wg);
        if (t128 == 0) {
          const int dest = (j + 2 * (k + 1)) & 7;
          const uint4* p = &g_part[(size_t)((mb * NSPLIT + dest) * 3 + k) * 1024 + wg * 512];
          asm volatile("cp.async.bulk.global.shared::cta.bulk_group [%0], [%1], %2;"
                       :: "l"(p), "r"(sbase + uslot_off(k) + wg * 8192), "r"(8192) : "memory");
          asm volatile("cp.async.bulk.commit_group;" ::: "memory");
        }
      }
    };
    auto issue = [&](int i) {
      mbar_wait(bar_full + 8 * (16 + 2 * i), 0);
      wg_fence();
#pragma unroll
      for (int ks = 0; ks < 7; ks++) {
        wgmma_rs_n64(acc2[i % 3], h[ks], make_desc(sbase + load_off(16 + 2 * i) + ks * 2048, 16, 1024, 1), ks != 0);
      }
      mbar_wait(bar_full + 8 * (17 + 2 * i), 0);
      wg_fence();
#pragma unroll
      for (int ks = 0; ks < 7; ks++) {
        wgmma_rs_n64(acc2[i % 3], h[7 + ks], make_desc(sbase + load_off(17 + 2 * i) + ks * 2048, 16, 1024, 1), 1);
      }
      wg_commit();
    };
    TSC(12);
    issue(0);
    issue(1);
#pragma unroll
    for (int i = 0; i < 7; i++) {
      wg_wait<1>();
      reg_fence(acc2[i % 3]);
      if (i <= 4 && t128 == 0) { mbar_arrive(bar_cons + 8 * (16 + 2 * i)); mbar_arrive(bar_cons + 8 * (17 + 2 * i)); }
      if (i + 2 < 8) issue(i + 2);
      TSC(13 + i);
      post(i, acc2[i % 3]);
    }
    prefetch(0); prefetch(1); prefetch(2);
    mbar_wait_cluster(bar_dfull + 8 * 3, 0);
#pragma unroll
    for (int c = 0; c < 4; c++) {
      const uint4 d = my_base[uslot_off(3) / 16 + c * 128];
      sum[c * 8 + 0] = bf_lo(d.x); sum[c * 8 + 1] = bf_hi(d.x); sum[c * 8 + 2] = bf_lo(d.y); sum[c * 8 + 3] = bf_hi(d.y);
      sum[c * 8 + 4] = bf_lo(d.z); sum[c * 8 + 5] = bf_hi(d.z); sum[c * 8 + 6] = bf_lo(d.w); sum[c * 8 + 7] = bf_hi(d.w);
    }
    consume(0);
    consume(1);
    wg_wait<0>();
    reg_fence(acc2[1]);
    TSC(20);
    consume(2);
    TSC(21);
    if (tid == 0) g_epoch[blockIdx.x] = epoch + 1;

    {
      const int row0 = mb * BM + wg * 64 + w4 * 16 + g;
      uint32_t* o0 = reinterpret_cast<uint32_t*>(out + (size_t)row0 * D_MOD + j * BN2) + q;
      uint32_t* o1 = o0 + 8 * D_MOD / 2;
#pragma unroll
      for (int i = 0; i < 8; i++) {
        const uint32_t bb = b2s[i * 4 + q];
        o0[i * 4] = hadd2_bf(pack_bf16(acc2[1][4 * i] + sum[4 * i], acc2[1][4 * i + 1] + sum[4 * i + 1]), bb);
        o1[i * 4] = hadd2_bf(pack_bf16(acc2[1][4 * i + 2] + sum[4 * i + 2], acc2[1][4 * i + 3] + sum[4 * i + 3]), bb);
      }
    }
    if (t128 == 0) asm volatile("cp.async.bulk.wait_group 0;" ::: "memory");
    TSC(26);
    TS_FLUSH;
    asm volatile("barrier.cluster.arrive.relaxed.aligned;\nbarrier.cluster.wait.aligned;" ::: "memory");
  }
}

typedef CUresult (*EncodeFn)(CUtensorMap*, CUtensorMapDataType, cuuint32_t, void*, const cuuint64_t*, const cuuint64_t*,
                             const cuuint32_t*, const cuuint32_t*, CUtensorMapInterleave, CUtensorMapSwizzle,
                             CUtensorMapL2promotion, CUtensorMapFloatOOBfill);

}

extern "C" void kernel_launch(void* const* d_in, const int* in_sizes, int n_in, void* d_out, int out_size) {
  (void)in_sizes; (void)n_in; (void)out_size;
  static CUtensorMap tm_x, tm_w1, tm_w2;
  static const void* cached_w1 = nullptr; static const void* cached_w2 = nullptr; static const void* cached_x = nullptr;
  const void* w1 = d_in[1]; const void* w2 = d_in[3]; const void* xp = d_in[0];
  if (cached_w1 != w1 || cached_w2 != w2 || cached_x != xp) {
    void* fn = nullptr; cudaDriverEntryPointQueryResult st;
    cudaGetDriverEntryPoint("cuTensorMapEncodeTiled", &fn, cudaEnableDefault, &st);
    EncodeFn enc = (EncodeFn)fn;
    {
      cuuint64_t dims[3] = {64, (cuuint64_t)S_TOK, (cuuint64_t)(D_MOD / 64)};
      cuuint64_t strides[2] = {(cuuint64_t)D_MOD * 2, 128};
      cuuint32_t box[3] = {64, 64, 8};
      cuuint32_t es[3] = {1, 1, 1};
      enc(&tm_x, CU_TENSOR_MAP_DATA_TYPE_BFLOAT16, 3, const_cast<void*>(xp), dims, strides, box, es,
          CU_TENSOR_MAP_INTERLEAVE_NONE, CU_TENSOR_MAP_SWIZZLE_128B, CU_TENSOR_MAP_L2_PROMOTION_L2_128B, CU_TENSOR_MAP_FLOAT_OOB_FILL_NONE);
    }
    {
      cuuint64_t dims[2] = {(cuuint64_t)F_HID, (cuuint64_t)D_MOD};
      cuuint64_t strides[1] = {(cuuint64_t)F_HID * 2};
      cuuint32_t box[2] = {64, 32};
      cuuint32_t es[2] = {1, 1};
      enc(&tm_w1, CU_TENSOR_MAP_DATA_TYPE_BFLOAT16, 2, const_cast<void*>(w1), dims, strides, box, es,
          CU_TENSOR_MAP_INTERLEAVE_NONE, CU_TENSOR_MAP_SWIZZLE_128B, CU_TENSOR_MAP_L2_PROMOTION_L2_128B, CU_TENSOR_MAP_FLOAT_OOB_FILL_NONE);
    }
    {
      cuuint64_t dims[2] = {(cuuint64_t)D_MOD, (cuuint64_t)F_HID};
      cuuint64_t strides[1] = {(cuuint64_t)D_MOD * 2};
      cuuint32_t box[2] = {64, 112};
      cuuint32_t es[2] = {1, 1};
      enc(&tm_w2, CU_TENSOR_MAP_DATA_TYPE_BFLOAT16, 2, const_cast<void*>(w2), dims, strides, box, es,
          CU_TENSOR_MAP_INTERLEAVE_NONE, CU_TENSOR_MAP_SWIZZLE_128B, CU_TENSOR_MAP_L2_PROMOTION_L2_128B, CU_TENSOR_MAP_FLOAT_OOB_FILL_NONE);
    }
    cudaFuncSetAttribute(fused_mlp_kernel, cudaFuncAttributeMaxDynamicSharedMemorySize, SMEM_TOTAL);
    cached_w1 = w1; cached_w2 = w2; cached_x = xp;
  }
  fused_mlp_kernel<<<NMB * NSPLIT, NTHREADS, SMEM_TOTAL>>>(tm_x, tm_w1, tm_w2,
      (const __nv_bfloat16*)d_in[2], (const __nv_bfloat16*)d_in[4], (__nv_bfloat16*)d_out);
}
```

```cpp
#include <cuda_runtime.h>
#include <cuda_bf16.h>
#include <cuda.h>
#include <stdint.h>

namespace {

constexpr int S_TOK = 2048, D_MOD = 512, F_HID = 1792;
constexpr int BM = 128, NSPLIT = 8, BF = F_HID / NSPLIT;
constexpr int BN2 = D_MOD / NSPLIT;
constexpr int NMB = S_TOK / BM;
constexpr int SLOT_BYTES = 16384;
constexpr int W1_BYTES = 16384;
constexpr int W2_BYTES = 14336;
constexpr int Y_BYTES = BM * D_MOD * 2;
constexpr int NRING = 6;
constexpr int NLOAD = 32;
constexpr int OFF_RING = Y_BYTES;
__host__ __device__ constexpr int yslot_off(int s) { return (s >> 1) * 65536 + (s & 1) * 16384; }
__host__ __device__ constexpr int uslot_off(int s) { return (s >> 1) * 65536 + 32768 + (s & 1) * 16384; }
constexpr int DSLOT_BYTES = 16384;
constexpr int OFF_BAR = OFF_RING + NRING * SLOT_BYTES;
constexpr int OFF_MEAN = OFF_BAR + 640;
constexpr int OFF_B1 = OFF_MEAN + 512;
constexpr int OFF_B2 = OFF_B1 + 1024;
constexpr int SMEM_TOTAL = OFF_B2 + 256;
constexpr int NTHREADS = 384;
static_assert(SMEM_TOTAL <= 232448, "smem");

__device__ uint4 g_part[(size_t)NMB * NSPLIT * 3 * 1024];
__device__ unsigned int g_epoch[NMB * NSPLIT];

#define TS_DECL
#define TS_FLUSH do {} while (0)
#define TS(role, idx) do {} while (0)
#define TSC(idx) do {} while (0)

__device__ __forceinline__ uint32_t smem_u32(const void* p) { return (uint32_t)__cvta_generic_to_shared(p); }
__device__ __forceinline__ uint32_t mapa(uint32_t a, uint32_t r) {
  uint32_t d; asm volatile("mapa.shared::cluster.u32 %0, %1, %2;" : "=r"(d) : "r"(a), "r"(r)); return d;
}
__device__ __forceinline__ void mbar_init(uint32_t bar, uint32_t cnt) {
  asm volatile("mbarrier.init.shared::cta.b64 [%0], %1;" :: "r"(bar), "r"(cnt) : "memory");
}
__device__ __forceinline__ void mbar_expect_tx(uint32_t bar, uint32_t bytes) {
  asm volatile("mbarrier.arrive.expect_tx.shared::cta.b64 _, [%0], %1;" :: "r"(bar), "r"(bytes) : "memory");
}
__device__ __forceinline__ void mbar_arrive(uint32_t bar) {
  asm volatile("mbarrier.arrive.shared::cta.b64 _, [%0];" :: "r"(bar) : "memory");
}
__device__ __forceinline__ void mbar_arrive_remote(uint32_t rbar) {
  asm volatile("mbarrier.arrive.release.cluster.shared::cluster.b64 _, [%0];" :: "r"(rbar) : "memory");
}
__device__ __forceinline__ void mbar_wait(uint32_t bar, uint32_t parity) {
  uint32_t done = 0; uint32_t it = 0;
  while (true) {
    asm volatile("{\n.reg .pred p;\nmbarrier.try_wait.parity.shared::cta.b64 p, [%1], %2;\nselp.u32 %0, 1, 0, p;\n}"
                 : "=r"(done) : "r"(bar), "r"(parity) : "memory");
    if (done) break;
    if (++it > (1u << 22)) asm volatile("trap;");
  }
}
__device__ __forceinline__ void mbar_wait_cluster(uint32_t bar, uint32_t parity) {
  uint32_t done = 0; uint32_t it = 0;
  while (true) {
    asm volatile("{\n.reg .pred p;\nmbarrier.try_wait.parity.acquire.cluster.shared::cta.b64 p, [%1], %2;\nselp.u32 %0, 1, 0, p;\n}"
                 : "=r"(done) : "r"(bar), "r"(parity) : "memory");
    if (done) break;
    if (++it > (1u << 22)) asm volatile("trap;");
  }
}
__device__ __forceinline__ void tma_load_3d(uint32_t dst, const CUtensorMap* tm, int c0, int c1, int c2, uint32_t bar) {
  asm volatile("cp.async.bulk.tensor.3d.shared::cluster.global.mbarrier::complete_tx::bytes [%0], [%1, {%3, %4, %5}], [%2];"
               :: "r"(dst), "l"(tm), "r"(bar), "r"(c0), "r"(c1), "r"(c2) : "memory");
}
__device__ __forceinline__ void tma_load_2d(uint32_t dst, const CUtensorMap* tm, int c0, int c1, uint32_t bar) {
  asm volatile("cp.async.bulk.tensor.2d.shared::cluster.global.mbarrier::complete_tx::bytes [%0], [%1, {%3, %4}], [%2];"
               :: "r"(dst), "l"(tm), "r"(bar), "r"(c0), "r"(c1) : "memory");
}
__device__ __forceinline__ void tma_prefetch_2d(const CUtensorMap* tm, int c0, int c1) {
  asm volatile("cp.async.bulk.prefetch.tensor.2d.L2.global.tile [%0, {%1, %2}];" :: "l"(tm), "r"(c0), "r"(c1) : "memory");
}
__device__ __forceinline__ void fence_async_smem() { asm volatile("fence.proxy.async.shared::cta;" ::: "memory"); }
__device__ __forceinline__ void wg_bar(int wg) {
  if (wg == 0) asm volatile("bar.sync 1, 128;" ::: "memory"); else asm volatile("bar.sync 2, 128;" ::: "memory");
}
__device__ __forceinline__ void wg_fence() { asm volatile("wgmma.fence.sync.aligned;" ::: "memory"); }
__device__ __forceinline__ void wg_commit() { asm volatile("wgmma.commit_group.sync.aligned;" ::: "memory"); }
template <int N> __device__ __forceinline__ void wg_wait() { asm volatile("wgmma.wait_group.sync.aligned %0;" :: "n"(N) : "memory"); }
template <int N> __device__ __forceinline__ void reg_fence(float (&d)[N]) {
#pragma unroll
  for (int i = 0; i < N; i++) asm volatile("" : "+f"(d[i]) :: "memory");
}
__device__ __forceinline__ uint64_t make_desc(uint32_t addr, uint32_t lbo, uint32_t sbo, uint32_t lt) {
  return (uint64_t)((addr & 0x3FFFF) >> 4) | ((uint64_t)(lbo >> 4) << 16) | ((uint64_t)(sbo >> 4) << 32) | ((uint64_t)lt << 62);
}
__device__ __forceinline__ uint32_t pack_bf16(float lo, float hi) {
  uint32_t r; asm("cvt.rn.bf16x2.f32 %0, %1, %2;" : "=r"(r) : "f"(hi), "f"(lo)); return r;
}
__device__ __forceinline__ float bf_lo(uint32_t v) { return __uint_as_float(v << 16); }
__device__ __forceinline__ float bf_hi(uint32_t v) { return __uint_as_float(v & 0xffff0000u); }
__device__ __forceinline__ float bf16r(float v) { return __bfloat162float(__float2bfloat16_rn(v)); }
__device__ __forceinline__ uint32_t hadd2_bf(uint32_t a, uint32_t b) {
  uint32_t r; asm("add.rn.bf16x2 %0, %1, %2;" : "=r"(r) : "r"(a), "r"(b)); return r;
}
__device__ __forceinline__ uint32_t hsub2_bf(uint32_t a, uint32_t b) {
  uint32_t r; asm("sub.rn.bf16x2 %0, %1, %2;" : "=r"(r) : "r"(a), "r"(b)); return r;
}
__device__ __forceinline__ float gelu_tanh(float u) {
  float inner = u * fmaf(0.035677408136300125f, u * u, 0.7978845608028654f);
  float th; asm("tanh.approx.f32 %0, %1;" : "=f"(th) : "f"(inner));
  float hu = 0.5f * u;
  return fmaf(hu, th, hu);
}
__device__ __forceinline__ void mma16816(float (&c)[4], uint32_t a0, uint32_t a1, uint32_t a2, uint32_t a3, uint32_t b0, uint32_t b1) {
  asm volatile("mma.sync.aligned.m16n8k16.row.col.f32.bf16.bf16.f32 {%0,%1,%2,%3}, {%4,%5,%6,%7}, {%8,%9}, {%0,%1,%2,%3};"
               : "+f"(c[0]), "+f"(c[1]), "+f"(c[2]), "+f"(c[3]) : "r"(a0), "r"(a1), "r"(a2), "r"(a3), "r"(b0), "r"(b1));
}

__device__ __forceinline__ void wgmma_ss_n224(float (&d)[112], uint64_t descA, uint64_t descB, int scaleD) {
  asm volatile("{\n.reg .pred p;\nsetp.ne.b32 p, %114, 0;\n"
    "wgmma.mma_async.sync.aligned.m64n224k16.f32.bf16.bf16 {%0, %1, %2, %3, %4, %5, %6, %7, %8, %9, %10, %11, %12, %13, %14, %15, %16, %17, %18, %19, %20, %21, %22, %23, %24, %25, %26, %27, %28, %29, %30, %31, %32, %33, %34, %35, %36, %37, %38, %39, %40, %41, %42, %43, %44, %45, %46, %47, %48, %49, %50, %51, %52, %53, %54, %55, %56, %57, %58, %59, %60, %61, %62, %63, %64, %65, %66, %67, %68, %69, %70, %71, %72, %73, %74, %75, %76, %77, %78, %79, %80, %81, %82, %83, %84, %85, %86, %87, %88, %89, %90, %91, %92, %93, %94, %95, %96, %97, %98, %99, %100, %101, %102, %103, %104, %105, %106, %107, %108, %109, %110, %111}, %112, %113, p, 1, 1, 0, 1;\n}\n"
    : "+f"(d[0]), "+f"(d[1]), "+f"(d[2]), "+f"(d[3]), "+f"(d[4]), "+f"(d[5]), "+f"(d[6]), "+f"(d[7]), "+f"(d[8]), "+f"(d[9]), "+f"(d[10]), "+f"(d[11]), "+f"(d[12]), "+f"(d[13]), "+f"(d[14]), "+f"(d[15]), "+f"(d[16]), "+f"(d[17]), "+f"(d[18]), "+f"(d[19]), "+f"(d[20]), "+f"(d[21]), "+f"(d[22]), "+f"(d[23]), "+f"(d[24]), "+f"(d[25]), "+f"(d[26]), "+f"(d[27]), "+f"(d[28]), "+f"(d[29]), "+f"(d[30]), "+f"(d[31]), "+f"(d[32]), "+f"(d[33]), "+f"(d[34]), "+f"(d[35]), "+f"(d[36]), "+f"(d[37]), "+f"(d[38]), "+f"(d[39]), "+f"(d[40]), "+f"(d[41]), "+f"(d[42]), "+f"(d[43]), "+f"(d[44]), "+f"(d[45]), "+f"(d[46]), "+f"(d[47]), "+f"(d[48]), "+f"(d[49]), "+f"(d[50]), "+f"(d[51]), "+f"(d[52]), "+f"(d[53]), "+f"(d[54]), "+f"(d[55]), "+f"(d[56]), "+f"(d[57]), "+f"(d[58]), "+f"(d[59]), "+f"(d[60]), "+f"(d[61]), "+f"(d[62]), "+f"(d[63]), "+f"(d[64]), "+f"(d[65]), "+f"(d[66]), "+f"(d[67]), "+f"(d[68]), "+f"(d[69]), "+f"(d[70]), "+f"(d[71]), "+f"(d[72]), "+f"(d[73]), "+f"(d[74]), "+f"(d[75]), "+f"(d[76]), "+f"(d[77]), "+f"(d[78]), "+f"(d[79]), "+f"(d[80]), "+f"(d[81]), "+f"(d[82]), "+f"(d[83]), "+f"(d[84]), "+f"(d[85]), "+f"(d[86]), "+f"(d[87]), "+f"(d[88]), "+f"(d[89]), "+f"(d[90]), "+f"(d[91]), "+f"(d[92]), "+f"(d[93]), "+f"(d[94]), "+f"(d[95]), "+f"(d[96]), "+f"(d[97]), "+f"(d[98]), "+f"(d[99]), "+f"(d[100]), "+f"(d[101]), "+f"(d[102]), "+f"(d[103]), "+f"(d[104]), "+f"(d[105]), "+f"(d[106]), "+f"(d[107]), "+f"(d[108]), "+f"(d[109]), "+f"(d[110]), "+f"(d[111])
    : "l"(descA), "l"(descB), "r"(scaleD));
}

__device__ __forceinline__ void wgmma_rs_n64(float (&d)[32], const uint32_t (&a)[4], uint64_t descB, int scaleD) {
  asm volatile("{\n.reg .pred p;\nsetp.ne.b32 p, %37, 0;\n"
    "wgmma.mma_async.sync.aligned.m64n64k16.f32.bf16.bf16 {%0, %1, %2, %3, %4, %5, %6, %7, %8, %9, %10, %11, %12, %13, %14, %15, %16, %17, %18, %19, %20, %21, %22, %23, %24, %25, %26, %27, %28, %29, %30, %31}, {%32, %33, %34, %35}, %36, p, 1, 1, 1;\n}\n"
    : "+f"(d[0]), "+f"(d[1]), "+f"(d[2]), "+f"(d[3]), "+f"(d[4]), "+f"(d[5]), "+f"(d[6]), "+f"(d[7]), "+f"(d[8]), "+f"(d[9]), "+f"(d[10]), "+f"(d[11]), "+f"(d[12]), "+f"(d[13]), "+f"(d[14]), "+f"(d[15]), "+f"(d[16]), "+f"(d[17]), "+f"(d[18]), "+f"(d[19]), "+f"(d[20]), "+f"(d[21]), "+f"(d[22]), "+f"(d[23]), "+f"(d[24]), "+f"(d[25]), "+f"(d[26]), "+f"(d[27]), "+f"(d[28]), "+f"(d[29]), "+f"(d[30]), "+f"(d[31])
    : "r"(a[0]), "r"(a[1]), "r"(a[2]), "r"(a[3]), "l"(descB), "r"(scaleD));
}

__device__ __forceinline__ void wgmma_rs_n224(float (&d)[112], const uint32_t (&a)[4], uint64_t descB, int scaleD) {
  asm volatile("{\n.reg .pred p;\nsetp.ne.b32 p, %117, 0;\n"
    "wgmma.mma_async.sync.aligned.m64n224k16.f32.bf16.bf16 {%0, %1, %2, %3, %4, %5, %6, %7, %8, %9, %10, %11, %12, %13, %14, %15, %16, %17, %18, %19, %20, %21, %22, %23, %24, %25, %26, %27, %28, %29, %30, %31, %32, %33, %34, %35, %36, %37, %38, %39, %40, %41, %42, %43, %44, %45, %46, %47, %48, %49, %50, %51, %52, %53, %54, %55, %56, %57, %58, %59, %60, %61, %62, %63, %64, %65, %66, %67, %68, %69, %70, %71, %72, %73, %74, %75, %76, %77, %78, %79, %80, %81, %82, %83, %84, %85, %86, %87, %88, %89, %90, %91, %92, %93, %94, %95, %96, %97, %98, %99, %100, %101, %102, %103, %104, %105, %106, %107, %108, %109, %110, %111}, {%112, %113, %114, %115}, %116, p, 1, 1, 1;\n}\n"
    : "+f"(d[0]), "+f"(d[1]), "+f"(d[2]), "+f"(d[3]), "+f"(d[4]), "+f"(d[5]), "+f"(d[6]), "+f"(d[7]), "+f"(d[8]), "+f"(d[9]), "+f"(d[10]), "+f"(d[11]), "+f"(d[12]), "+f"(d[13]), "+f"(d[14]), "+f"(d[15]), "+f"(d[16]), "+f"(d[17]), "+f"(d[18]), "+f"(d[19]), "+f"(d[20]), "+f"(d[21]), "+f"(d[22]), "+f"(d[23]), "+f"(d[24]), "+f"(d[25]), "+f"(d[26]), "+f"(d[27]), "+f"(d[28]), "+f"(d[29]), "+f"(d[30]), "+f"(d[31]), "+f"(d[32]), "+f"(d[33]), "+f"(d[34]), "+f"(d[35]), "+f"(d[36]), "+f"(d[37]), "+f"(d[38]), "+f"(d[39]), "+f"(d[40]), "+f"(d[41]), "+f"(d[42]), "+f"(d[43]), "+f"(d[44]), "+f"(d[45]), "+f"(d[46]), "+f"(d[47]), "+f"(d[48]), "+f"(d[49]), "+f"(d[50]), "+f"(d[51]), "+f"(d[52]), "+f"(d[53]), "+f"(d[54]), "+f"(d[55]), "+f"(d[56]), "+f"(d[57]), "+f"(d[58]), "+f"(d[59]), "+f"(d[60]), "+f"(d[61]), "+f"(d[62]), "+f"(d[63]), "+f"(d[64]), "+f"(d[65]), "+f"(d[66]), "+f"(d[67]), "+f"(d[68]), "+f"(d[69]), "+f"(d[70]), "+f"(d[71]), "+f"(d[72]), "+f"(d[73]), "+f"(d[74]), "+f"(d[75]), "+f"(d[76]), "+f"(d[77]), "+f"(d[78]), "+f"(d[79]), "+f"(d[80]), "+f"(d[81]), "+f"(d[82]), "+f"(d[83]), "+f"(d[84]), "+f"(d[85]), "+f"(d[86]), "+f"(d[87]), "+f"(d[88]), "+f"(d[89]), "+f"(d[90]), "+f"(d[91]), "+f"(d[92]), "+f"(d[93]), "+f"(d[94]), "+f"(d[95]), "+f"(d[96]), "+f"(d[97]), "+f"(d[98]), "+f"(d[99]), "+f"(d[100]), "+f"(d[101]), "+f"(d[102]), "+f"(d[103]), "+f"(d[104]), "+f"(d[105]), "+f"(d[106]), "+f"(d[107]), "+f"(d[108]), "+f"(d[109]), "+f"(d[110]), "+f"(d[111])
    : "r"(a[0]), "r"(a[1]), "r"(a[2]), "r"(a[3]), "l"(descB), "r"(scaleD));
}

__host__ __device__ constexpr int step_kind(int i) { return (i == 0 || i == 1 || i == 3 || i == 6) ? 0 : (i == 7 ? 2 : 1); }
__host__ __device__ constexpr int step_k(int i) { return i == 0 ? 0 : i == 1 ? 1 : i == 2 ? 0 : i == 3 ? 2 : i == 4 ? 1 : i == 5 ? 2 : 3; }
__device__ __forceinline__ int step_slice(int i, int j) {
  const int kind = step_kind(i), k = step_k(i);
  const int base = (kind == 0) ? (j ^ 1) : j;
  return (k == 3) ? base : ((base + 2 * (k + 1)) & 7);
}

__host__ __device__ constexpr int load_off(int i) {
  return i < 6 ? OFF_RING + i * SLOT_BYTES : (i < 10 ? yslot_off(i - 6) : OFF_RING + ((i - 10) % NRING) * SLOT_BYTES);
}
__host__ __device__ constexpr int load_dep(int i) { return i < 6 ? -1 : (i < 10 ? -2 : (i < 16 ? i - 10 : i - 6)); }

__global__ void __cluster_dims__(2, 1, 1) __launch_bounds__(NTHREADS, 1)
fused_mlp_kernel(const __grid_constant__ CUtensorMap tm_x, const __grid_constant__ CUtensorMap tm_w1, const __grid_constant__ CUtensorMap tm_w2,
                 const __nv_bfloat16* __restrict__ b1, const __nv_bfloat16* __restrict__ b2, __nv_bfloat16* __restrict__ out)
{
  extern __shared__ __align__(1024) unsigned char smem[];
  const uint32_t sbase = smem_u32(smem);
  const uint32_t bar_full = sbase + OFF_BAR;
  const uint32_t bar_cons = sbase + OFF_BAR + 256;
  const uint32_t bar_x = sbase + OFF_BAR + 512;
  const uint32_t bar_dfull = sbase + OFF_BAR + 528;
  const uint32_t bar_peer = sbase + OFF_BAR + 560;
  const uint32_t bar_ln = sbase + OFF_BAR + 568;
  const int tid = threadIdx.x, warp = tid >> 5, lane = tid & 31;
  const int mb = blockIdx.x >> 3, j = blockIdx.x & 7;

  TS_DECL
  TSC(0);
  if (warp == 8) {
    mbar_init(bar_full + 8 * lane, 1); mbar_init(bar_cons + 8 * lane, 2);
    if (lane < 4) mbar_init(bar_dfull + 8 * lane, 1);
    if (lane == 4) mbar_init(bar_peer, 2);
    if (lane == 5) mbar_init(bar_ln, 2);
    if (lane == 6) mbar_init(bar_x, 1);
    if (lane == 7) mbar_init(bar_x + 8, 1);
    asm volatile("fence.mbarrier_init.release.cluster;" ::: "memory");
    fence_async_smem();
    __syncwarp();
    if (lane < 4) mbar_expect_tx(bar_dfull + 8 * lane, DSLOT_BYTES);
    __syncwarp();
  }
  asm volatile("barrier.cluster.arrive.relaxed.aligned;" ::: "memory");
  __syncthreads();

  if (warp >= 8) {
    asm volatile("setmaxnreg.dec.sync.aligned.u32 40;");
    if (warp == 8 && lane == 0) {
      mbar_expect_tx(bar_x, 65536);
      tma_load_3d(sbase, &tm_x, 0, mb * BM, 0, bar_x);
      for (int i = 0; i < NRING; i++) {
        if (i == 2) {
          mbar_expect_tx(bar_x + 8, 65536);
          tma_load_3d(sbase + 65536, &tm_x, 0, mb * BM + 64, 0, bar_x + 8);
        }
        mbar_expect_tx(bar_full + 8 * i, W1_BYTES);
        for (int a = 0; a < 4; a++)
          tma_load_2d(sbase + OFF_RING + i * SLOT_BYTES + a * 4096, &tm_w1, j * BF + a * 64, i * 32, bar_full + 8 * i);
      }
      TS(2, 1);
      for (int t = 2 * mb; t < 2 * mb + 2; t++) {
        if (t < 16) { if (t >= NRING) for (int a = 0; a < 4; a++) tma_prefetch_2d(&tm_w1, j * BF + a * 64, t * 32); }
        else tma_prefetch_2d(&tm_w2, ((t - 16) >> 1) * 64, j * BF + ((t - 16) & 1) * 112);
      }
#pragma unroll
      for (int i = NRING; i < NLOAD; i++) {
        if (load_dep(i) >= 0) mbar_wait(bar_cons + 8 * load_dep(i), 0); else if (i == NRING) mbar_wait(bar_ln, 0);
        TS(2, i);
        const uint32_t dst = sbase + load_off(i);
        if (i < 16) {
          mbar_expect_tx(bar_full + 8 * i, W1_BYTES);
          for (int a = 0; a < 4; a++) tma_load_2d(dst + a * 4096, &tm_w1, j * BF + a * 64, i * 32, bar_full + 8 * i);
        } else {
          mbar_expect_tx(bar_full + 8 * i, W2_BYTES);
          tma_load_2d(dst, &tm_w2, step_slice((i - 16) >> 1, j) * BN2, j * BF + ((i - 16) & 1) * 112, bar_full + 8 * i);
        }
      }
    }
    __syncwarp();
    asm volatile("barrier.cluster.wait.aligned;" ::: "memory");
    asm volatile("barrier.cluster.arrive.relaxed.aligned;\nbarrier.cluster.wait.aligned;" ::: "memory");
  } else {
    asm volatile("setmaxnreg.inc.sync.aligned.u32 232;");
    const int wg = warp >> 2, w4 = warp & 3, t128 = tid & 127;
    const int q = lane & 3, g = lane >> 2;
    uint32_t* b1s = reinterpret_cast<uint32_t*>(smem + OFF_B1 + wg * 512);
    uint32_t* b2s = reinterpret_cast<uint32_t*>(smem + OFF_B2 + wg * 128);
    uint32_t bias_a = 0, bias_b = 0;
    if (t128 < BF / 2) bias_a = reinterpret_cast<const uint32_t*>(b1 + j * BF)[t128];
    if (t128 < BN2 / 2) bias_b = reinterpret_cast<const uint32_t*>(b2 + j * BN2)[t128];
    const uint32_t epoch = g_epoch[blockIdx.x];

    float r0, r1;
    uint32_t xa[16][4];
    TSC(24);
    mbar_wait(bar_x + 8 * wg, 0);
    TSC(25);
    {
      uint32_t xb[16][4];
      float cs[2][4], c0[2][4], c1[2][4];
#pragma unroll
      for (int u = 0; u < 2; u++)
#pragma unroll
        for (int e = 0; e < 4; e++) { cs[u][e] = 0.f; c0[u][e] = 0.f; c1[u][e] = 0.f; }
      const int lrow = w4 * 16 + (lane & 7) + ((lane >> 3) & 1) * 8;
      const uint32_t lbase = sbase + wg * 65536 + lrow * 128;
      const uint32_t ones = 0x3F803F80u;
#pragma unroll
      for (int ks = 0; ks < 32; ks++) {
        uint32_t (&a)[4] = ks < 16 ? xa[ks] : xb[ks - 16];
        const uint32_t addr = lbase + (ks >> 2) * 8192 + (((2 * (ks & 3) + (lane >> 4)) ^ (lane & 7)) << 4);
        asm volatile("ldmatrix.sync.aligned.m8n8.x4.shared.b16 {%0,%1,%2,%3}, [%4];" : "=r"(a[0]), "=r"(a[1]), "=r"(a[2]), "=r"(a[3]) : "r"(addr));
        mma16816(cs[ks & 1], a[0], a[1], a[2], a[3], ones, ones);
        mma16816(c0[ks & 1], a[0], a[1], a[2], a[3], a[0], a[2]);
        mma16816(c1[ks & 1], a[0], a[1], a[2], a[3], a[1], a[3]);
      }
      TSC(27);
      const int dsrc = g * 4 + (g >> 1);
      const float q0 = __shfl_sync(0xffffffffu, (g & 1) ? c0[0][1] + c0[1][1] : c0[0][0] + c0[1][0], dsrc);
      const float q1 = __shfl_sync(0xffffffffu, (g & 1) ? c1[0][3] + c1[1][3] : c1[0][2] + c1[1][2], dsrc);
      const float m0 = (cs[0][0] + cs[1][0]) * (1.0f / D_MOD), m1 = (cs[0][2] + cs[1][2]) * (1.0f / D_MOD);
      const uint32_t mm0 = pack_bf16(m0, m0), mm1 = pack_bf16(m1, m1);
#pragma unroll
      for (int ks = 16; ks < 32; ks++) {
        const uint32_t addr = lbase + (ks >> 2) * 8192 + (((2 * (ks & 3) + (lane >> 4)) ^ (lane & 7)) << 4);
        asm volatile("stmatrix.sync.aligned.m8n8.x4.shared.b16 [%0], {%1,%2,%3,%4};" :: "r"(addr),
                     "r"(hsub2_bf(xb[ks - 16][0], mm0)), "r"(hsub2_bf(xb[ks - 16][1], mm1)),
                     "r"(hsub2_bf(xb[ks - 16][2], mm0)), "r"(hsub2_bf(xb[ks - 16][3], mm1)) : "memory");
      }
#pragma unroll
      for (int ks = 0; ks < 16; ks++) {
        xa[ks][0] = hsub2_bf(xa[ks][0], mm0); xa[ks][1] = hsub2_bf(xa[ks][1], mm1);
        xa[ks][2] = hsub2_bf(xa[ks][2], mm0); xa[ks][3] = hsub2_bf(xa[ks][3], mm1);
      }
      const float v0 = fmaxf(fmaf(-m0, m0, q0 * (1.0f / D_MOD)), 0.f), v1 = fmaxf(fmaf(-m1, m1, q1 * (1.0f / D_MOD)), 0.f);
      r0 = 1.0f / bf16r(sqrtf(bf16r(bf16r(v0) + 1e-5f)));
      r1 = 1.0f / bf16r(sqrtf(bf16r(bf16r(v1) + 1e-5f)));
    }
    if (t128 < BF / 2) b1s[t128] = bias_a;
    if (t128 < BN2 / 2) b2s[t128] = bias_b;
    TSC(1);
    fence_async_smem();
    wg_bar(wg);
    if (t128 == 0) mbar_arrive(bar_ln);
    TSC(2);

    uint32_t h[14][4];
    {
      float acc[112];
#pragma unroll
      for (int kb = 0; kb < 16; kb++) {
        mbar_wait(bar_full + 8 * kb, 0);
        wg_fence();
        const uint32_t abase = sbase + wg * 65536 + (kb >> 1) * 8192 + (kb & 1) * 64;
        const uint32_t bbase = sbase + load_off(kb);
#pragma unroll
        for (int kk = 0; kk < 2; kk++) {
          if (kb < 8) wgmma_rs_n224(acc, xa[2 * kb + kk], make_desc(bbase + kk * 2048, 4096, 1024, 1), (kb | kk) != 0);
          else wgmma_ss_n224(acc, make_desc(abase + kk * 32, 16, 1024, 1), make_desc(bbase + kk * 2048, 4096, 1024, 1), 1);
        }
        wg_commit();
        if (kb > 0) { wg_wait<1>(); if (t128 == 0) mbar_arrive(bar_cons + 8 * (kb - 1)); }
      }
      wg_wait<0>();
      reg_fence(acc);
      asm volatile("barrier.cluster.wait.aligned;" ::: "memory");
      if (t128 == 0) { mbar_arrive(bar_cons + 8 * 15); mbar_arrive_remote(mapa(bar_peer, (j & 1) ^ 1)); }
      TSC(11);

#pragma unroll
      for (int i = 0; i < 28; i++) {
        const uint32_t bb = b1s[i * 4 + q];
        uint32_t p0 = hadd2_bf(pack_bf16(acc[4 * i] * r0, acc[4 * i + 1] * r0), bb);
        uint32_t p1 = hadd2_bf(pack_bf16(acc[4 * i + 2] * r1, acc[4 * i + 3] * r1), bb);
        h[i >> 1][(i & 1) * 2 + 0] = pack_bf16(gelu_tanh(bf_lo(p0)), gelu_tanh(bf_hi(p0)));
        h[i >> 1][(i & 1) * 2 + 1] = pack_bf16(gelu_tanh(bf_lo(p1)), gelu_tanh(bf_hi(p1)));
      }
    }

    const uint32_t par = (epoch + 1) & 1;
    float acc2[2][32];
    float sum[32];
    uint4 pf[3][4];
    const uint32_t peer_base = mapa(sbase + wg * 8192, (j & 1) ^ 1);
    const uint32_t peer_dfull = mapa(bar_dfull, (j & 1) ^ 1);
    uint4* my_base = reinterpret_cast<uint4*>(smem) + wg * 512 + t128;
    const uint4* in_part = &g_part[(size_t)((mb * NSPLIT + j) * 3) * 1024 + wg * 512 + t128];
    auto ld_part = [&](const uint4* p) {
      uint4 v;
      asm volatile("ld.relaxed.gpu.global.v4.u32 {%0, %1, %2, %3}, [%4];" : "=r"(v.x), "=r"(v.y), "=r"(v.z), "=r"(v.w) : "l"(p) : "memory");
      return v;
    };
    auto prefetch = [&](int k) {
#pragma unroll
      for (int c = 0; c < 4; c++) pf[k][c] = ld_part(in_part + k * 1024 + c * 128);
    };
    auto consume = [&](int k) {
#pragma unroll
      for (int c = 0; c < 4; c++) {
        uint4 v = pf[k][c];
        uint32_t it = 0;
        while ((((v.x ^ par) | (v.y ^ par) | (v.z ^ par) | (v.w ^ par)) & 1u) != 0) {
          v = ld_part(in_part + k * 1024 + c * 128);
          if (++it > (1u << 20)) asm volatile("trap;");
        }
        sum[c * 8 + 0] += bf_lo(v.x & ~1u); sum[c * 8 + 1] += bf_hi(v.x);
        sum[c * 8 + 2] += bf_lo(v.y & ~1u); sum[c * 8 + 3] += bf_hi(v.y);
        sum[c * 8 + 4] += bf_lo(v.z & ~1u); sum[c * 8 + 5] += bf_hi(v.z);
        sum[c * 8 + 6] += bf_lo(v.w & ~1u); sum[c * 8 + 7] += bf_hi(v.w);
      }
    };
    auto post_pack = [&](int st, float (&a)[32], uint4 (&v)[4]) {
      const int kind = step_kind(st), k = step_k(st);
      if (kind == 0) {
#pragma unroll
        for (int c = 0; c < 4; c++) {
          v[c].x = pack_bf16(a[c * 8 + 0], a[c * 8 + 1]); v[c].y = pack_bf16(a[c * 8 + 2], a[c * 8 + 3]);
          v[c].z = pack_bf16(a[c * 8 + 4], a[c * 8 + 5]); v[c].w = pack_bf16(a[c * 8 + 6], a[c * 8 + 7]);
        }
      } else {
#pragma unroll
        for (int c = 0; c < 4; c++) {
          const uint4 d = v[c];
          v[c].x = (pack_bf16(a[c * 8 + 0] + bf_lo(d.x), a[c * 8 + 1] + bf_hi(d.x)) & ~1u) | par;
          v[c].y = (pack_bf16(a[c * 8 + 2] + bf_lo(d.y), a[c * 8 + 3] + bf_hi(d.y)) & ~1u) | par;
          v[c].z = (pack_bf16(a[c * 8 + 4] + bf_lo(d.z), a[c * 8 + 5] + bf_hi(d.z)) & ~1u) | par;
          v[c].w = (pack_bf16(a[c * 8 + 6] + bf_lo(d.w), a[c * 8 + 7] + bf_hi(d.w)) & ~1u) | par;
        }
      }
      (void)k;
    };
    auto post_send = [&](int st, uint4 (&v)[4]) {
      const int kind = step_kind(st), k = step_k(st);
      if (kind == 0) {
        if (st == 0) mbar_wait(bar_cons + 8 * 15, 0);
#pragma unroll
        for (int c = 0; c < 4; c++) my_base[yslot_off(k) / 16 + c * 128] = v[c];
        fence_async_smem();
        wg_bar(wg);
        if (t128 == 0) {
          if (st == 0) mbar_wait_cluster(bar_peer, 0);
          asm volatile("cp.async.bulk.shared::cluster.shared::cta.mbarrier::complete_tx::bytes [%0], [%1], %2, [%3];"
                       :: "r"(peer_base + uslot_off(k)), "r"(sbase + yslot_off(k) + wg * 8192), "r"(8192), "r"(peer_dfull + 8 * k) : "memory");
        }
      } else {
#pragma unroll
        for (int c = 0; c < 4; c++) my_base[uslot_off(k) / 16 + c * 128] = v[c];
        fence_async_smem();
        wg_bar(wg);
        if (t128 == 0) {
          const int dest = (j + 2 * (k + 1)) & 7;
          const uint4* p = &g_part[(size_t)((mb * NSPLIT + dest) * 3 + k) * 1024 + wg * 512];
          asm volatile("cp.async.bulk.global.shared::cta.bulk_group [%0], [%1], %2;"
                       :: "l"(p), "r"(sbase + uslot_off(k) + wg * 8192), "r"(8192) : "memory");
          asm volatile("cp.async.bulk.commit_group;" ::: "memory");
        }
      }
    };
    auto issue = [&](int i) {
      mbar_wait(bar_full + 8 * (16 + 2 * i), 0);
      wg_fence();
#pragma unroll
      for (int ks = 0; ks < 7; ks++) {
        wgmma_rs_n64(acc2[i & 1], h[ks], make_desc(sbase + load_off(16 + 2 * i) + ks * 2048, 16, 1024, 1), ks != 0);
      }
      mbar_wait(bar_full + 8 * (17 + 2 * i), 0);
      wg_fence();
#pragma unroll
      for (int ks = 0; ks < 7; ks++) {
        wgmma_rs_n64(acc2[i & 1], h[7 + ks], make_desc(sbase + load_off(17 + 2 * i) + ks * 2048, 16, 1024, 1), 1);
      }
      wg_commit();
    };
    TSC(12);
    issue(0);
    issue(1);
#pragma unroll
    for (int i = 0; i < 7; i++) {
      uint4 v[4];
      if (step_kind(i) == 1) {
        mbar_wait_cluster(bar_dfull + 8 * step_k(i), 0);
#pragma unroll
        for (int c = 0; c < 4; c++) v[c] = my_base[uslot_off(step_k(i)) / 16 + c * 128];
      }
      wg_wait<1>();
      reg_fence(acc2[i & 1]);
      post_pack(i, acc2[i & 1], v);
      if (i <= 4 && t128 == 0) { mbar_arrive(bar_cons + 8 * (16 + 2 * i)); mbar_arrive(bar_cons + 8 * (17 + 2 * i)); }
      if (i + 2 < 8) issue(i + 2);
      TSC(13 + i);
      post_send(i, v);
    }
    prefetch(0); prefetch(1); prefetch(2);
    mbar_wait_cluster(bar_dfull + 8 * 3, 0);
#pragma unroll
    for (int c = 0; c < 4; c++) {
      const uint4 d = my_base[uslot_off(3) / 16 + c * 128];
      sum[c * 8 + 0] = bf_lo(d.x); sum[c * 8 + 1] = bf_hi(d.x); sum[c * 8 + 2] = bf_lo(d.y); sum[c * 8 + 3] = bf_hi(d.y);
      sum[c * 8 + 4] = bf_lo(d.z); sum[c * 8 + 5] = bf_hi(d.z); sum[c * 8 + 6] = bf_lo(d.w); sum[c * 8 + 7] = bf_hi(d.w);
    }
    consume(0);
    consume(1);
    wg_wait<0>();
    reg_fence(acc2[1]);
    TSC(20);
    consume(2);
    TSC(21);
    if (tid == 0) g_epoch[blockIdx.x] = epoch + 1;

    {
      const int row0 = mb * BM + wg * 64 + w4 * 16 + g;
      uint32_t* o0 = reinterpret_cast<uint32_t*>(out + (size_t)row0 * D_MOD + j * BN2) + q;
      uint32_t* o1 = o0 + 8 * D_MOD / 2;
#pragma unroll
      for (int i = 0; i < 8; i++) {
        const uint32_t bb = b2s[i * 4 + q];
        o0[i * 4] = hadd2_bf(pack_bf16(acc2[1][4 * i] + sum[4 * i], acc2[1][4 * i + 1] + sum[4 * i + 1]), bb);
        o1[i * 4] = hadd2_bf(pack_bf16(acc2[1][4 * i + 2] + sum[4 * i + 2], acc2[1][4 * i + 3] + sum[4 * i + 3]), bb);
      }
    }
    if (t128 == 0) asm volatile("cp.async.bulk.wait_group 0;" ::: "memory");
    TSC(26);
    TS_FLUSH;
    asm volatile("barrier.cluster.arrive.relaxed.aligned;\nbarrier.cluster.wait.aligned;" ::: "memory");
  }
}

typedef CUresult (*EncodeFn)(CUtensorMap*, CUtensorMapDataType, cuuint32_t, void*, const cuuint64_t*, const cuuint64_t*,
                             const cuuint32_t*, const cuuint32_t*, CUtensorMapInterleave, CUtensorMapSwizzle,
                             CUtensorMapL2promotion, CUtensorMapFloatOOBfill);

}

extern "C" void kernel_launch(void* const* d_in, const int* in_sizes, int n_in, void* d_out, int out_size) {
  (void)in_sizes; (void)n_in; (void)out_size;
  static CUtensorMap tm_x, tm_w1, tm_w2;
  static const void* cached_w1 = nullptr; static const void* cached_w2 = nullptr; static const void* cached_x = nullptr;
  const void* w1 = d_in[1]; const void* w2 = d_in[3]; const void* xp = d_in[0];
  if (cached_w1 != w1 || cached_w2 != w2 || cached_x != xp) {
    void* fn = nullptr; cudaDriverEntryPointQueryResult st;
    cudaGetDriverEntryPoint("cuTensorMapEncodeTiled", &fn, cudaEnableDefault, &st);
    EncodeFn enc = (EncodeFn)fn;
    {
      cuuint64_t dims[3] = {64, (cuuint64_t)S_TOK, (cuuint64_t)(D_MOD / 64)};
      cuuint64_t strides[2] = {(cuuint64_t)D_MOD * 2, 128};
      cuuint32_t box[3] = {64, 64, 8};
      cuuint32_t es[3] = {1, 1, 1};
      enc(&tm_x, CU_TENSOR_MAP_DATA_TYPE_BFLOAT16, 3, const_cast<void*>(xp), dims, strides, box, es,
          CU_TENSOR_MAP_INTERLEAVE_NONE, CU_TENSOR_MAP_SWIZZLE_128B, CU_TENSOR_MAP_L2_PROMOTION_L2_128B, CU_TENSOR_MAP_FLOAT_OOB_FILL_NONE);
    }
    {
      cuuint64_t dims[2] = {(cuuint64_t)F_HID, (cuuint64_t)D_MOD};
      cuuint64_t strides[1] = {(cuuint64_t)F_HID * 2};
      cuuint32_t box[2] = {64, 32};
      cuuint32_t es[2] = {1, 1};
      enc(&tm_w1, CU_TENSOR_MAP_DATA_TYPE_BFLOAT16, 2, const_cast<void*>(w1), dims, strides, box, es,
          CU_TENSOR_MAP_INTERLEAVE_NONE, CU_TENSOR_MAP_SWIZZLE_128B, CU_TENSOR_MAP_L2_PROMOTION_L2_128B, CU_TENSOR_MAP_FLOAT_OOB_FILL_NONE);
    }
    {
      cuuint64_t dims[2] = {(cuuint64_t)D_MOD, (cuuint64_t)F_HID};
      cuuint64_t strides[1] = {(cuuint64_t)D_MOD * 2};
      cuuint32_t box[2] = {64, 112};
      cuuint32_t es[2] = {1, 1};
      enc(&tm_w2, CU_TENSOR_MAP_DATA_TYPE_BFLOAT16, 2, const_cast<void*>(w2), dims, strides, box, es,
          CU_TENSOR_MAP_INTERLEAVE_NONE, CU_TENSOR_MAP_SWIZZLE_128B, CU_TENSOR_MAP_L2_PROMOTION_L2_128B, CU_TENSOR_MAP_FLOAT_OOB_FILL_NONE);
    }
    cudaFuncSetAttribute(fused_mlp_kernel, cudaFuncAttributeMaxDynamicSharedMemorySize, SMEM_TOTAL);
    cached_w1 = w1; cached_w2 = w2; cached_x = xp;
  }
  fused_mlp_kernel<<<NMB * NSPLIT, NTHREADS, SMEM_TOTAL>>>(tm_x, tm_w1, tm_w2,
      (const __nv_bfloat16*)d_in[2], (const __nv_bfloat16*)d_in[4], (__nv_bfloat16*)d_out);
}
```

```cpp
#include <cuda_runtime.h>
#include <cuda_bf16.h>
#include <cuda.h>
#include <stdint.h>

namespace {

constexpr int S_TOK = 2048, D_MOD = 512, F_HID = 1792;
constexpr int BM = 128, NSPLIT = 8, BF = F_HID / NSPLIT;
constexpr int BN2 = D_MOD / NSPLIT;
constexpr int NMB = S_TOK / BM;
constexpr int SLOT_BYTES = 16384;
constexpr int W1_BYTES = 16384;
constexpr int W2_BYTES = 14336;
constexpr int Y_BYTES = BM * D_MOD * 2;
constexpr int NRING = 6;
constexpr int NLOAD = 32;
constexpr int OFF_RING = Y_BYTES;
__host__ __device__ constexpr int yslot_off(int s) { return (s >> 1) * 65536 + (s & 1) * 16384; }
__host__ __device__ constexpr int uslot_off(int s) { return (s >> 1) * 65536 + 32768 + (s & 1) * 16384; }
constexpr int DSLOT_BYTES = 16384;
constexpr int OFF_BAR = OFF_RING + NRING * SLOT_BYTES;
constexpr int OFF_MEAN = OFF_BAR + 640;
constexpr int OFF_B1 = OFF_MEAN + 512;
constexpr int OFF_B2 = OFF_B1 + 1024;
constexpr int SMEM_TOTAL = OFF_B2 + 256;
constexpr int NTHREADS = 384;
static_assert(SMEM_TOTAL <= 232448, "smem");

__device__ uint4 g_part[(size_t)NMB * NSPLIT * 3 * 1024];
__device__ unsigned int g_epoch[NMB * NSPLIT];

#define TS_DECL
#define TS_FLUSH do {} while (0)
#define TS(role, idx) do {} while (0)
#define TSC(idx) do {} while (0)

__device__ __forceinline__ uint32_t smem_u32(const void* p) { return (uint32_t)__cvta_generic_to_shared(p); }
__device__ __forceinline__ uint32_t mapa(uint32_t a, uint32_t r) {
  uint32_t d; asm volatile("mapa.shared::cluster.u32 %0, %1, %2;" : "=r"(d) : "r"(a), "r"(r)); return d;
}
__device__ __forceinline__ void mbar_init(uint32_t bar, uint32_t cnt) {
  asm volatile("mbarrier.init.shared::cta.b64 [%0], %1;" :: "r"(bar), "r"(cnt) : "memory");
}
__device__ __forceinline__ void mbar_expect_tx(uint32_t bar, uint32_t bytes) {
  asm volatile("mbarrier.arrive.expect_tx.shared::cta.b64 _, [%0], %1;" :: "r"(bar), "r"(bytes) : "memory");
}
__device__ __forceinline__ void mbar_arrive(uint32_t bar) {
  asm volatile("mbarrier.arrive.shared::cta.b64 _, [%0];" :: "r"(bar) : "memory");
}
__device__ __forceinline__ void mbar_arrive_remote(uint32_t rbar) {
  asm volatile("mbarrier.arrive.release.cluster.shared::cluster.b64 _, [%0];" :: "r"(rbar) : "memory");
}
__device__ __forceinline__ void mbar_wait(uint32_t bar, uint32_t parity) {
  uint32_t done = 0; uint32_t it = 0;
  while (true) {
    asm volatile("{\n.reg .pred p;\nmbarrier.try_wait.parity.shared::cta.b64 p, [%1], %2;\nselp.u32 %0, 1, 0, p;\n}"
                 : "=r"(done) : "r"(bar), "r"(parity) : "memory");
    if (done) break;
    if (++it > (1u << 22)) asm volatile("trap;");
  }
}
__device__ __forceinline__ void mbar_wait_cluster(uint32_t bar, uint32_t parity) {
  uint32_t done = 0; uint32_t it = 0;
  while (true) {
    asm volatile("{\n.reg .pred p;\nmbarrier.try_wait.parity.acquire.cluster.shared::cta.b64 p, [%1], %2;\nselp.u32 %0, 1, 0, p;\n}"
                 : "=r"(done) : "r"(bar), "r"(parity) : "memory");
    if (done) break;
    if (++it > (1u << 22)) asm volatile("trap;");
  }
}
__device__ __forceinline__ void tma_load_3d(uint32_t dst, const CUtensorMap* tm, int c0, int c1, int c2, uint32_t bar) {
  asm volatile("cp.async.bulk.tensor.3d.shared::cluster.global.mbarrier::complete_tx::bytes [%0], [%1, {%3, %4, %5}], [%2];"
               :: "r"(dst), "l"(tm), "r"(bar), "r"(c0), "r"(c1), "r"(c2) : "memory");
}
__device__ __forceinline__ void tma_load_2d(uint32_t dst, const CUtensorMap* tm, int c0, int c1, uint32_t bar) {
  asm volatile("cp.async.bulk.tensor.2d.shared::cluster.global.mbarrier::complete_tx::bytes [%0], [%1, {%3, %4}], [%2];"
               :: "r"(dst), "l"(tm), "r"(bar), "r"(c0), "r"(c1) : "memory");
}
__device__ __forceinline__ void tma_prefetch_2d(const CUtensorMap* tm, int c0, int c1) {
  asm volatile("cp.async.bulk.prefetch.tensor.2d.L2.global.tile [%0, {%1, %2}];" :: "l"(tm), "r"(c0), "r"(c1) : "memory");
}
__device__ __forceinline__ void fence_async_smem() { asm volatile("fence.proxy.async.shared::cta;" ::: "memory"); }
__device__ __forceinline__ void wg_bar(int wg) {
  if (wg == 0) asm volatile("bar.sync 1, 128;" ::: "memory"); else asm volatile("bar.sync 2, 128;" ::: "memory");
}
__device__ __forceinline__ void wg_fence() { asm volatile("wgmma.fence.sync.aligned;" ::: "memory"); }
__device__ __forceinline__ void wg_commit() { asm volatile("wgmma.commit_group.sync.aligned;" ::: "memory"); }
template <int N> __device__ __forceinline__ void wg_wait() { asm volatile("wgmma.wait_group.sync.aligned %0;" :: "n"(N) : "memory"); }
template <int N> __device__ __forceinline__ void reg_fence(float (&d)[N]) {
#pragma unroll
  for (int i = 0; i < N; i++) asm volatile("" : "+f"(d[i]) :: "memory");
}
__device__ __forceinline__ uint64_t make_desc(uint32_t addr, uint32_t lbo, uint32_t sbo, uint32_t lt) {
  return (uint64_t)((addr & 0x3FFFF) >> 4) | ((uint64_t)(lbo >> 4) << 16) | ((uint64_t)(sbo >> 4) << 32) | ((uint64_t)lt << 62);
}
__device__ __forceinline__ uint32_t pack_bf16(float lo, float hi) {
  uint32_t r; asm("cvt.rn.bf16x2.f32 %0, %1, %2;" : "=r"(r) : "f"(hi), "f"(lo)); return r;
}
__device__ __forceinline__ float bf_lo(uint32_t v) { return __uint_as_float(v << 16); }
__device__ __forceinline__ float bf_hi(uint32_t v) { return __uint_as_float(v & 0xffff0000u); }
__device__ __forceinline__ float bf16r(float v) { return __bfloat162float(__float2bfloat16_rn(v)); }
__device__ __forceinline__ uint32_t hadd2_bf(uint32_t a, uint32_t b) {
  uint32_t r; asm("add.rn.bf16x2 %0, %1, %2;" : "=r"(r) : "r"(a), "r"(b)); return r;
}
__device__ __forceinline__ uint32_t hsub2_bf(uint32_t a, uint32_t b) {
  uint32_t r; asm("sub.rn.bf16x2 %0, %1, %2;" : "=r"(r) : "r"(a), "r"(b)); return r;
}
__device__ __forceinline__ float gelu_tanh(float u) {
  float inner = u * fmaf(0.035677408136300125f, u * u, 0.7978845608028654f);
  float th; asm("tanh.approx.f32 %0, %1;" : "=f"(th) : "f"(inner));
  float hu = 0.5f * u;
  return fmaf(hu, th, hu);
}
__device__ __forceinline__ void mma16816(float (&c)[4], uint32_t a0, uint32_t a1, uint32_t a2, uint32_t a3, uint32_t b0, uint32_t b1) {
  asm volatile("mma.sync.aligned.m16n8k16.row.col.f32.bf16.bf16.f32 {%0,%1,%2,%3}, {%4,%5,%6,%7}, {%8,%9}, {%0,%1,%2,%3};"
               : "+f"(c[0]), "+f"(c[1]), "+f"(c[2]), "+f"(c[3]) : "r"(a0), "r"(a1), "r"(a2), "r"(a3), "r"(b0), "r"(b1));
}

__device__ __forceinline__ void wgmma_ss_n224(float (&d)[112], uint64_t descA, uint64_t descB, int scaleD) {
  asm volatile("{\n.reg .pred p;\nsetp.ne.b32 p, %114, 0;\n"
    "wgmma.mma_async.sync.aligned.m64n224k16.f32.bf16.bf16 {%0, %1, %2, %3, %4, %5, %6, %7, %8, %9, %10, %11, %12, %13, %14, %15, %16, %17, %18, %19, %20, %21, %22, %23, %24, %25, %26, %27, %28, %29, %30, %31, %32, %33, %34, %35, %36, %37, %38, %39, %40, %41, %42, %43, %44, %45, %46, %47, %48, %49, %50, %51, %52, %53, %54, %55, %56, %57, %58, %59, %60, %61, %62, %63, %64, %65, %66, %67, %68, %69, %70, %71, %72, %73, %74, %75, %76, %77, %78, %79, %80, %81, %82, %83, %84, %85, %86, %87, %88, %89, %90, %91, %92, %93, %94, %95, %96, %97, %98, %99, %100, %101, %102, %103, %104, %105, %106, %107, %108, %109, %110, %111}, %112, %113, p, 1, 1, 0, 1;\n}\n"
    : "+f"(d[0]), "+f"(d[1]), "+f"(d[2]), "+f"(d[3]), "+f"(d[4]), "+f"(d[5]), "+f"(d[6]), "+f"(d[7]), "+f"(d[8]), "+f"(d[9]), "+f"(d[10]), "+f"(d[11]), "+f"(d[12]), "+f"(d[13]), "+f"(d[14]), "+f"(d[15]), "+f"(d[16]), "+f"(d[17]), "+f"(d[18]), "+f"(d[19]), "+f"(d[20]), "+f"(d[21]), "+f"(d[22]), "+f"(d[23]), "+f"(d[24]), "+f"(d[25]), "+f"(d[26]), "+f"(d[27]), "+f"(d[28]), "+f"(d[29]), "+f"(d[30]), "+f"(d[31]), "+f"(d[32]), "+f"(d[33]), "+f"(d[34]), "+f"(d[35]), "+f"(d[36]), "+f"(d[37]), "+f"(d[38]), "+f"(d[39]), "+f"(d[40]), "+f"(d[41]), "+f"(d[42]), "+f"(d[43]), "+f"(d[44]), "+f"(d[45]), "+f"(d[46]), "+f"(d[47]), "+f"(d[48]), "+f"(d[49]), "+f"(d[50]), "+f"(d[51]), "+f"(d[52]), "+f"(d[53]), "+f"(d[54]), "+f"(d[55]), "+f"(d[56]), "+f"(d[57]), "+f"(d[58]), "+f"(d[59]), "+f"(d[60]), "+f"(d[61]), "+f"(d[62]), "+f"(d[63]), "+f"(d[64]), "+f"(d[65]), "+f"(d[66]), "+f"(d[67]), "+f"(d[68]), "+f"(d[69]), "+f"(d[70]), "+f"(d[71]), "+f"(d[72]), "+f"(d[73]), "+f"(d[74]), "+f"(d[75]), "+f"(d[76]), "+f"(d[77]), "+f"(d[78]), "+f"(d[79]), "+f"(d[80]), "+f"(d[81]), "+f"(d[82]), "+f"(d[83]), "+f"(d[84]), "+f"(d[85]), "+f"(d[86]), "+f"(d[87]), "+f"(d[88]), "+f"(d[89]), "+f"(d[90]), "+f"(d[91]), "+f"(d[92]), "+f"(d[93]), "+f"(d[94]), "+f"(d[95]), "+f"(d[96]), "+f"(d[97]), "+f"(d[98]), "+f"(d[99]), "+f"(d[100]), "+f"(d[101]), "+f"(d[102]), "+f"(d[103]), "+f"(d[104]), "+f"(d[105]), "+f"(d[106]), "+f"(d[107]), "+f"(d[108]), "+f"(d[109]), "+f"(d[110]), "+f"(d[111])
    : "l"(descA), "l"(descB), "r"(scaleD));
}

__device__ __forceinline__ void wgmma_rs_n64(float (&d)[32], const uint32_t (&a)[4], uint64_t descB, int scaleD) {
  asm volatile("{\n.reg .pred p;\nsetp.ne.b32 p, %37, 0;\n"
    "wgmma.mma_async.sync.aligned.m64n64k16.f32.bf16.bf16 {%0, %1, %2, %3, %4, %5, %6, %7, %8, %9, %10, %11, %12, %13, %14, %15, %16, %17, %18, %19, %20, %21, %22, %23, %24, %25, %26, %27, %28, %29, %30, %31}, {%32, %33, %34, %35}, %36, p, 1, 1, 1;\n}\n"
    : "+f"(d[0]), "+f"(d[1]), "+f"(d[2]), "+f"(d[3]), "+f"(d[4]), "+f"(d[5]), "+f"(d[6]), "+f"(d[7]), "+f"(d[8]), "+f"(d[9]), "+f"(d[10]), "+f"(d[11]), "+f"(d[12]), "+f"(d[13]), "+f"(d[14]), "+f"(d[15]), "+f"(d[16]), "+f"(d[17]), "+f"(d[18]), "+f"(d[19]), "+f"(d[20]), "+f"(d[21]), "+f"(d[22]), "+f"(d[23]), "+f"(d[24]), "+f"(d[25]), "+f"(d[26]), "+f"(d[27]), "+f"(d[28]), "+f"(d[29]), "+f"(d[30]), "+f"(d[31])
    : "r"(a[0]), "r"(a[1]), "r"(a[2]), "r"(a[3]), "l"(descB), "r"(scaleD));
}

__device__ __forceinline__ void wgmma_rs_n224(float (&d)[112], const uint32_t (&a)[4], uint64_t descB, int scaleD) {
  asm volatile("{\n.reg .pred p;\nsetp.ne.b32 p, %117, 0;\n"
    "wgmma.mma_async.sync.aligned.m64n224k16.f32.bf16.bf16 {%0, %1, %2, %3, %4, %5, %6, %7, %8, %9, %10, %11, %12, %13, %14, %15, %16, %17, %18, %19, %20, %21, %22, %23, %24, %25, %26, %27, %28, %29, %30, %31, %32, %33, %34, %35, %36, %37, %38, %39, %40, %41, %42, %43, %44, %45, %46, %47, %48, %49, %50, %51, %52, %53, %54, %55, %56, %57, %58, %59, %60, %61, %62, %63, %64, %65, %66, %67, %68, %69, %70, %71, %72, %73, %74, %75, %76, %77, %78, %79, %80, %81, %82, %83, %84, %85, %86, %87, %88, %89, %90, %91, %92, %93, %94, %95, %96, %97, %98, %99, %100, %101, %102, %103, %104, %105, %106, %107, %108, %109, %110, %111}, {%112, %113, %114, %115}, %116, p, 1, 1, 1;\n}\n"
    : "+f"(d[0]), "+f"(d[1]), "+f"(d[2]), "+f"(d[3]), "+f"(d[4]), "+f"(d[5]), "+f"(d[6]), "+f"(d[7]), "+f"(d[8]), "+f"(d[9]), "+f"(d[10]), "+f"(d[11]), "+f"(d[12]), "+f"(d[13]), "+f"(d[14]), "+f"(d[15]), "+f"(d[16]), "+f"(d[17]), "+f"(d[18]), "+f"(d[19]), "+f"(d[20]), "+f"(d[21]), "+f"(d[22]), "+f"(d[23]), "+f"(d[24]), "+f"(d[25]), "+f"(d[26]), "+f"(d[27]), "+f"(d[28]), "+f"(d[29]), "+f"(d[30]), "+f"(d[31]), "+f"(d[32]), "+f"(d[33]), "+f"(d[34]), "+f"(d[35]), "+f"(d[36]), "+f"(d[37]), "+f"(d[38]), "+f"(d[39]), "+f"(d[40]), "+f"(d[41]), "+f"(d[42]), "+f"(d[43]), "+f"(d[44]), "+f"(d[45]), "+f"(d[46]), "+f"(d[47]), "+f"(d[48]), "+f"(d[49]), "+f"(d[50]), "+f"(d[51]), "+f"(d[52]), "+f"(d[53]), "+f"(d[54]), "+f"(d[55]), "+f"(d[56]), "+f"(d[57]), "+f"(d[58]), "+f"(d[59]), "+f"(d[60]), "+f"(d[61]), "+f"(d[62]), "+f"(d[63]), "+f"(d[64]), "+f"(d[65]), "+f"(d[66]), "+f"(d[67]), "+f"(d[68]), "+f"(d[69]), "+f"(d[70]), "+f"(d[71]), "+f"(d[72]), "+f"(d[73]), "+f"(d[74]), "+f"(d[75]), "+f"(d[76]), "+f"(d[77]), "+f"(d[78]), "+f"(d[79]), "+f"(d[80]), "+f"(d[81]), "+f"(d[82]), "+f"(d[83]), "+f"(d[84]), "+f"(d[85]), "+f"(d[86]), "+f"(d[87]), "+f"(d[88]), "+f"(d[89]), "+f"(d[90]), "+f"(d[91]), "+f"(d[92]), "+f"(d[93]), "+f"(d[94]), "+f"(d[95]), "+f"(d[96]), "+f"(d[97]), "+f"(d[98]), "+f"(d[99]), "+f"(d[100]), "+f"(d[101]), "+f"(d[102]), "+f"(d[103]), "+f"(d[104]), "+f"(d[105]), "+f"(d[106]), "+f"(d[107]), "+f"(d[108]), "+f"(d[109]), "+f"(d[110]), "+f"(d[111])
    : "r"(a[0]), "r"(a[1]), "r"(a[2]), "r"(a[3]), "l"(descB), "r"(scaleD));
}

__host__ __device__ constexpr int step_kind(int i) { return (i == 0 || i == 1 || i == 3 || i == 6) ? 0 : (i == 7 ? 2 : 1); }
__host__ __device__ constexpr int step_k(int i) { return i == 0 ? 0 : i == 1 ? 1 : i == 2 ? 0 : i == 3 ? 2 : i == 4 ? 1 : i == 5 ? 2 : 3; }
__device__ __forceinline__ int step_slice(int i, int j) {
  const int kind = step_kind(i), k = step_k(i);
  const int base = (kind == 0) ? (j ^ 1) : j;
  return (k == 3) ? base : ((base + 2 * (k + 1)) & 7);
}

__host__ __device__ constexpr int load_off(int i) {
  return i < 6 ? OFF_RING + i * SLOT_BYTES
       : i < 10 ? yslot_off(i - 6)
       : i < 16 ? OFF_RING + (i - 10) * SLOT_BYTES
       : i < 18 ? yslot_off(i - 14)
       : i < 24 ? OFF_RING + (i - 18) * SLOT_BYTES
       : i < 26 ? yslot_off(i - 22)
       : OFF_RING + (i - 26) * SLOT_BYTES;
}
__host__ __device__ constexpr int load_dep(int i) { return i < 6 ? -1 : (i < 10 ? -2 : (i < 16 ? i - 10 : i - 8)); }

__global__ void __cluster_dims__(2, 1, 1) __launch_bounds__(NTHREADS, 1)
fused_mlp_kernel(const __grid_constant__ CUtensorMap tm_x, const __grid_constant__ CUtensorMap tm_w1, const __grid_constant__ CUtensorMap tm_w2,
                 const __nv_bfloat16* __restrict__ b1, const __nv_bfloat16* __restrict__ b2, __nv_bfloat16* __restrict__ out)
{
  extern __shared__ __align__(1024) unsigned char smem[];
  const uint32_t sbase = smem_u32(smem);
  const uint32_t bar_full = sbase + OFF_BAR;
  const uint32_t bar_cons = sbase + OFF_BAR + 256;
  const uint32_t bar_x = sbase + OFF_BAR + 512;
  const uint32_t bar_dfull = sbase + OFF_BAR + 528;
  const uint32_t bar_peer = sbase + OFF_BAR + 560;
  const uint32_t bar_dack = sbase + OFF_BAR + 576;
  const uint32_t bar_ln = sbase + OFF_BAR + 568;
  const int tid = threadIdx.x, warp = tid >> 5, lane = tid & 31;
  const int mb = blockIdx.x >> 3, j = blockIdx.x & 7;

  TS_DECL
  TSC(0);
  if (warp == 8) {
    if (lane == 0) {
      mbar_init(bar_x, 1); mbar_init(bar_x + 8, 1);
      asm volatile("fence.mbarrier_init.release.cluster;" ::: "memory");
      fence_async_smem();
      mbar_expect_tx(bar_x, 65536);
      tma_load_3d(sbase, &tm_x, 0, mb * BM, 0, bar_x);
      mbar_expect_tx(bar_x + 8, 65536);
      tma_load_3d(sbase + 65536, &tm_x, 0, mb * BM + 64, 0, bar_x + 8);
    }
    mbar_init(bar_full + 8 * lane, 1); mbar_init(bar_cons + 8 * lane, 2);
    if (lane < 4) mbar_init(bar_dfull + 8 * lane, 1);
    if (lane == 4) mbar_init(bar_peer, 2);
    if (lane == 5) mbar_init(bar_ln, 2);
    if (lane == 6) mbar_init(bar_dack, 2);
    if (lane == 7) mbar_init(bar_dack + 8, 2);
    asm volatile("fence.mbarrier_init.release.cluster;" ::: "memory");
    fence_async_smem();
    __syncwarp();
    if (lane < 4) mbar_expect_tx(bar_dfull + 8 * lane, DSLOT_BYTES);
    __syncwarp();
  }
  asm volatile("barrier.cluster.arrive.relaxed.aligned;" ::: "memory");
  TSC(30);
  __syncthreads();
  TSC(31);

  if (warp >= 8) {
    asm volatile("setmaxnreg.dec.sync.aligned.u32 40;");
    if (warp == 8 && lane == 0) {
      for (int i = 0; i < NRING; i++) {
        mbar_expect_tx(bar_full + 8 * i, W1_BYTES);
        for (int a = 0; a < 4; a++)
          tma_load_2d(sbase + OFF_RING + i * SLOT_BYTES + a * 4096, &tm_w1, j * BF + a * 64, i * 32, bar_full + 8 * i);
      }
      TS(2, 1);
      for (int t = 2 * mb; t < 2 * mb + 2; t++) {
        if (t < 16) { if (t >= NRING) for (int a = 0; a < 4; a++) tma_prefetch_2d(&tm_w1, j * BF + a * 64, t * 32); }
        else tma_prefetch_2d(&tm_w2, ((t - 16) >> 1) * 64, j * BF + ((t - 16) & 1) * 112);
      }
#pragma unroll
      for (int i = NRING; i < NLOAD; i++) {
        if (load_dep(i) >= 0) mbar_wait(bar_cons + 8 * load_dep(i), 0); else if (i == NRING) mbar_wait(bar_ln, 0);
        TS(2, i);
        const uint32_t dst = sbase + load_off(i);
        if (i < 16) {
          mbar_expect_tx(bar_full + 8 * i, W1_BYTES);
          for (int a = 0; a < 4; a++) tma_load_2d(dst + a * 4096, &tm_w1, j * BF + a * 64, i * 32, bar_full + 8 * i);
        } else {
          mbar_expect_tx(bar_full + 8 * i, W2_BYTES);
          tma_load_2d(dst, &tm_w2, step_slice((i - 16) >> 1, j) * BN2, j * BF + ((i - 16) & 1) * 112, bar_full + 8 * i);
        }
      }
    }
    __syncwarp();
    asm volatile("barrier.cluster.wait.aligned;" ::: "memory");
    asm volatile("barrier.cluster.arrive.relaxed.aligned;\nbarrier.cluster.wait.aligned;" ::: "memory");
  } else {
    asm volatile("setmaxnreg.inc.sync.aligned.u32 232;");
    TSC(23);
    const int wg = warp >> 2, w4 = warp & 3, t128 = tid & 127;
    const int q = lane & 3, g = lane >> 2;
    uint32_t* b1s = reinterpret_cast<uint32_t*>(smem + OFF_B1 + wg * 512);
    uint32_t* b2s = reinterpret_cast<uint32_t*>(smem + OFF_B2 + wg * 128);
    uint32_t bias_a = 0, bias_b = 0;
    if (t128 < BF / 2) bias_a = reinterpret_cast<const uint32_t*>(b1 + j * BF)[t128];
    if (t128 < BN2 / 2) bias_b = reinterpret_cast<const uint32_t*>(b2 + j * BN2)[t128];
    const uint32_t epoch = g_epoch[blockIdx.x];

    float r0, r1;
    uint32_t xa[16][4];
    TSC(24);
    mbar_wait(bar_x + 8 * wg, 0);
    TSC(25);
    {
      uint32_t xb[16][4];
      float cs[2][4], c0[2][4], c1[2][4];
#pragma unroll
      for (int u = 0; u < 2; u++)
#pragma unroll
        for (int e = 0; e < 4; e++) { cs[u][e] = 0.f; c0[u][e] = 0.f; c1[u][e] = 0.f; }
      const int lrow = w4 * 16 + (lane & 7) + ((lane >> 3) & 1) * 8;
      const uint32_t lbase = sbase + wg * 65536 + lrow * 128;
      const uint32_t ones = 0x3F803F80u;
#pragma unroll
      for (int ks = 0; ks < 32; ks++) {
        uint32_t (&a)[4] = ks < 16 ? xa[ks] : xb[ks - 16];
        const uint32_t addr = lbase + (ks >> 2) * 8192 + (((2 * (ks & 3) + (lane >> 4)) ^ (lane & 7)) << 4);
        asm volatile("ldmatrix.sync.aligned.m8n8.x4.shared.b16 {%0,%1,%2,%3}, [%4];" : "=r"(a[0]), "=r"(a[1]), "=r"(a[2]), "=r"(a[3]) : "r"(addr));
        mma16816(cs[ks & 1], a[0], a[1], a[2], a[3], ones, ones);
        mma16816(c0[ks & 1], a[0], a[1], a[2], a[3], a[0], a[2]);
        mma16816(c1[ks & 1], a[0], a[1], a[2], a[3], a[1], a[3]);
      }
      TSC(27);
      const int dsrc = g * 4 + (g >> 1);
      const float q0 = __shfl_sync(0xffffffffu, (g & 1) ? c0[0][1] + c0[1][1] : c0[0][0] + c0[1][0], dsrc);
      const float q1 = __shfl_sync(0xffffffffu, (g & 1) ? c1[0][3] + c1[1][3] : c1[0][2] + c1[1][2], dsrc);
      const float m0 = (cs[0][0] + cs[1][0]) * (1.0f / D_MOD), m1 = (cs[0][2] + cs[1][2]) * (1.0f / D_MOD);
      const uint32_t mm0 = pack_bf16(m0, m0), mm1 = pack_bf16(m1, m1);
#pragma unroll
      for (int ks = 16; ks < 32; ks++) {
        const uint32_t addr = lbase + (ks >> 2) * 8192 + (((2 * (ks & 3) + (lane >> 4)) ^ (lane & 7)) << 4);
        asm volatile("stmatrix.sync.aligned.m8n8.x4.shared.b16 [%0], {%1,%2,%3,%4};" :: "r"(addr),
                     "r"(hsub2_bf(xb[ks - 16][0], mm0)), "r"(hsub2_bf(xb[ks - 16][1], mm1)),
                     "r"(hsub2_bf(xb[ks - 16][2], mm0)), "r"(hsub2_bf(xb[ks - 16][3], mm1)) : "memory");
      }
#pragma unroll
      for (int ks = 0; ks < 16; ks++) {
        xa[ks][0] = hsub2_bf(xa[ks][0], mm0); xa[ks][1] = hsub2_bf(xa[ks][1], mm1);
        xa[ks][2] = hsub2_bf(xa[ks][2], mm0); xa[ks][3] = hsub2_bf(xa[ks][3], mm1);
      }
      const float v0 = fmaxf(fmaf(-m0, m0, q0 * (1.0f / D_MOD)), 0.f), v1 = fmaxf(fmaf(-m1, m1, q1 * (1.0f / D_MOD)), 0.f);
      r0 = 1.0f / bf16r(sqrtf(bf16r(bf16r(v0) + 1e-5f)));
      r1 = 1.0f / bf16r(sqrtf(bf16r(bf16r(v1) + 1e-5f)));
    }
    if (t128 < BF / 2) b1s[t128] = bias_a;
    if (t128 < BN2 / 2) b2s[t128] = bias_b;
    TSC(1);
    fence_async_smem();
    wg_bar(wg);
    if (t128 == 0) mbar_arrive(bar_ln);
    TSC(2);

    uint32_t h[14][4];
    {
      float acc[112];
#pragma unroll
      for (int kb = 0; kb < 16; kb++) {
        mbar_wait(bar_full + 8 * kb, 0);
        wg_fence();
        const uint32_t abase = sbase + wg * 65536 + (kb >> 1) * 8192 + (kb & 1) * 64;
        const uint32_t bbase = sbase + load_off(kb);
#pragma unroll
        for (int kk = 0; kk < 2; kk++) {
          if (kb < 8) wgmma_rs_n224(acc, xa[2 * kb + kk], make_desc(bbase + kk * 2048, 4096, 1024, 1), (kb | kk) != 0);
          else wgmma_ss_n224(acc, make_desc(abase + kk * 32, 16, 1024, 1), make_desc(bbase + kk * 2048, 4096, 1024, 1), 1);
        }
        wg_commit();
        if (kb > 0) { wg_wait<1>(); if (t128 == 0) mbar_arrive(bar_cons + 8 * (kb - 1)); }
      }
      wg_wait<0>();
      reg_fence(acc);
      asm volatile("barrier.cluster.wait.aligned;" ::: "memory");
      if (t128 == 0) { mbar_arrive(bar_cons + 8 * 15); mbar_arrive_remote(mapa(bar_peer, (j & 1) ^ 1)); }
      TSC(11);

#pragma unroll
      for (int i = 0; i < 28; i++) {
        const uint32_t bb = b1s[i * 4 + q];
        uint32_t p0 = hadd2_bf(pack_bf16(acc[4 * i] * r0, acc[4 * i + 1] * r0), bb);
        uint32_t p1 = hadd2_bf(pack_bf16(acc[4 * i + 2] * r1, acc[4 * i + 3] * r1), bb);
        h[i >> 1][(i & 1) * 2 + 0] = pack_bf16(gelu_tanh(bf_lo(p0)), gelu_tanh(bf_hi(p0)));
        h[i >> 1][(i & 1) * 2 + 1] = pack_bf16(gelu_tanh(bf_lo(p1)), gelu_tanh(bf_hi(p1)));
      }
    }

    const uint32_t par = (epoch + 1) & 1;
    float acc2[2][32];
    float sum[32];
    uint4 pf[3][4];
    const uint32_t peer_base = mapa(sbase + wg * 8192, (j & 1) ^ 1);
    const uint32_t peer_dfull = mapa(bar_dfull, (j & 1) ^ 1);
    uint4* my_base = reinterpret_cast<uint4*>(smem) + wg * 512 + t128;
    const uint4* in_part = &g_part[(size_t)((mb * NSPLIT + j) * 3) * 1024 + wg * 512 + t128];
    auto ld_part = [&](const uint4* p) {
      uint4 v;
      asm volatile("ld.relaxed.gpu.global.v4.u32 {%0, %1, %2, %3}, [%4];" : "=r"(v.x), "=r"(v.y), "=r"(v.z), "=r"(v.w) : "l"(p) : "memory");
      return v;
    };
    auto prefetch = [&](int k) {
#pragma unroll
      for (int c = 0; c < 4; c++) pf[k][c] = ld_part(in_part + k * 1024 + c * 128);
    };
    auto consume = [&](int k) {
#pragma unroll
      for (int c = 0; c < 4; c++) {
        uint4 v = pf[k][c];
        uint32_t it = 0;
        while ((((v.x ^ par) | (v.y ^ par) | (v.z ^ par) | (v.w ^ par)) & 1u) != 0) {
          v = ld_part(in_part + k * 1024 + c * 128);
          if (++it > (1u << 20)) asm volatile("trap;");
        }
        sum[c * 8 + 0] += bf_lo(v.x & ~1u); sum[c * 8 + 1] += bf_hi(v.x);
        sum[c * 8 + 2] += bf_lo(v.y & ~1u); sum[c * 8 + 3] += bf_hi(v.y);
        sum[c * 8 + 4] += bf_lo(v.z & ~1u); sum[c * 8 + 5] += bf_hi(v.z);
        sum[c * 8 + 6] += bf_lo(v.w & ~1u); sum[c * 8 + 7] += bf_hi(v.w);
      }
    };
    auto post_pack = [&](int st, float (&a)[32], uint4 (&v)[4]) {
      const int kind = step_kind(st), k = step_k(st);
      if (kind == 0) {
#pragma unroll
        for (int c = 0; c < 4; c++) {
          v[c].x = pack_bf16(a[c * 8 + 0], a[c * 8 + 1]); v[c].y = pack_bf16(a[c * 8 + 2], a[c * 8 + 3]);
          v[c].z = pack_bf16(a[c * 8 + 4], a[c * 8 + 5]); v[c].w = pack_bf16(a[c * 8 + 6], a[c * 8 + 7]);
        }
      } else {
#pragma unroll
        for (int c = 0; c < 4; c++) {
          const uint4 d = v[c];
          v[c].x = (pack_bf16(a[c * 8 + 0] + bf_lo(d.x), a[c * 8 + 1] + bf_hi(d.x)) & ~1u) | par;
          v[c].y = (pack_bf16(a[c * 8 + 2] + bf_lo(d.y), a[c * 8 + 3] + bf_hi(d.y)) & ~1u) | par;
          v[c].z = (pack_bf16(a[c * 8 + 4] + bf_lo(d.z), a[c * 8 + 5] + bf_hi(d.z)) & ~1u) | par;
          v[c].w = (pack_bf16(a[c * 8 + 6] + bf_lo(d.w), a[c * 8 + 7] + bf_hi(d.w)) & ~1u) | par;
        }
      }
      (void)k;
    };
    auto post_send = [&](int st, uint4 (&v)[4]) {
      const int kind = step_kind(st), k = step_k(st);
      if (kind == 0) {
        if (st == 0) mbar_wait(bar_cons + 8 * 15, 0);
        if (k >= 2) mbar_wait_cluster(bar_dack + 8 * (k - 2), 0);
#pragma unroll
        for (int c = 0; c < 4; c++) my_base[yslot_off(k & 1) / 16 + c * 128] = v[c];
        fence_async_smem();
        wg_bar(wg);
        if (t128 == 0) {
          if (st == 0) mbar_wait_cluster(bar_peer, 0);
          asm volatile("cp.async.bulk.shared::cluster.shared::cta.mbarrier::complete_tx::bytes [%0], [%1], %2, [%3];"
                       :: "r"(peer_base + uslot_off(k)), "r"(sbase + yslot_off(k & 1) + wg * 8192), "r"(8192), "r"(peer_dfull + 8 * k) : "memory");
        }
      } else {
#pragma unroll
        for (int c = 0; c < 4; c++) my_base[uslot_off(k) / 16 + c * 128] = v[c];
        fence_async_smem();
        wg_bar(wg);
        if (t128 == 0) {
          const int dest = (j + 2 * (k + 1)) & 7;
          const uint4* p = &g_part[(size_t)((mb * NSPLIT + dest) * 3 + k) * 1024 + wg * 512];
          asm volatile("cp.async.bulk.global.shared::cta.bulk_group [%0], [%1], %2;"
                       :: "l"(p), "r"(sbase + uslot_off(k) + wg * 8192), "r"(8192) : "memory");
          asm volatile("cp.async.bulk.commit_group;" ::: "memory");
        }
      }
    };
    auto issue = [&](int i) {
      mbar_wait(bar_full + 8 * (16 + 2 * i), 0);
      wg_fence();
#pragma unroll
      for (int ks = 0; ks < 7; ks++) {
        wgmma_rs_n64(acc2[i & 1], h[ks], make_desc(sbase + load_off(16 + 2 * i) + ks * 2048, 16, 1024, 1), ks != 0);
      }
      mbar_wait(bar_full + 8 * (17 + 2 * i), 0);
      wg_fence();
#pragma unroll
      for (int ks = 0; ks < 7; ks++) {
        wgmma_rs_n64(acc2[i & 1], h[7 + ks], make_desc(sbase + load_off(17 + 2 * i) + ks * 2048, 16, 1024, 1), 1);
      }
      wg_commit();
    };
    TSC(12);
    issue(0);
    issue(1);
#pragma unroll
    for (int i = 0; i < 7; i++) {
      uint4 v[4];
      if (step_kind(i) == 1) {
        mbar_wait_cluster(bar_dfull + 8 * step_k(i), 0);
        if (step_k(i) < 2 && t128 == 0) mbar_arrive_remote(mapa(bar_dack + 8 * step_k(i), (j & 1) ^ 1));
#pragma unroll
        for (int c = 0; c < 4; c++) v[c] = my_base[uslot_off(step_k(i)) / 16 + c * 128];
      }
      wg_wait<1>();
      reg_fence(acc2[i & 1]);
      post_pack(i, acc2[i & 1], v);
      if (i <= 3 && t128 == 0) { mbar_arrive(bar_cons + 8 * (16 + 2 * i)); mbar_arrive(bar_cons + 8 * (17 + 2 * i)); }
      if (i + 2 < 8) issue(i + 2);
      TSC(13 + i);
      post_send(i, v);
    }
    prefetch(0); prefetch(1); prefetch(2);
    mbar_wait_cluster(bar_dfull + 8 * 3, 0);
#pragma unroll
    for (int c = 0; c < 4; c++) {
      const uint4 d = my_base[uslot_off(3) / 16 + c * 128];
      sum[c * 8 + 0] = bf_lo(d.x); sum[c * 8 + 1] = bf_hi(d.x); sum[c * 8 + 2] = bf_lo(d.y); sum[c * 8 + 3] = bf_hi(d.y);
      sum[c * 8 + 4] = bf_lo(d.z); sum[c * 8 + 5] = bf_hi(d.z); sum[c * 8 + 6] = bf_lo(d.w); sum[c * 8 + 7] = bf_hi(d.w);
    }
    consume(0);
    consume(1);
    wg_wait<0>();
    reg_fence(acc2[1]);
    TSC(20);
    consume(2);
    TSC(21);
    if (tid == 0) g_epoch[blockIdx.x] = epoch + 1;

    {
      const int row0 = mb * BM + wg * 64 + w4 * 16 + g;
      uint32_t* o0 = reinterpret_cast<uint32_t*>(out + (size_t)row0 * D_MOD + j * BN2) + q;
      uint32_t* o1 = o0 + 8 * D_MOD / 2;
#pragma unroll
      for (int i = 0; i < 8; i++) {
        const uint32_t bb = b2s[i * 4 + q];
        o0[i * 4] = hadd2_bf(pack_bf16(acc2[1][4 * i] + sum[4 * i], acc2[1][4 * i + 1] + sum[4 * i + 1]), bb);
        o1[i * 4] = hadd2_bf(pack_bf16(acc2[1][4 * i + 2] + sum[4 * i + 2], acc2[1][4 * i + 3] + sum[4 * i + 3]), bb);
      }
    }
    if (t128 == 0) asm volatile("cp.async.bulk.wait_group 0;" ::: "memory");
    TSC(26);
    TS_FLUSH;
    asm volatile("barrier.cluster.arrive.relaxed.aligned;\nbarrier.cluster.wait.aligned;" ::: "memory");
  }
}

typedef CUresult (*EncodeFn)(CUtensorMap*, CUtensorMapDataType, cuuint32_t, void*, const cuuint64_t*, const cuuint64_t*,
                             const cuuint32_t*, const cuuint32_t*, CUtensorMapInterleave, CUtensorMapSwizzle,
                             CUtensorMapL2promotion, CUtensorMapFloatOOBfill);

}

extern "C" void kernel_launch(void* const* d_in, const int* in_sizes, int n_in, void* d_out, int out_size) {
  (void)in_sizes; (void)n_in; (void)out_size;
  static CUtensorMap tm_x, tm_w1, tm_w2;
  static const void* cached_w1 = nullptr; static const void* cached_w2 = nullptr; static const void* cached_x = nullptr;
  const void* w1 = d_in[1]; const void* w2 = d_in[3]; const void* xp = d_in[0];
  if (cached_w1 != w1 || cached_w2 != w2 || cached_x != xp) {
    void* fn = nullptr; cudaDriverEntryPointQueryResult st;
    cudaGetDriverEntryPoint("cuTensorMapEncodeTiled", &fn, cudaEnableDefault, &st);
    EncodeFn enc = (EncodeFn)fn;
    {
      cuuint64_t dims[3] = {64, (cuuint64_t)S_TOK, (cuuint64_t)(D_MOD / 64)};
      cuuint64_t strides[2] = {(cuuint64_t)D_MOD * 2, 128};
      cuuint32_t box[3] = {64, 64, 8};
      cuuint32_t es[3] = {1, 1, 1};
      enc(&tm_x, CU_TENSOR_MAP_DATA_TYPE_BFLOAT16, 3, const_cast<void*>(xp), dims, strides, box, es,
          CU_TENSOR_MAP_INTERLEAVE_NONE, CU_TENSOR_MAP_SWIZZLE_128B, CU_TENSOR_MAP_L2_PROMOTION_L2_128B, CU_TENSOR_MAP_FLOAT_OOB_FILL_NONE);
    }
    {
      cuuint64_t dims[2] = {(cuuint64_t)F_HID, (cuuint64_t)D_MOD};
      cuuint64_t strides[1] = {(cuuint64_t)F_HID * 2};
      cuuint32_t box[2] = {64, 32};
      cuuint32_t es[2] = {1, 1};
      enc(&tm_w1, CU_TENSOR_MAP_DATA_TYPE_BFLOAT16, 2, const_cast<void*>(w1), dims, strides, box, es,
          CU_TENSOR_MAP_INTERLEAVE_NONE, CU_TENSOR_MAP_SWIZZLE_128B, CU_TENSOR_MAP_L2_PROMOTION_L2_128B, CU_TENSOR_MAP_FLOAT_OOB_FILL_NONE);
    }
    {
      cuuint64_t dims[2] = {(cuuint64_t)D_MOD, (cuuint64_t)F_HID};
      cuuint64_t strides[1] = {(cuuint64_t)D_MOD * 2};
      cuuint32_t box[2] = {64, 112};
      cuuint32_t es[2] = {1, 1};
      enc(&tm_w2, CU_TENSOR_MAP_DATA_TYPE_BFLOAT16, 2, const_cast<void*>(w2), dims, strides, box, es,
          CU_TENSOR_MAP_INTERLEAVE_NONE, CU_TENSOR_MAP_SWIZZLE_128B, CU_TENSOR_MAP_L2_PROMOTION_L2_128B, CU_TENSOR_MAP_FLOAT_OOB_FILL_NONE);
    }
    cudaFuncSetAttribute(fused_mlp_kernel, cudaFuncAttributeMaxDynamicSharedMemorySize, SMEM_TOTAL);
    cached_w1 = w1; cached_w2 = w2; cached_x = xp;
  }
  fused_mlp_kernel<<<NMB * NSPLIT, NTHREADS, SMEM_TOTAL>>>(tm_x, tm_w1, tm_w2,
      (const __nv_bfloat16*)d_in[2], (const __nv_bfloat16*)d_in[4], (__nv_bfloat16*)d_out);
}
```

```cpp
#include <cuda_runtime.h>
#include <cuda_bf16.h>
#include <cuda.h>
#include <stdint.h>

namespace {

constexpr int S_TOK = 2048, D_MOD = 512, F_HID = 1792;
constexpr int BM = 128, NSPLIT = 8, BF = F_HID / NSPLIT;
constexpr int BN2 = D_MOD / NSPLIT;
constexpr int NMB = S_TOK / BM;
constexpr int SLOT_BYTES = 16384;
constexpr int W1_BYTES = 16384;
constexpr int W2_BYTES = 14336;
constexpr int Y_BYTES = BM * D_MOD * 2;
constexpr int NRING = 6;
constexpr int NLOAD = 32;
constexpr int OFF_RING = Y_BYTES;
__host__ __device__ constexpr int yslot_off(int s) { return (s >> 1) * 65536 + (s & 1) * 16384; }
__host__ __device__ constexpr int uslot_off(int s) { return (s >> 1) * 65536 + 32768 + (s & 1) * 16384; }
constexpr int DSLOT_BYTES = 16384;
constexpr int OFF_BAR = OFF_RING + NRING * SLOT_BYTES;
constexpr int OFF_MEAN = OFF_BAR + 640;
constexpr int OFF_B1 = OFF_MEAN + 512;
constexpr int OFF_B2 = OFF_B1 + 1024;
constexpr int SMEM_TOTAL = OFF_B2 + 256;
constexpr int NTHREADS = 384;
static_assert(SMEM_TOTAL <= 232448, "smem");

__device__ uint4 g_part[(size_t)NMB * NSPLIT * 3 * 1024];
__device__ unsigned int g_epoch[NMB * NSPLIT];

#define TS_DECL
#define TS_FLUSH do {} while (0)
#define TS(role, idx) do {} while (0)
#define TSC(idx) do {} while (0)

__device__ __forceinline__ uint32_t smem_u32(const void* p) { return (uint32_t)__cvta_generic_to_shared(p); }
__device__ __forceinline__ uint32_t mapa(uint32_t a, uint32_t r) {
  uint32_t d; asm volatile("mapa.shared::cluster.u32 %0, %1, %2;" : "=r"(d) : "r"(a), "r"(r)); return d;
}
__device__ __forceinline__ void mbar_init(uint32_t bar, uint32_t cnt) {
  asm volatile("mbarrier.init.shared::cta.b64 [%0], %1;" :: "r"(bar), "r"(cnt) : "memory");
}
__device__ __forceinline__ void mbar_expect_tx(uint32_t bar, uint32_t bytes) {
  asm volatile("mbarrier.arrive.expect_tx.shared::cta.b64 _, [%0], %1;" :: "r"(bar), "r"(bytes) : "memory");
}
__device__ __forceinline__ void mbar_arrive(uint32_t bar) {
  asm volatile("mbarrier.arrive.shared::cta.b64 _, [%0];" :: "r"(bar) : "memory");
}
__device__ __forceinline__ void mbar_arrive_remote(uint32_t rbar) {
  asm volatile("mbarrier.arrive.release.cluster.shared::cluster.b64 _, [%0];" :: "r"(rbar) : "memory");
}
__device__ __forceinline__ void mbar_wait(uint32_t bar, uint32_t parity) {
  uint32_t done = 0; uint32_t it = 0;
  while (true) {
    asm volatile("{\n.reg .pred p;\nmbarrier.try_wait.parity.shared::cta.b64 p, [%1], %2;\nselp.u32 %0, 1, 0, p;\n}"
                 : "=r"(done) : "r"(bar), "r"(parity) : "memory");
    if (done) break;
    if (++it > (1u << 22)) asm volatile("trap;");
  }
}
__device__ __forceinline__ void mbar_wait_cluster(uint32_t bar, uint32_t parity) {
  uint32_t done = 0; uint32_t it = 0;
  while (true) {
    asm volatile("{\n.reg .pred p;\nmbarrier.try_wait.parity.acquire.cluster.shared::cta.b64 p, [%1], %2;\nselp.u32 %0, 1, 0, p;\n}"
                 : "=r"(done) : "r"(bar), "r"(parity) : "memory");
    if (done) break;
    if (++it > (1u << 22)) asm volatile("trap;");
  }
}
__device__ __forceinline__ void tma_load_3d(uint32_t dst, const CUtensorMap* tm, int c0, int c1, int c2, uint32_t bar) {
  asm volatile("cp.async.bulk.tensor.3d.shared::cluster.global.mbarrier::complete_tx::bytes [%0], [%1, {%3, %4, %5}], [%2];"
               :: "r"(dst), "l"(tm), "r"(bar), "r"(c0), "r"(c1), "r"(c2) : "memory");
}
__device__ __forceinline__ void tma_load_2d(uint32_t dst, const CUtensorMap* tm, int c0, int c1, uint32_t bar) {
  asm volatile("cp.async.bulk.tensor.2d.shared::cluster.global.mbarrier::complete_tx::bytes [%0], [%1, {%3, %4}], [%2];"
               :: "r"(dst), "l"(tm), "r"(bar), "r"(c0), "r"(c1) : "memory");
}
__device__ __forceinline__ void tma_prefetch_2d(const CUtensorMap* tm, int c0, int c1) {
  asm volatile("cp.async.bulk.prefetch.tensor.2d.L2.global.tile [%0, {%1, %2}];" :: "l"(tm), "r"(c0), "r"(c1) : "memory");
}
__device__ __forceinline__ void fence_async_smem() { asm volatile("fence.proxy.async.shared::cta;" ::: "memory"); }
__device__ __forceinline__ void wg_bar(int wg) {
  if (wg == 0) asm volatile("bar.sync 1, 128;" ::: "memory"); else asm volatile("bar.sync 2, 128;" ::: "memory");
}
__device__ __forceinline__ void wg_fence() { asm volatile("wgmma.fence.sync.aligned;" ::: "memory"); }
__device__ __forceinline__ void wg_commit() { asm volatile("wgmma.commit_group.sync.aligned;" ::: "memory"); }
template <int N> __device__ __forceinline__ void wg_wait() { asm volatile("wgmma.wait_group.sync.aligned %0;" :: "n"(N) : "memory"); }
template <int N> __device__ __forceinline__ void reg_fence(float (&d)[N]) {
#pragma unroll
  for (int i = 0; i < N; i++) asm volatile("" : "+f"(d[i]) :: "memory");
}
__device__ __forceinline__ uint64_t make_desc(uint32_t addr, uint32_t lbo, uint32_t sbo, uint32_t lt) {
  return (uint64_t)((addr & 0x3FFFF) >> 4) | ((uint64_t)(lbo >> 4) << 16) | ((uint64_t)(sbo >> 4) << 32) | ((uint64_t)lt << 62);
}
__device__ __forceinline__ uint32_t pack_bf16(float lo, float hi) {
  uint32_t r; asm("cvt.rn.bf16x2.f32 %0, %1, %2;" : "=r"(r) : "f"(hi), "f"(lo)); return r;
}
__device__ __forceinline__ float bf_lo(uint32_t v) { return __uint_as_float(v << 16); }
__device__ __forceinline__ float bf_hi(uint32_t v) { return __uint_as_float(v & 0xffff0000u); }
__device__ __forceinline__ float bf16r(float v) { return __bfloat162float(__float2bfloat16_rn(v)); }
__device__ __forceinline__ uint32_t hadd2_bf(uint32_t a, uint32_t b) {
  uint32_t r; asm("add.rn.bf16x2 %0, %1, %2;" : "=r"(r) : "r"(a), "r"(b)); return r;
}
__device__ __forceinline__ uint32_t hsub2_bf(uint32_t a, uint32_t b) {
  uint32_t r; asm("sub.rn.bf16x2 %0, %1, %2;" : "=r"(r) : "r"(a), "r"(b)); return r;
}
__device__ __forceinline__ float gelu_tanh(float u) {
  float inner = u * fmaf(0.035677408136300125f, u * u, 0.7978845608028654f);
  float th; asm("tanh.approx.f32 %0, %1;" : "=f"(th) : "f"(inner));
  float hu = 0.5f * u;
  return fmaf(hu, th, hu);
}
__device__ __forceinline__ void mma16816(float (&c)[4], uint32_t a0, uint32_t a1, uint32_t a2, uint32_t a3, uint32_t b0, uint32_t b1) {
  asm volatile("mma.sync.aligned.m16n8k16.row.col.f32.bf16.bf16.f32 {%0,%1,%2,%3}, {%4,%5,%6,%7}, {%8,%9}, {%0,%1,%2,%3};"
               : "+f"(c[0]), "+f"(c[1]), "+f"(c[2]), "+f"(c[3]) : "r"(a0), "r"(a1), "r"(a2), "r"(a3), "r"(b0), "r"(b1));
}

__device__ __forceinline__ void wgmma_ss_n224(float (&d)[112], uint64_t descA, uint64_t descB, int scaleD) {
  asm volatile("{\n.reg .pred p;\nsetp.ne.b32 p, %114, 0;\n"
    "wgmma.mma_async.sync.aligned.m64n224k16.f32.bf16.bf16 {%0, %1, %2, %3, %4, %5, %6, %7, %8, %9, %10, %11, %12, %13, %14, %15, %16, %17, %18, %19, %20, %21, %22, %23, %24, %25, %26, %27, %28, %29, %30, %31, %32, %33, %34, %35, %36, %37, %38, %39, %40, %41, %42, %43, %44, %45, %46, %47, %48, %49, %50, %51, %52, %53, %54, %55, %56, %57, %58, %59, %60, %61, %62, %63, %64, %65, %66, %67, %68, %69, %70, %71, %72, %73, %74, %75, %76, %77, %78, %79, %80, %81, %82, %83, %84, %85, %86, %87, %88, %89, %90, %91, %92, %93, %94, %95, %96, %97, %98, %99, %100, %101, %102, %103, %104, %105, %106, %107, %108, %109, %110, %111}, %112, %113, p, 1, 1, 0, 1;\n}\n"
    : "+f"(d[0]), "+f"(d[1]), "+f"(d[2]), "+f"(d[3]), "+f"(d[4]), "+f"(d[5]), "+f"(d[6]), "+f"(d[7]), "+f"(d[8]), "+f"(d[9]), "+f"(d[10]), "+f"(d[11]), "+f"(d[12]), "+f"(d[13]), "+f"(d[14]), "+f"(d[15]), "+f"(d[16]), "+f"(d[17]), "+f"(d[18]), "+f"(d[19]), "+f"(d[20]), "+f"(d[21]), "+f"(d[22]), "+f"(d[23]), "+f"(d[24]), "+f"(d[25]), "+f"(d[26]), "+f"(d[27]), "+f"(d[28]), "+f"(d[29]), "+f"(d[30]), "+f"(d[31]), "+f"(d[32]), "+f"(d[33]), "+f"(d[34]), "+f"(d[35]), "+f"(d[36]), "+f"(d[37]), "+f"(d[38]), "+f"(d[39]), "+f"(d[40]), "+f"(d[41]), "+f"(d[42]), "+f"(d[43]), "+f"(d[44]), "+f"(d[45]), "+f"(d[46]), "+f"(d[47]), "+f"(d[48]), "+f"(d[49]), "+f"(d[50]), "+f"(d[51]), "+f"(d[52]), "+f"(d[53]), "+f"(d[54]), "+f"(d[55]), "+f"(d[56]), "+f"(d[57]), "+f"(d[58]), "+f"(d[59]), "+f"(d[60]), "+f"(d[61]), "+f"(d[62]), "+f"(d[63]), "+f"(d[64]), "+f"(d[65]), "+f"(d[66]), "+f"(d[67]), "+f"(d[68]), "+f"(d[69]), "+f"(d[70]), "+f"(d[71]), "+f"(d[72]), "+f"(d[73]), "+f"(d[74]), "+f"(d[75]), "+f"(d[76]), "+f"(d[77]), "+f"(d[78]), "+f"(d[79]), "+f"(d[80]), "+f"(d[81]), "+f"(d[82]), "+f"(d[83]), "+f"(d[84]), "+f"(d[85]), "+f"(d[86]), "+f"(d[87]), "+f"(d[88]), "+f"(d[89]), "+f"(d[90]), "+f"(d[91]), "+f"(d[92]), "+f"(d[93]), "+f"(d[94]), "+f"(d[95]), "+f"(d[96]), "+f"(d[97]), "+f"(d[98]), "+f"(d[99]), "+f"(d[100]), "+f"(d[101]), "+f"(d[102]), "+f"(d[103]), "+f"(d[104]), "+f"(d[105]), "+f"(d[106]), "+f"(d[107]), "+f"(d[108]), "+f"(d[109]), "+f"(d[110]), "+f"(d[111])
    : "l"(descA), "l"(descB), "r"(scaleD));
}

__device__ __forceinline__ void wgmma_rs_n64(float (&d)[32], const uint32_t (&a)[4], uint64_t descB, int scaleD) {
  asm volatile("{\n.reg .pred p;\nsetp.ne.b32 p, %37, 0;\n"
    "wgmma.mma_async.sync.aligned.m64n64k16.f32.bf16.bf16 {%0, %1, %2, %3, %4, %5, %6, %7, %8, %9, %10, %11, %12, %13, %14, %15, %16, %17, %18, %19, %20, %21, %22, %23, %24, %25, %26, %27, %28, %29, %30, %31}, {%32, %33, %34, %35}, %36, p, 1, 1, 1;\n}\n"
    : "+f"(d[0]), "+f"(d[1]), "+f"(d[2]), "+f"(d[3]), "+f"(d[4]), "+f"(d[5]), "+f"(d[6]), "+f"(d[7]), "+f"(d[8]), "+f"(d[9]), "+f"(d[10]), "+f"(d[11]), "+f"(d[12]), "+f"(d[13]), "+f"(d[14]), "+f"(d[15]), "+f"(d[16]), "+f"(d[17]), "+f"(d[18]), "+f"(d[19]), "+f"(d[20]), "+f"(d[21]), "+f"(d[22]), "+f"(d[23]), "+f"(d[24]), "+f"(d[25]), "+f"(d[26]), "+f"(d[27]), "+f"(d[28]), "+f"(d[29]), "+f"(d[30]), "+f"(d[31])
    : "r"(a[0]), "r"(a[1]), "r"(a[2]), "r"(a[3]), "l"(descB), "r"(scaleD));
}

__device__ __forceinline__ void wgmma_rs_n224(float (&d)[112], const uint32_t (&a)[4], uint64_t descB, int scaleD) {
  asm volatile("{\n.reg .pred p;\nsetp.ne.b32 p, %117, 0;\n"
    "wgmma.mma_async.sync.aligned.m64n224k16.f32.bf16.bf16 {%0, %1, %2, %3, %4, %5, %6, %7, %8, %9, %10, %11, %12, %13, %14, %15, %16, %17, %18, %19, %20, %21, %22, %23, %24, %25, %26, %27, %28, %29, %30, %31, %32, %33, %34, %35, %36, %37, %38, %39, %40, %41, %42, %43, %44, %45, %46, %47, %48, %49, %50, %51, %52, %53, %54, %55, %56, %57, %58, %59, %60, %61, %62, %63, %64, %65, %66, %67, %68, %69, %70, %71, %72, %73, %74, %75, %76, %77, %78, %79, %80, %81, %82, %83, %84, %85, %86, %87, %88, %89, %90, %91, %92, %93, %94, %95, %96, %97, %98, %99, %100, %101, %102, %103, %104, %105, %106, %107, %108, %109, %110, %111}, {%112, %113, %114, %115}, %116, p, 1, 1, 1;\n}\n"
    : "+f"(d[0]), "+f"(d[1]), "+f"(d[2]), "+f"(d[3]), "+f"(d[4]), "+f"(d[5]), "+f"(d[6]), "+f"(d[7]), "+f"(d[8]), "+f"(d[9]), "+f"(d[10]), "+f"(d[11]), "+f"(d[12]), "+f"(d[13]), "+f"(d[14]), "+f"(d[15]), "+f"(d[16]), "+f"(d[17]), "+f"(d[18]), "+f"(d[19]), "+f"(d[20]), "+f"(d[21]), "+f"(d[22]), "+f"(d[23]), "+f"(d[24]), "+f"(d[25]), "+f"(d[26]), "+f"(d[27]), "+f"(d[28]), "+f"(d[29]), "+f"(d[30]), "+f"(d[31]), "+f"(d[32]), "+f"(d[33]), "+f"(d[34]), "+f"(d[35]), "+f"(d[36]), "+f"(d[37]), "+f"(d[38]), "+f"(d[39]), "+f"(d[40]), "+f"(d[41]), "+f"(d[42]), "+f"(d[43]), "+f"(d[44]), "+f"(d[45]), "+f"(d[46]), "+f"(d[47]), "+f"(d[48]), "+f"(d[49]), "+f"(d[50]), "+f"(d[51]), "+f"(d[52]), "+f"(d[53]), "+f"(d[54]), "+f"(d[55]), "+f"(d[56]), "+f"(d[57]), "+f"(d[58]), "+f"(d[59]), "+f"(d[60]), "+f"(d[61]), "+f"(d[62]), "+f"(d[63]), "+f"(d[64]), "+f"(d[65]), "+f"(d[66]), "+f"(d[67]), "+f"(d[68]), "+f"(d[69]), "+f"(d[70]), "+f"(d[71]), "+f"(d[72]), "+f"(d[73]), "+f"(d[74]), "+f"(d[75]), "+f"(d[76]), "+f"(d[77]), "+f"(d[78]), "+f"(d[79]), "+f"(d[80]), "+f"(d[81]), "+f"(d[82]), "+f"(d[83]), "+f"(d[84]), "+f"(d[85]), "+f"(d[86]), "+f"(d[87]), "+f"(d[88]), "+f"(d[89]), "+f"(d[90]), "+f"(d[91]), "+f"(d[92]), "+f"(d[93]), "+f"(d[94]), "+f"(d[95]), "+f"(d[96]), "+f"(d[97]), "+f"(d[98]), "+f"(d[99]), "+f"(d[100]), "+f"(d[101]), "+f"(d[102]), "+f"(d[103]), "+f"(d[104]), "+f"(d[105]), "+f"(d[106]), "+f"(d[107]), "+f"(d[108]), "+f"(d[109]), "+f"(d[110]), "+f"(d[111])
    : "r"(a[0]), "r"(a[1]), "r"(a[2]), "r"(a[3]), "l"(descB), "r"(scaleD));
}

__host__ __device__ constexpr int step_kind(int i) { return (i < 3 || i == 6) ? 0 : (i == 7 ? 2 : 1); }
__host__ __device__ constexpr int step_k(int i) { return i < 3 ? i : (i < 6 ? i - 3 : 3); }
__device__ __forceinline__ int step_slice(int i, int j) {
  const int kind = step_kind(i), k = step_k(i);
  const int base = (kind == 0) ? (j ^ 1) : j;
  return (k == 3) ? base : ((base + 2 * (k + 1)) & 7);
}

__host__ __device__ constexpr int load_off(int i) {
  return i < 6 ? OFF_RING + i * SLOT_BYTES
       : i < 10 ? yslot_off(i - 6)
       : i < 16 ? OFF_RING + (i - 10) * SLOT_BYTES
       : i < 18 ? yslot_off(i - 14)
       : i < 24 ? OFF_RING + (i - 18) * SLOT_BYTES
       : i < 26 ? yslot_off(i - 22)
       : OFF_RING + (i - 26) * SLOT_BYTES;
}
__host__ __device__ constexpr int load_dep(int i) { return i < 6 ? -1 : (i < 10 ? -2 : (i < 16 ? i - 10 : i - 8)); }

__global__ void __cluster_dims__(2, 1, 1) __launch_bounds__(NTHREADS, 1)
fused_mlp_kernel(const __grid_constant__ CUtensorMap tm_x, const __grid_constant__ CUtensorMap tm_w1, const __grid_constant__ CUtensorMap tm_w2,
                 const __nv_bfloat16* __restrict__ b1, const __nv_bfloat16* __restrict__ b2, __nv_bfloat16* __restrict__ out)
{
  extern __shared__ __align__(1024) unsigned char smem[];
  const uint32_t sbase = smem_u32(smem);
  const uint32_t bar_full = sbase + OFF_BAR;
  const uint32_t bar_cons = sbase + OFF_BAR + 256;
  const uint32_t bar_x = sbase + OFF_BAR + 592;
  const uint32_t bar_dfull = sbase + OFF_BAR + 528;
  const uint32_t bar_peer = sbase + OFF_BAR + 560;
  const uint32_t bar_dack = sbase + OFF_BAR + 576;
  const uint32_t bar_ln = sbase + OFF_BAR + 568;
  const int tid = threadIdx.x, warp = tid >> 5, lane = tid & 31;
  const int mb = blockIdx.x >> 3, j = blockIdx.x & 7;

  TS_DECL
  TSC(0);
  if (warp == 8) {
    mbar_init(bar_full + 8 * lane, 1); mbar_init(bar_cons + 8 * lane, 2);
    if (lane < 4) mbar_init(bar_dfull + 8 * lane, 1);
    if (lane == 4) mbar_init(bar_peer, 2);
    if (lane == 5) mbar_init(bar_ln, 2);
    if (lane == 6 || lane == 7) mbar_init(bar_dack + 8 * (lane - 6), 1);
    if (lane >= 8 && lane < 12) mbar_init(bar_x + 8 * (lane - 8), 1);
    asm volatile("fence.mbarrier_init.release.cluster;" ::: "memory");
    fence_async_smem();
    __syncwarp();
    if (lane == 0) {
      for (int kq = 0; kq < 4; kq++) {
        mbar_expect_tx(bar_x + 8 * kq, 32768);
        tma_load_3d(sbase + kq * 16384, &tm_x, 0, mb * BM, 2 * kq, bar_x + 8 * kq);
        tma_load_3d(sbase + 65536 + kq * 16384, &tm_x, 0, mb * BM + 64, 2 * kq, bar_x + 8 * kq);
      }
    }
    if (lane >= 4 && lane < 8) mbar_expect_tx(bar_dfull + 8 * (lane - 4), DSLOT_BYTES);
    __syncwarp();
  }
  __syncthreads();

  if (warp >= 8) {
    asm volatile("setmaxnreg.dec.sync.aligned.u32 40;");
    asm volatile("barrier.cluster.arrive.relaxed.aligned;" ::: "memory");
    if (warp == 8 && lane == 0) {
      for (int i = 0; i < NRING; i++) {
        if (i == 2) mbar_wait(bar_x + 8 * 3, 0);
        mbar_expect_tx(bar_full + 8 * i, W1_BYTES);
        for (int a = 0; a < 4; a++)
          tma_load_2d(sbase + OFF_RING + i * SLOT_BYTES + a * 4096, &tm_w1, j * BF + a * 64, i * 32, bar_full + 8 * i);
      }
      TS(2, 1);
      for (int t = 2 * mb; t < 2 * mb + 2; t++) {
        if (t < 16) { if (t >= NRING) for (int a = 0; a < 4; a++) tma_prefetch_2d(&tm_w1, j * BF + a * 64, t * 32); }
        else tma_prefetch_2d(&tm_w2, ((t - 16) >> 1) * 64, j * BF + ((t - 16) & 1) * 112);
      }
#pragma unroll
      for (int i = NRING; i < NLOAD; i++) {
        if (load_dep(i) >= 0) mbar_wait(bar_cons + 8 * load_dep(i), 0); else if (i == NRING) mbar_wait(bar_ln, 0);
        TS(2, i);
        const uint32_t dst = sbase + load_off(i);
        if (i < 16) {
          mbar_expect_tx(bar_full + 8 * i, W1_BYTES);
          for (int a = 0; a < 4; a++) tma_load_2d(dst + a * 4096, &tm_w1, j * BF + a * 64, i * 32, bar_full + 8 * i);
        } else {
          mbar_expect_tx(bar_full + 8 * i, W2_BYTES);
          tma_load_2d(dst, &tm_w2, step_slice((i - 16) >> 1, j) * BN2, j * BF + ((i - 16) & 1) * 112, bar_full + 8 * i);
        }
      }
    }
    __syncwarp();
    asm volatile("barrier.cluster.wait.aligned;" ::: "memory");
    if (warp == 9 && lane == 0) {
      for (int k = 0; k < 2; k++) {
        mbar_wait_cluster(bar_dfull + 8 * k, 0);
        mbar_arrive_remote(mapa(bar_dack + 8 * k, (j & 1) ^ 1));
      }
    }
    __syncwarp();
    asm volatile("barrier.cluster.arrive.relaxed.aligned;\nbarrier.cluster.wait.aligned;" ::: "memory");
  } else {
    asm volatile("setmaxnreg.inc.sync.aligned.u32 232;");
    asm volatile("barrier.cluster.arrive.relaxed.aligned;" ::: "memory");
    TSC(23);
    const int wg = warp >> 2, w4 = warp & 3, t128 = tid & 127;
    const int q = lane & 3, g = lane >> 2;
    uint32_t* b1s = reinterpret_cast<uint32_t*>(smem + OFF_B1 + wg * 512);
    uint32_t* b2s = reinterpret_cast<uint32_t*>(smem + OFF_B2 + wg * 128);
    uint32_t bias_a = 0, bias_b = 0;
    if (t128 < BF / 2) bias_a = reinterpret_cast<const uint32_t*>(b1 + j * BF)[t128];
    if (t128 < BN2 / 2) bias_b = reinterpret_cast<const uint32_t*>(b2 + j * BN2)[t128];
    const uint32_t epoch = g_epoch[blockIdx.x];

    float r0, r1;
    uint32_t xa[16][4];
    TSC(24);
    {
      uint32_t xb[16][4];
      float cs[2][4], c0[2][4], c1[2][4];
#pragma unroll
      for (int u = 0; u < 2; u++)
#pragma unroll
        for (int e = 0; e < 4; e++) { cs[u][e] = 0.f; c0[u][e] = 0.f; c1[u][e] = 0.f; }
      const int lrow = w4 * 16 + (lane & 7) + ((lane >> 3) & 1) * 8;
      const uint32_t lbase = sbase + wg * 65536 + lrow * 128;
      const uint32_t ones = 0x3F803F80u;
#pragma unroll
      for (int ks = 0; ks < 32; ks++) {
        if ((ks & 7) == 0) { mbar_wait(bar_x + 8 * (ks >> 3), 0); if (ks == 0) TSC(25); if (ks == 24) TSC(22); }
        uint32_t (&a)[4] = ks < 16 ? xa[ks] : xb[ks - 16];
        const uint32_t addr = lbase + (ks >> 2) * 8192 + (((2 * (ks & 3) + (lane >> 4)) ^ (lane & 7)) << 4);
        asm volatile("ldmatrix.sync.aligned.m8n8.x4.shared.b16 {%0,%1,%2,%3}, [%4];" : "=r"(a[0]), "=r"(a[1]), "=r"(a[2]), "=r"(a[3]) : "r"(addr));
        mma16816(cs[ks & 1], a[0], a[1], a[2], a[3], ones, ones);
        mma16816(c0[ks & 1], a[0], a[1], a[2], a[3], a[0], a[2]);
        mma16816(c1[ks & 1], a[0], a[1], a[2], a[3], a[1], a[3]);
      }
      TSC(27);
      const int dsrc = g * 4 + (g >> 1);
      const float q0 = __shfl_sync(0xffffffffu, (g & 1) ? c0[0][1] + c0[1][1] : c0[0][0] + c0[1][0], dsrc);
      const float q1 = __shfl_sync(0xffffffffu, (g & 1) ? c1[0][3] + c1[1][3] : c1[0][2] + c1[1][2], dsrc);
      const float m0 = (cs[0][0] + cs[1][0]) * (1.0f / D_MOD), m1 = (cs[0][2] + cs[1][2]) * (1.0f / D_MOD);
      const uint32_t mm0 = pack_bf16(m0, m0), mm1 = pack_bf16(m1, m1);
#pragma unroll
      for (int ks = 16; ks < 32; ks++) {
        const uint32_t addr = lbase + (ks >> 2) * 8192 + (((2 * (ks & 3) + (lane >> 4)) ^ (lane & 7)) << 4);
        asm volatile("stmatrix.sync.aligned.m8n8.x4.shared.b16 [%0], {%1,%2,%3,%4};" :: "r"(addr),
                     "r"(hsub2_bf(xb[ks - 16][0], mm0)), "r"(hsub2_bf(xb[ks - 16][1], mm1)),
                     "r"(hsub2_bf(xb[ks - 16][2], mm0)), "r"(hsub2_bf(xb[ks - 16][3], mm1)) : "memory");
      }
#pragma unroll
      for (int ks = 0; ks < 16; ks++) {
        xa[ks][0] = hsub2_bf(xa[ks][0], mm0); xa[ks][1] = hsub2_bf(xa[ks][1], mm1);
        xa[ks][2] = hsub2_bf(xa[ks][2], mm0); xa[ks][3] = hsub2_bf(xa[ks][3], mm1);
      }
      const float v0 = fmaxf(fmaf(-m0, m0, q0 * (1.0f / D_MOD)), 0.f), v1 = fmaxf(fmaf(-m1, m1, q1 * (1.0f / D_MOD)), 0.f);
      r0 = 1.0f / bf16r(sqrtf(bf16r(bf16r(v0) + 1e-5f)));
      r1 = 1.0f / bf16r(sqrtf(bf16r(bf16r(v1) + 1e-5f)));
    }
    if (t128 < BF / 2) b1s[t128] = bias_a;
    if (t128 < BN2 / 2) b2s[t128] = bias_b;
    TSC(1);
    fence_async_smem();
    wg_bar(wg);
    if (t128 == 0) mbar_arrive(bar_ln);
    TSC(2);

    uint32_t h[14][4];
    {
      float acc[112];
#pragma unroll
      for (int kb = 0; kb < 16; kb++) {
        mbar_wait(bar_full + 8 * kb, 0);
        wg_fence();
        const uint32_t abase = sbase + wg * 65536 + (kb >> 1) * 8192 + (kb & 1) * 64;
        const uint32_t bbase = sbase + load_off(kb);
#pragma unroll
        for (int kk = 0; kk < 2; kk++) {
          if (kb < 8) wgmma_rs_n224(acc, xa[2 * kb + kk], make_desc(bbase + kk * 2048, 4096, 1024, 1), (kb | kk) != 0);
          else wgmma_ss_n224(acc, make_desc(abase + kk * 32, 16, 1024, 1), make_desc(bbase + kk * 2048, 4096, 1024, 1), 1);
        }
        wg_commit();
        if (kb > 0) { wg_wait<1>(); if (t128 == 0) mbar_arrive(bar_cons + 8 * (kb - 1)); }
      }
      wg_wait<0>();
      reg_fence(acc);
      asm volatile("barrier.cluster.wait.aligned;" ::: "memory");
      if (t128 == 0) { mbar_arrive(bar_cons + 8 * 15); mbar_arrive_remote(mapa(bar_peer, (j & 1) ^ 1)); }
      TSC(11);

#pragma unroll
      for (int i = 0; i < 28; i++) {
        const uint32_t bb = b1s[i * 4 + q];
        uint32_t p0 = hadd2_bf(pack_bf16(acc[4 * i] * r0, acc[4 * i + 1] * r0), bb);
        uint32_t p1 = hadd2_bf(pack_bf16(acc[4 * i + 2] * r1, acc[4 * i + 3] * r1), bb);
        h[i >> 1][(i & 1) * 2 + 0] = pack_bf16(gelu_tanh(bf_lo(p0)), gelu_tanh(bf_hi(p0)));
        h[i >> 1][(i & 1) * 2 + 1] = pack_bf16(gelu_tanh(bf_lo(p1)), gelu_tanh(bf_hi(p1)));
      }
    }

    const uint32_t par = (epoch + 1) & 1;
    float acc2[2][32];
    float sum[32];
    uint4 pf[3][4];
    const uint32_t peer_base = mapa(sbase + wg * 8192, (j & 1) ^ 1);
    const uint32_t peer_dfull = mapa(bar_dfull, (j & 1) ^ 1);
    uint4* my_base = reinterpret_cast<uint4*>(smem) + wg * 512 + t128;
    const uint4* in_part = &g_part[(size_t)((mb * NSPLIT + j) * 3) * 1024 + wg * 512 + t128];
    auto ld_part = [&](const uint4* p) {
      uint4 v;
      asm volatile("ld.relaxed.gpu.global.v4.u32 {%0, %1, %2, %3}, [%4];" : "=r"(v.x), "=r"(v.y), "=r"(v.z), "=r"(v.w) : "l"(p) : "memory");
      return v;
    };
    auto prefetch = [&](int k) {
#pragma unroll
      for (int c = 0; c < 4; c++) pf[k][c] = ld_part(in_part + k * 1024 + c * 128);
    };
    auto consume = [&](int k) {
#pragma unroll
      for (int c = 0; c < 4; c++) {
        uint4 v = pf[k][c];
        uint32_t it = 0;
        while ((((v.x ^ par) | (v.y ^ par) | (v.z ^ par) | (v.w ^ par)) & 1u) != 0) {
          v = ld_part(in_part + k * 1024 + c * 128);
          if (++it > (1u << 20)) asm volatile("trap;");
        }
        sum[c * 8 + 0] += bf_lo(v.x & ~1u); sum[c * 8 + 1] += bf_hi(v.x);
        sum[c * 8 + 2] += bf_lo(v.y & ~1u); sum[c * 8 + 3] += bf_hi(v.y);
        sum[c * 8 + 4] += bf_lo(v.z & ~1u); sum[c * 8 + 5] += bf_hi(v.z);
        sum[c * 8 + 6] += bf_lo(v.w & ~1u); sum[c * 8 + 7] += bf_hi(v.w);
      }
    };
    auto post_pack = [&](int st, float (&a)[32], uint4 (&v)[4]) {
      const int kind = step_kind(st), k = step_k(st);
      if (kind == 0) {
#pragma unroll
        for (int c = 0; c < 4; c++) {
          v[c].x = pack_bf16(a[c * 8 + 0], a[c * 8 + 1]); v[c].y = pack_bf16(a[c * 8 + 2], a[c * 8 + 3]);
          v[c].z = pack_bf16(a[c * 8 + 4], a[c * 8 + 5]); v[c].w = pack_bf16(a[c * 8 + 6], a[c * 8 + 7]);
        }
      } else {
#pragma unroll
        for (int c = 0; c < 4; c++) {
          const uint4 d = v[c];
          v[c].x = (pack_bf16(a[c * 8 + 0] + bf_lo(d.x), a[c * 8 + 1] + bf_hi(d.x)) & ~1u) | par;
          v[c].y = (pack_bf16(a[c * 8 + 2] + bf_lo(d.y), a[c * 8 + 3] + bf_hi(d.y)) & ~1u) | par;
          v[c].z = (pack_bf16(a[c * 8 + 4] + bf_lo(d.z), a[c * 8 + 5] + bf_hi(d.z)) & ~1u) | par;
          v[c].w = (pack_bf16(a[c * 8 + 6] + bf_lo(d.w), a[c * 8 + 7] + bf_hi(d.w)) & ~1u) | par;
        }
      }
      (void)k;
    };
    auto post_send = [&](int st, uint4 (&v)[4]) {
      const int kind = step_kind(st), k = step_k(st);
      if (kind == 0) {
        if (st == 0) mbar_wait(bar_cons + 8 * 15, 0);
        if (k >= 2) mbar_wait_cluster(bar_dack + 8 * (k - 2), 0);
#pragma unroll
        for (int c = 0; c < 4; c++) my_base[yslot_off(k & 1) / 16 + c * 128] = v[c];
        fence_async_smem();
        wg_bar(wg);
        if (t128 == 0) {
          if (st == 0) mbar_wait_cluster(bar_peer, 0);
          asm volatile("cp.async.bulk.shared::cluster.shared::cta.mbarrier::complete_tx::bytes [%0], [%1], %2, [%3];"
                       :: "r"(peer_base + uslot_off(k)), "r"(sbase + yslot_off(k & 1) + wg * 8192), "r"(8192), "r"(peer_dfull + 8 * k) : "memory");
        }
      } else {
#pragma unroll
        for (int c = 0; c < 4; c++) my_base[uslot_off(k) / 16 + c * 128] = v[c];
        fence_async_smem();
        wg_bar(wg);
        if (t128 == 0) {
          const int dest = (j + 2 * (k + 1)) & 7;
          const uint4* p = &g_part[(size_t)((mb * NSPLIT + dest) * 3 + k) * 1024 + wg * 512];
          asm volatile("cp.async.bulk.global.shared::cta.bulk_group [%0], [%1], %2;"
                       :: "l"(p), "r"(sbase + uslot_off(k) + wg * 8192), "r"(8192) : "memory");
          asm volatile("cp.async.bulk.commit_group;" ::: "memory");
        }
      }
    };
    auto issue = [&](int i) {
      mbar_wait(bar_full + 8 * (16 + 2 * i), 0);
      wg_fence();
#pragma unroll
      for (int ks = 0; ks < 7; ks++) {
        wgmma_rs_n64(acc2[i & 1], h[ks], make_desc(sbase + load_off(16 + 2 * i) + ks * 2048, 16, 1024, 1), ks != 0);
      }
      mbar_wait(bar_full + 8 * (17 + 2 * i), 0);
      wg_fence();
#pragma unroll
      for (int ks = 0; ks < 7; ks++) {
        wgmma_rs_n64(acc2[i & 1], h[7 + ks], make_desc(sbase + load_off(17 + 2 * i) + ks * 2048, 16, 1024, 1), 1);
      }
      wg_commit();
    };
    TSC(12);
    issue(0);
    issue(1);
#pragma unroll
    for (int i = 0; i < 7; i++) {
      uint4 v[4];
      if (step_kind(i) == 1) {
        mbar_wait_cluster(bar_dfull + 8 * step_k(i), 0);
#pragma unroll
        for (int c = 0; c < 4; c++) v[c] = my_base[uslot_off(step_k(i)) / 16 + c * 128];
      }
      wg_wait<1>();
      reg_fence(acc2[i & 1]);
      post_pack(i, acc2[i & 1], v);
      if (i <= 3 && t128 == 0) { mbar_arrive(bar_cons + 8 * (16 + 2 * i)); mbar_arrive(bar_cons + 8 * (17 + 2 * i)); }
      if (i + 2 < 8) issue(i + 2);
      TSC(13 + i);
      post_send(i, v);
    }
    prefetch(0); prefetch(1); prefetch(2);
    mbar_wait_cluster(bar_dfull + 8 * 3, 0);
#pragma unroll
    for (int c = 0; c < 4; c++) {
      const uint4 d = my_base[uslot_off(3) / 16 + c * 128];
      sum[c * 8 + 0] = bf_lo(d.x); sum[c * 8 + 1] = bf_hi(d.x); sum[c * 8 + 2] = bf_lo(d.y); sum[c * 8 + 3] = bf_hi(d.y);
      sum[c * 8 + 4] = bf_lo(d.z); sum[c * 8 + 5] = bf_hi(d.z); sum[c * 8 + 6] = bf_lo(d.w); sum[c * 8 + 7] = bf_hi(d.w);
    }
    consume(0);
    consume(1);
    wg_wait<0>();
    reg_fence(acc2[1]);
    TSC(20);
    consume(2);
    TSC(21);
    if (tid == 0) g_epoch[blockIdx.x] = epoch + 1;

    {
      const int row0 = mb * BM + wg * 64 + w4 * 16 + g;
      uint32_t* o0 = reinterpret_cast<uint32_t*>(out + (size_t)row0 * D_MOD + j * BN2) + q;
      uint32_t* o1 = o0 + 8 * D_MOD / 2;
#pragma unroll
      for (int i = 0; i < 8; i++) {
        const uint32_t bb = b2s[i * 4 + q];
        o0[i * 4] = hadd2_bf(pack_bf16(acc2[1][4 * i] + sum[4 * i], acc2[1][4 * i + 1] + sum[4 * i + 1]), bb);
        o1[i * 4] = hadd2_bf(pack_bf16(acc2[1][4 * i + 2] + sum[4 * i + 2], acc2[1][4 * i + 3] + sum[4 * i + 3]), bb);
      }
    }
    if (t128 == 0) asm volatile("cp.async.bulk.wait_group 0;" ::: "memory");
    TSC(26);
    TS_FLUSH;
    asm volatile("barrier.cluster.arrive.relaxed.aligned;\nbarrier.cluster.wait.aligned;" ::: "memory");
  }
}

typedef CUresult (*EncodeFn)(CUtensorMap*, CUtensorMapDataType, cuuint32_t, void*, const cuuint64_t*, const cuuint64_t*,
                             const cuuint32_t*, const cuuint32_t*, CUtensorMapInterleave, CUtensorMapSwizzle,
                             CUtensorMapL2promotion, CUtensorMapFloatOOBfill);

}

extern "C" void kernel_launch(void* const* d_in, const int* in_sizes, int n_in, void* d_out, int out_size) {
  (void)in_sizes; (void)n_in; (void)out_size;
  static CUtensorMap tm_x, tm_w1, tm_w2;
  static const void* cached_w1 = nullptr; static const void* cached_w2 = nullptr; static const void* cached_x = nullptr;
  const void* w1 = d_in[1]; const void* w2 = d_in[3]; const void* xp = d_in[0];
  if (cached_w1 != w1 || cached_w2 != w2 || cached_x != xp) {
    void* fn = nullptr; cudaDriverEntryPointQueryResult st;
    cudaGetDriverEntryPoint("cuTensorMapEncodeTiled", &fn, cudaEnableDefault, &st);
    EncodeFn enc = (EncodeFn)fn;
    {
      cuuint64_t dims[3] = {64, (cuuint64_t)S_TOK, (cuuint64_t)(D_MOD / 64)};
      cuuint64_t strides[2] = {(cuuint64_t)D_MOD * 2, 128};
      cuuint32_t box[3] = {64, 64, 2};
      cuuint32_t es[3] = {1, 1, 1};
      enc(&tm_x, CU_TENSOR_MAP_DATA_TYPE_BFLOAT16, 3, const_cast<void*>(xp), dims, strides, box, es,
          CU_TENSOR_MAP_INTERLEAVE_NONE, CU_TENSOR_MAP_SWIZZLE_128B, CU_TENSOR_MAP_L2_PROMOTION_L2_128B, CU_TENSOR_MAP_FLOAT_OOB_FILL_NONE);
    }
    {
      cuuint64_t dims[2] = {(cuuint64_t)F_HID, (cuuint64_t)D_MOD};
      cuuint64_t strides[1] = {(cuuint64_t)F_HID * 2};
      cuuint32_t box[2] = {64, 32};
      cuuint32_t es[2] = {1, 1};
      enc(&tm_w1, CU_TENSOR_MAP_DATA_TYPE_BFLOAT16, 2, const_cast<void*>(w1), dims, strides, box, es,
          CU_TENSOR_MAP_INTERLEAVE_NONE, CU_TENSOR_MAP_SWIZZLE_128B, CU_TENSOR_MAP_L2_PROMOTION_L2_128B, CU_TENSOR_MAP_FLOAT_OOB_FILL_NONE);
    }
    {
      cuuint64_t dims[2] = {(cuuint64_t)D_MOD, (cuuint64_t)F_HID};
      cuuint64_t strides[1] = {(cuuint64_t)D_MOD * 2};
      cuuint32_t box[2] = {64, 112};
      cuuint32_t es[2] = {1, 1};
      enc(&tm_w2, CU_TENSOR_MAP_DATA_TYPE_BFLOAT16, 2, const_cast<void*>(w2), dims, strides, box, es,
          CU_TENSOR_MAP_INTERLEAVE_NONE, CU_TENSOR_MAP_SWIZZLE_128B, CU_TENSOR_MAP_L2_PROMOTION_L2_128B, CU_TENSOR_MAP_FLOAT_OOB_FILL_NONE);
    }
    cudaFuncSetAttribute(fused_mlp_kernel, cudaFuncAttributeMaxDynamicSharedMemorySize, SMEM_TOTAL);
    cached_w1 = w1; cached_w2 = w2; cached_x = xp;
  }
  fused_mlp_kernel<<<NMB * NSPLIT, NTHREADS, SMEM_TOTAL>>>(tm_x, tm_w1, tm_w2,
      (const __nv_bfloat16*)d_in[2], (const __nv_bfloat16*)d_in[4], (__nv_bfloat16*)d_out);
}
```

```cpp
#include <cuda_runtime.h>
#include <cuda_bf16.h>
#include <cuda.h>
#include <stdint.h>

namespace {

constexpr int S_TOK = 2048, D_MOD = 512, F_HID = 1792;
constexpr int BM = 128, NSPLIT = 8, BF = F_HID / NSPLIT;
constexpr int BN2 = D_MOD / NSPLIT;
constexpr int NMB = S_TOK / BM;
constexpr int SLOT_BYTES = 16384;
constexpr int W1_BYTES = 16384;
constexpr int W2_BYTES = 14336;
constexpr int Y_BYTES = BM * D_MOD * 2;
constexpr int NRING = 6;
constexpr int NLOAD = 32;
constexpr int OFF_RING = Y_BYTES;
__host__ __device__ constexpr int yslot_off(int s) { return (s >> 1) * 65536 + (s & 1) * 16384; }
__host__ __device__ constexpr int uslot_off(int s) { return (s >> 1) * 65536 + 32768 + (s & 1) * 16384; }
constexpr int DSLOT_BYTES = 16384;
constexpr int OFF_BAR = OFF_RING + NRING * SLOT_BYTES;
constexpr int OFF_MEAN = OFF_BAR + 640;
constexpr int OFF_B1 = OFF_MEAN + 512;
constexpr int OFF_B2 = OFF_B1 + 1024;
constexpr int SMEM_TOTAL = OFF_B2 + 256;
constexpr int NTHREADS = 384;
static_assert(SMEM_TOTAL <= 232448, "smem");

__device__ uint4 g_part[(size_t)NMB * NSPLIT * 3 * 1024];
__device__ unsigned int g_epoch[NMB * NSPLIT];

#define TS_DECL
#define TS_FLUSH do {} while (0)
#define TS(role, idx) do {} while (0)
#define TSC(idx) do {} while (0)

__device__ __forceinline__ uint32_t smem_u32(const void* p) { return (uint32_t)__cvta_generic_to_shared(p); }
__device__ __forceinline__ uint32_t mapa(uint32_t a, uint32_t r) {
  uint32_t d; asm volatile("mapa.shared::cluster.u32 %0, %1, %2;" : "=r"(d) : "r"(a), "r"(r)); return d;
}
__device__ __forceinline__ void mbar_init(uint32_t bar, uint32_t cnt) {
  asm volatile("mbarrier.init.shared::cta.b64 [%0], %1;" :: "r"(bar), "r"(cnt) : "memory");
}
__device__ __forceinline__ void mbar_expect_tx(uint32_t bar, uint32_t bytes) {
  asm volatile("mbarrier.arrive.expect_tx.shared::cta.b64 _, [%0], %1;" :: "r"(bar), "r"(bytes) : "memory");
}
__device__ __forceinline__ void mbar_arrive(uint32_t bar) {
  asm volatile("mbarrier.arrive.shared::cta.b64 _, [%0];" :: "r"(bar) : "memory");
}
__device__ __forceinline__ void mbar_arrive_remote(uint32_t rbar) {
  asm volatile("mbarrier.arrive.release.cluster.shared::cluster.b64 _, [%0];" :: "r"(rbar) : "memory");
}
__device__ __forceinline__ void mbar_wait(uint32_t bar, uint32_t parity) {
  uint32_t done = 0; uint32_t it = 0;
  while (true) {
    asm volatile("{\n.reg .pred p;\nmbarrier.try_wait.parity.shared::cta.b64 p, [%1], %2;\nselp.u32 %0, 1, 0, p;\n}"
                 : "=r"(done) : "r"(bar), "r"(parity) : "memory");
    if (done) break;
    if (++it > (1u << 22)) asm volatile("trap;");
  }
}
__device__ __forceinline__ void mbar_wait_cluster(uint32_t bar, uint32_t parity) {
  uint32_t done = 0; uint32_t it = 0;
  while (true) {
    asm volatile("{\n.reg .pred p;\nmbarrier.try_wait.parity.acquire.cluster.shared::cta.b64 p, [%1], %2;\nselp.u32 %0, 1, 0, p;\n}"
                 : "=r"(done) : "r"(bar), "r"(parity) : "memory");
    if (done) break;
    if (++it > (1u << 22)) asm volatile("trap;");
  }
}
__device__ __forceinline__ void tma_load_3d(uint32_t dst, const CUtensorMap* tm, int c0, int c1, int c2, uint32_t bar) {
  asm volatile("cp.async.bulk.tensor.3d.shared::cluster.global.mbarrier::complete_tx::bytes [%0], [%1, {%3, %4, %5}], [%2];"
               :: "r"(dst), "l"(tm), "r"(bar), "r"(c0), "r"(c1), "r"(c2) : "memory");
}
__device__ __forceinline__ void tma_load_2d(uint32_t dst, const CUtensorMap* tm, int c0, int c1, uint32_t bar) {
  asm volatile("cp.async.bulk.tensor.2d.shared::cluster.global.mbarrier::complete_tx::bytes [%0], [%1, {%3, %4}], [%2];"
               :: "r"(dst), "l"(tm), "r"(bar), "r"(c0), "r"(c1) : "memory");
}
__device__ __forceinline__ void tma_prefetch_2d(const CUtensorMap* tm, int c0, int c1) {
  asm volatile("cp.async.bulk.prefetch.tensor.2d.L2.global.tile [%0, {%1, %2}];" :: "l"(tm), "r"(c0), "r"(c1) : "memory");
}
__device__ __forceinline__ void fence_async_smem() { asm volatile("fence.proxy.async.shared::cta;" ::: "memory"); }
__device__ __forceinline__ void wg_bar(int wg) {
  if (wg == 0) asm volatile("bar.sync 1, 128;" ::: "memory"); else asm volatile("bar.sync 2, 128;" ::: "memory");
}
__device__ __forceinline__ void wg_fence() { asm volatile("wgmma.fence.sync.aligned;" ::: "memory"); }
__device__ __forceinline__ void wg_commit() { asm volatile("wgmma.commit_group.sync.aligned;" ::: "memory"); }
template <int N> __device__ __forceinline__ void wg_wait() { asm volatile("wgmma.wait_group.sync.aligned %0;" :: "n"(N) : "memory"); }
template <int N> __device__ __forceinline__ void reg_fence(float (&d)[N]) {
#pragma unroll
  for (int i = 0; i < N; i++) asm volatile("" : "+f"(d[i]) :: "memory");
}
__device__ __forceinline__ uint64_t make_desc(uint32_t addr, uint32_t lbo, uint32_t sbo, uint32_t lt) {
  return (uint64_t)((addr & 0x3FFFF) >> 4) | ((uint64_t)(lbo >> 4) << 16) | ((uint64_t)(sbo >> 4) << 32) | ((uint64_t)lt << 62);
}
__device__ __forceinline__ uint32_t pack_bf16(float lo, float hi) {
  uint32_t r; asm("cvt.rn.bf16x2.f32 %0, %1, %2;" : "=r"(r) : "f"(hi), "f"(lo)); return r;
}
__device__ __forceinline__ float bf_lo(uint32_t v) { return __uint_as_float(v << 16); }
__device__ __forceinline__ float bf_hi(uint32_t v) { return __uint_as_float(v & 0xffff0000u); }
__device__ __forceinline__ float bf16r(float v) { return __bfloat162float(__float2bfloat16_rn(v)); }
__device__ __forceinline__ uint32_t hadd2_bf(uint32_t a, uint32_t b) {
  uint32_t r; asm("add.rn.bf16x2 %0, %1, %2;" : "=r"(r) : "r"(a), "r"(b)); return r;
}
__device__ __forceinline__ uint32_t hsub2_bf(uint32_t a, uint32_t b) {
  uint32_t r; asm("sub.rn.bf16x2 %0, %1, %2;" : "=r"(r) : "r"(a), "r"(b)); return r;
}
__device__ __forceinline__ float gelu_tanh(float u) {
  float inner = u * fmaf(0.035677408136300125f, u * u, 0.7978845608028654f);
  float th; asm("tanh.approx.f32 %0, %1;" : "=f"(th) : "f"(inner));
  float hu = 0.5f * u;
  return fmaf(hu, th, hu);
}
__device__ __forceinline__ void mma16816(float (&c)[4], uint32_t a0, uint32_t a1, uint32_t a2, uint32_t a3, uint32_t b0, uint32_t b1) {
  asm volatile("mma.sync.aligned.m16n8k16.row.col.f32.bf16.bf16.f32 {%0,%1,%2,%3}, {%4,%5,%6,%7}, {%8,%9}, {%0,%1,%2,%3};"
               : "+f"(c[0]), "+f"(c[1]), "+f"(c[2]), "+f"(c[3]) : "r"(a0), "r"(a1), "r"(a2), "r"(a3), "r"(b0), "r"(b1));
}

__device__ __forceinline__ void wgmma_ss_n224(float (&d)[112], uint64_t descA, uint64_t descB, int scaleD) {
  asm volatile("{\n.reg .pred p;\nsetp.ne.b32 p, %114, 0;\n"
    "wgmma.mma_async.sync.aligned.m64n224k16.f32.bf16.bf16 {%0, %1, %2, %3, %4, %5, %6, %7, %8, %9, %10, %11, %12, %13, %14, %15, %16, %17, %18, %19, %20, %21, %22, %23, %24, %25, %26, %27, %28, %29, %30, %31, %32, %33, %34, %35, %36, %37, %38, %39, %40, %41, %42, %43, %44, %45, %46, %47, %48, %49, %50, %51, %52, %53, %54, %55, %56, %57, %58, %59, %60, %61, %62, %63, %64, %65, %66, %67, %68, %69, %70, %71, %72, %73, %74, %75, %76, %77, %78, %79, %80, %81, %82, %83, %84, %85, %86, %87, %88, %89, %90, %91, %92, %93, %94, %95, %96, %97, %98, %99, %100, %101, %102, %103, %104, %105, %106, %107, %108, %109, %110, %111}, %112, %113, p, 1, 1, 0, 1;\n}\n"
    : "+f"(d[0]), "+f"(d[1]), "+f"(d[2]), "+f"(d[3]), "+f"(d[4]), "+f"(d[5]), "+f"(d[6]), "+f"(d[7]), "+f"(d[8]), "+f"(d[9]), "+f"(d[10]), "+f"(d[11]), "+f"(d[12]), "+f"(d[13]), "+f"(d[14]), "+f"(d[15]), "+f"(d[16]), "+f"(d[17]), "+f"(d[18]), "+f"(d[19]), "+f"(d[20]), "+f"(d[21]), "+f"(d[22]), "+f"(d[23]), "+f"(d[24]), "+f"(d[25]), "+f"(d[26]), "+f"(d[27]), "+f"(d[28]), "+f"(d[29]), "+f"(d[30]), "+f"(d[31]), "+f"(d[32]), "+f"(d[33]), "+f"(d[34]), "+f"(d[35]), "+f"(d[36]), "+f"(d[37]), "+f"(d[38]), "+f"(d[39]), "+f"(d[40]), "+f"(d[41]), "+f"(d[42]), "+f"(d[43]), "+f"(d[44]), "+f"(d[45]), "+f"(d[46]), "+f"(d[47]), "+f"(d[48]), "+f"(d[49]), "+f"(d[50]), "+f"(d[51]), "+f"(d[52]), "+f"(d[53]), "+f"(d[54]), "+f"(d[55]), "+f"(d[56]), "+f"(d[57]), "+f"(d[58]), "+f"(d[59]), "+f"(d[60]), "+f"(d[61]), "+f"(d[62]), "+f"(d[63]), "+f"(d[64]), "+f"(d[65]), "+f"(d[66]), "+f"(d[67]), "+f"(d[68]), "+f"(d[69]), "+f"(d[70]), "+f"(d[71]), "+f"(d[72]), "+f"(d[73]), "+f"(d[74]), "+f"(d[75]), "+f"(d[76]), "+f"(d[77]), "+f"(d[78]), "+f"(d[79]), "+f"(d[80]), "+f"(d[81]), "+f"(d[82]), "+f"(d[83]), "+f"(d[84]), "+f"(d[85]), "+f"(d[86]), "+f"(d[87]), "+f"(d[88]), "+f"(d[89]), "+f"(d[90]), "+f"(d[91]), "+f"(d[92]), "+f"(d[93]), "+f"(d[94]), "+f"(d[95]), "+f"(d[96]), "+f"(d[97]), "+f"(d[98]), "+f"(d[99]), "+f"(d[100]), "+f"(d[101]), "+f"(d[102]), "+f"(d[103]), "+f"(d[104]), "+f"(d[105]), "+f"(d[106]), "+f"(d[107]), "+f"(d[108]), "+f"(d[109]), "+f"(d[110]), "+f"(d[111])
    : "l"(descA), "l"(descB), "r"(scaleD));
}

__device__ __forceinline__ void wgmma_rs_n64(float (&d)[32], const uint32_t (&a)[4], uint64_t descB, int scaleD) {
  asm volatile("{\n.reg .pred p;\nsetp.ne.b32 p, %37, 0;\n"
    "wgmma.mma_async.sync.aligned.m64n64k16.f32.bf16.bf16 {%0, %1, %2, %3, %4, %5, %6, %7, %8, %9, %10, %11, %12, %13, %14, %15, %16, %17, %18, %19, %20, %21, %22, %23, %24, %25, %26, %27, %28, %29, %30, %31}, {%32, %33, %34, %35}, %36, p, 1, 1, 1;\n}\n"
    : "+f"(d[0]), "+f"(d[1]), "+f"(d[2]), "+f"(d[3]), "+f"(d[4]), "+f"(d[5]), "+f"(d[6]), "+f"(d[7]), "+f"(d[8]), "+f"(d[9]), "+f"(d[10]), "+f"(d[11]), "+f"(d[12]), "+f"(d[13]), "+f"(d[14]), "+f"(d[15]), "+f"(d[16]), "+f"(d[17]), "+f"(d[18]), "+f"(d[19]), "+f"(d[20]), "+f"(d[21]), "+f"(d[22]), "+f"(d[23]), "+f"(d[24]), "+f"(d[25]), "+f"(d[26]), "+f"(d[27]), "+f"(d[28]), "+f"(d[29]), "+f"(d[30]), "+f"(d[31])
    : "r"(a[0]), "r"(a[1]), "r"(a[2]), "r"(a[3]), "l"(descB), "r"(scaleD));
}

__device__ __forceinline__ void wgmma_rs_n224(float (&d)[112], const uint32_t (&a)[4], uint64_t descB, int scaleD) {
  asm volatile("{\n.reg .pred p;\nsetp.ne.b32 p, %117, 0;\n"
    "wgmma.mma_async.sync.aligned.m64n224k16.f32.bf16.bf16 {%0, %1, %2, %3, %4, %5, %6, %7, %8, %9, %10, %11, %12, %13, %14, %15, %16, %17, %18, %19, %20, %21, %22, %23, %24, %25, %26, %27, %28, %29, %30, %31, %32, %33, %34, %35, %36, %37, %38, %39, %40, %41, %42, %43, %44, %45, %46, %47, %48, %49, %50, %51, %52, %53, %54, %55, %56, %57, %58, %59, %60, %61, %62, %63, %64, %65, %66, %67, %68, %69, %70, %71, %72, %73, %74, %75, %76, %77, %78, %79, %80, %81, %82, %83, %84, %85, %86, %87, %88, %89, %90, %91, %92, %93, %94, %95, %96, %97, %98, %99, %100, %101, %102, %103, %104, %105, %106, %107, %108, %109, %110, %111}, {%112, %113, %114, %115}, %116, p, 1, 1, 1;\n}\n"
    : "+f"(d[0]), "+f"(d[1]), "+f"(d[2]), "+f"(d[3]), "+f"(d[4]), "+f"(d[5]), "+f"(d[6]), "+f"(d[7]), "+f"(d[8]), "+f"(d[9]), "+f"(d[10]), "+f"(d[11]), "+f"(d[12]), "+f"(d[13]), "+f"(d[14]), "+f"(d[15]), "+f"(d[16]), "+f"(d[17]), "+f"(d[18]), "+f"(d[19]), "+f"(d[20]), "+f"(d[21]), "+f"(d[22]), "+f"(d[23]), "+f"(d[24]), "+f"(d[25]), "+f"(d[26]), "+f"(d[27]), "+f"(d[28]), "+f"(d[29]), "+f"(d[30]), "+f"(d[31]), "+f"(d[32]), "+f"(d[33]), "+f"(d[34]), "+f"(d[35]), "+f"(d[36]), "+f"(d[37]), "+f"(d[38]), "+f"(d[39]), "+f"(d[40]), "+f"(d[41]), "+f"(d[42]), "+f"(d[43]), "+f"(d[44]), "+f"(d[45]), "+f"(d[46]), "+f"(d[47]), "+f"(d[48]), "+f"(d[49]), "+f"(d[50]), "+f"(d[51]), "+f"(d[52]), "+f"(d[53]), "+f"(d[54]), "+f"(d[55]), "+f"(d[56]), "+f"(d[57]), "+f"(d[58]), "+f"(d[59]), "+f"(d[60]), "+f"(d[61]), "+f"(d[62]), "+f"(d[63]), "+f"(d[64]), "+f"(d[65]), "+f"(d[66]), "+f"(d[67]), "+f"(d[68]), "+f"(d[69]), "+f"(d[70]), "+f"(d[71]), "+f"(d[72]), "+f"(d[73]), "+f"(d[74]), "+f"(d[75]), "+f"(d[76]), "+f"(d[77]), "+f"(d[78]), "+f"(d[79]), "+f"(d[80]), "+f"(d[81]), "+f"(d[82]), "+f"(d[83]), "+f"(d[84]), "+f"(d[85]), "+f"(d[86]), "+f"(d[87]), "+f"(d[88]), "+f"(d[89]), "+f"(d[90]), "+f"(d[91]), "+f"(d[92]), "+f"(d[93]), "+f"(d[94]), "+f"(d[95]), "+f"(d[96]), "+f"(d[97]), "+f"(d[98]), "+f"(d[99]), "+f"(d[100]), "+f"(d[101]), "+f"(d[102]), "+f"(d[103]), "+f"(d[104]), "+f"(d[105]), "+f"(d[106]), "+f"(d[107]), "+f"(d[108]), "+f"(d[109]), "+f"(d[110]), "+f"(d[111])
    : "r"(a[0]), "r"(a[1]), "r"(a[2]), "r"(a[3]), "l"(descB), "r"(scaleD));
}

__host__ __device__ constexpr int step_kind(int i) { return (i < 3 || i == 6) ? 0 : (i == 7 ? 2 : 1); }
__host__ __device__ constexpr int step_k(int i) { return i < 3 ? i : (i < 6 ? i - 3 : 3); }
__device__ __forceinline__ int step_slice(int i, int j) {
  const int kind = step_kind(i), k = step_k(i);
  const int base = (kind == 0) ? (j ^ 1) : j;
  return (k == 3) ? base : ((base + 2 * (k + 1)) & 7);
}

__host__ __device__ constexpr int load_off(int i) {
  return i < 6 ? OFF_RING + i * SLOT_BYTES
       : i < 10 ? yslot_off(i - 6)
       : i < 16 ? OFF_RING + (i - 10) * SLOT_BYTES
       : i < 18 ? yslot_off(i - 14)
       : i < 24 ? OFF_RING + (i - 18) * SLOT_BYTES
       : i < 26 ? yslot_off(i - 22)
       : OFF_RING + (i - 26) * SLOT_BYTES;
}
__host__ __device__ constexpr int load_dep(int i) { return i < 6 ? -1 : (i < 10 ? -2 : (i < 16 ? i - 10 : i - 8)); }

__global__ void __cluster_dims__(2, 1, 1) __launch_bounds__(NTHREADS, 1)
fused_mlp_kernel(const __nv_bfloat16* __restrict__ x, const __grid_constant__ CUtensorMap tm_w1, const __grid_constant__ CUtensorMap tm_w2,
                 const __nv_bfloat16* __restrict__ b1, const __nv_bfloat16* __restrict__ b2, __nv_bfloat16* __restrict__ out)
{
  extern __shared__ __align__(1024) unsigned char smem[];
  const uint32_t sbase = smem_u32(smem);
  const uint32_t bar_full = sbase + OFF_BAR;
  const uint32_t bar_cons = sbase + OFF_BAR + 256;
  const uint32_t bar_x = sbase + OFF_BAR + 592;
  const uint32_t bar_dfull = sbase + OFF_BAR + 528;
  const uint32_t bar_peer = sbase + OFF_BAR + 560;
  const uint32_t bar_dack = sbase + OFF_BAR + 576;
  const uint32_t bar_ln = sbase + OFF_BAR + 568;
  const int tid = threadIdx.x, warp = tid >> 5, lane = tid & 31;
  const int mb = blockIdx.x >> 3, j = blockIdx.x & 7;

  TS_DECL
  TSC(0);
  if (warp >= 8) {
    asm volatile("setmaxnreg.dec.sync.aligned.u32 40;");
  if (warp == 9 && lane == 0) asm volatile("prefetch.tensormap [%0];" :: "l"(&tm_w1) : "memory");
  if (warp == 10 && lane == 0) asm volatile("prefetch.tensormap [%0];" :: "l"(&tm_w2) : "memory");
  if (warp == 8) {
    mbar_init(bar_full + 8 * lane, 1); mbar_init(bar_cons + 8 * lane, 2);
    if (lane < 4) mbar_init(bar_dfull + 8 * lane, 1);
    if (lane == 4) mbar_init(bar_peer, 2);
    if (lane == 5) mbar_init(bar_ln, 2);
    if (lane == 6 || lane == 7) mbar_init(bar_dack + 8 * (lane - 6), 1);
    asm volatile("fence.mbarrier_init.release.cluster;" ::: "memory");
    fence_async_smem();
    __syncwarp();
    if (lane >= 4 && lane < 8) mbar_expect_tx(bar_dfull + 8 * (lane - 4), DSLOT_BYTES);
    __syncwarp();
  }
    asm volatile("bar.sync 0, 384;" ::: "memory");
    asm volatile("barrier.cluster.arrive.relaxed.aligned;" ::: "memory");
    if (warp == 8 && lane == 0) {
      for (int i = 0; i < NRING; i++) {
        mbar_expect_tx(bar_full + 8 * i, W1_BYTES);
        for (int a = 0; a < 4; a++)
          tma_load_2d(sbase + OFF_RING + i * SLOT_BYTES + a * 4096, &tm_w1, j * BF + a * 64, i * 32, bar_full + 8 * i);
      }
      TS(2, 1);
      for (int t = 2 * mb; t < 2 * mb + 2; t++) {
        if (t < 16) { if (t >= NRING) for (int a = 0; a < 4; a++) tma_prefetch_2d(&tm_w1, j * BF + a * 64, t * 32); }
        else tma_prefetch_2d(&tm_w2, ((t - 16) >> 1) * 64, j * BF + ((t - 16) & 1) * 112);
      }
#pragma unroll
      for (int i = NRING; i < NLOAD; i++) {
        if (load_dep(i) >= 0) mbar_wait(bar_cons + 8 * load_dep(i), 0); else if (i == NRING) mbar_wait(bar_ln, 0);
        TS(2, i);
        const uint32_t dst = sbase + load_off(i);
        if (i < 16) {
          mbar_expect_tx(bar_full + 8 * i, W1_BYTES);
          for (int a = 0; a < 4; a++) tma_load_2d(dst + a * 4096, &tm_w1, j * BF + a * 64, i * 32, bar_full + 8 * i);
        } else {
          mbar_expect_tx(bar_full + 8 * i, W2_BYTES);
          tma_load_2d(dst, &tm_w2, step_slice((i - 16) >> 1, j) * BN2, j * BF + ((i - 16) & 1) * 112, bar_full + 8 * i);
        }
      }
    }
    __syncwarp();
    asm volatile("barrier.cluster.wait.aligned;" ::: "memory");
    if (warp == 9 && lane == 0) {
      for (int k = 0; k < 2; k++) {
        mbar_wait_cluster(bar_dfull + 8 * k, 0);
        mbar_arrive_remote(mapa(bar_dack + 8 * k, (j & 1) ^ 1));
      }
    }
    __syncwarp();
    asm volatile("barrier.cluster.arrive.relaxed.aligned;\nbarrier.cluster.wait.aligned;" ::: "memory");
  } else {
    asm volatile("setmaxnreg.inc.sync.aligned.u32 232;");
    {
      const int wg_ = warp >> 2, w4_ = warp & 3;
      const unsigned char* xg = reinterpret_cast<const unsigned char*>(x + (size_t)(mb * BM + wg_ * 64 + w4_ * 16) * D_MOD) + (lane >> 4) * 1024 + (lane & 15) * 16;
      const uint32_t xs = sbase + wg_ * 65536 + ((lane & 15) >> 3) * 8192 + (w4_ * 16 + (lane >> 4)) * 128;
#pragma unroll
      for (int kq = 0; kq < 4; kq++) {
#pragma unroll
        for (int i = 0; i < 8; i++) {
          const uint32_t dst = xs + kq * 16384 + i * 256 + (((lane & 7) ^ ((2 * i + (lane >> 4)) & 7)) << 4);
          asm volatile("cp.async.cg.shared.global [%0], [%1], 16;" :: "r"(dst), "l"(xg + i * 2048 + kq * 256) : "memory");
        }
        asm volatile("cp.async.commit_group;" ::: "memory");
      }
    }
    TSC(29);
    asm volatile("bar.sync 0, 384;" ::: "memory");
    TSC(31);
    asm volatile("barrier.cluster.arrive.relaxed.aligned;" ::: "memory");
    TSC(23);
    const int wg = warp >> 2, w4 = warp & 3, t128 = tid & 127;
    const int q = lane & 3, g = lane >> 2;
    uint32_t* b1s = reinterpret_cast<uint32_t*>(smem + OFF_B1 + wg * 512);
    uint32_t* b2s = reinterpret_cast<uint32_t*>(smem + OFF_B2 + wg * 128);
    uint32_t bias_a = 0, bias_b = 0;
    if (t128 < BF / 2) bias_a = reinterpret_cast<const uint32_t*>(b1 + j * BF)[t128];
    if (t128 < BN2 / 2) bias_b = reinterpret_cast<const uint32_t*>(b2 + j * BN2)[t128];
    const uint32_t epoch = g_epoch[blockIdx.x];

    float r0, r1;
    uint32_t xa[16][4];
    TSC(24);
    {
      uint32_t xb[16][4];
      float cs[2][4], c0[2][4], c1[2][4];
#pragma unroll
      for (int u = 0; u < 2; u++)
#pragma unroll
        for (int e = 0; e < 4; e++) { cs[u][e] = 0.f; c0[u][e] = 0.f; c1[u][e] = 0.f; }
      const int lrow = w4 * 16 + (lane & 7) + ((lane >> 3) & 1) * 8;
      const uint32_t lbase = sbase + wg * 65536 + lrow * 128;
      const uint32_t ones = 0x3F803F80u;
#pragma unroll
      for (int ks = 0; ks < 32; ks++) {
        if (ks == 0) { asm volatile("cp.async.wait_group 3;" ::: "memory"); __syncwarp(); TSC(25); }
        if (ks == 8) { asm volatile("cp.async.wait_group 2;" ::: "memory"); __syncwarp(); }
        if (ks == 16) { asm volatile("cp.async.wait_group 1;" ::: "memory"); __syncwarp(); }
        if (ks == 24) { asm volatile("cp.async.wait_group 0;" ::: "memory"); __syncwarp(); TSC(22); }
        uint32_t (&a)[4] = ks < 16 ? xa[ks] : xb[ks - 16];
        const uint32_t addr = lbase + (ks >> 2) * 8192 + (((2 * (ks & 3) + (lane >> 4)) ^ (lane & 7)) << 4);
        asm volatile("ldmatrix.sync.aligned.m8n8.x4.shared.b16 {%0,%1,%2,%3}, [%4];" : "=r"(a[0]), "=r"(a[1]), "=r"(a[2]), "=r"(a[3]) : "r"(addr));
        mma16816(cs[ks & 1], a[0], a[1], a[2], a[3], ones, ones);
        mma16816(c0[ks & 1], a[0], a[1], a[2], a[3], a[0], a[2]);
        mma16816(c1[ks & 1], a[0], a[1], a[2], a[3], a[1], a[3]);
      }
      TSC(27);
      const int dsrc = g * 4 + (g >> 1);
      const float q0 = __shfl_sync(0xffffffffu, (g & 1) ? c0[0][1] + c0[1][1] : c0[0][0] + c0[1][0], dsrc);
      const float q1 = __shfl_sync(0xffffffffu, (g & 1) ? c1[0][3] + c1[1][3] : c1[0][2] + c1[1][2], dsrc);
      const float m0 = (cs[0][0] + cs[1][0]) * (1.0f / D_MOD), m1 = (cs[0][2] + cs[1][2]) * (1.0f / D_MOD);
      const uint32_t mm0 = pack_bf16(m0, m0), mm1 = pack_bf16(m1, m1);
#pragma unroll
      for (int ks = 16; ks < 32; ks++) {
        const uint32_t addr = lbase + (ks >> 2) * 8192 + (((2 * (ks & 3) + (lane >> 4)) ^ (lane & 7)) << 4);
        asm volatile("stmatrix.sync.aligned.m8n8.x4.shared.b16 [%0], {%1,%2,%3,%4};" :: "r"(addr),
                     "r"(hsub2_bf(xb[ks - 16][0], mm0)), "r"(hsub2_bf(xb[ks - 16][1], mm1)),
                     "r"(hsub2_bf(xb[ks - 16][2], mm0)), "r"(hsub2_bf(xb[ks - 16][3], mm1)) : "memory");
      }
#pragma unroll
      for (int ks = 0; ks < 16; ks++) {
        xa[ks][0] = hsub2_bf(xa[ks][0], mm0); xa[ks][1] = hsub2_bf(xa[ks][1], mm1);
        xa[ks][2] = hsub2_bf(xa[ks][2], mm0); xa[ks][3] = hsub2_bf(xa[ks][3], mm1);
      }
      const float v0 = fmaxf(fmaf(-m0, m0, q0 * (1.0f / D_MOD)), 0.f), v1 = fmaxf(fmaf(-m1, m1, q1 * (1.0f / D_MOD)), 0.f);
      r0 = 1.0f / bf16r(sqrtf(bf16r(bf16r(v0) + 1e-5f)));
      r1 = 1.0f / bf16r(sqrtf(bf16r(bf16r(v1) + 1e-5f)));
    }
    if (t128 < BF / 2) b1s[t128] = bias_a;
    if (t128 < BN2 / 2) b2s[t128] = bias_b;
    TSC(1);
    fence_async_smem();
    wg_bar(wg);
    if (t128 == 0) mbar_arrive(bar_ln);
    TSC(2);

    uint32_t h[14][4];
    {
      float acc[112];
#pragma unroll
      for (int kb = 0; kb < 16; kb++) {
        mbar_wait(bar_full + 8 * kb, 0);
        wg_fence();
        const uint32_t abase = sbase + wg * 65536 + (kb >> 1) * 8192 + (kb & 1) * 64;
        const uint32_t bbase = sbase + load_off(kb);
#pragma unroll
        for (int kk = 0; kk < 2; kk++) {
          if (kb < 8) wgmma_rs_n224(acc, xa[2 * kb + kk], make_desc(bbase + kk * 2048, 4096, 1024, 1), (kb | kk) != 0);
          else wgmma_ss_n224(acc, make_desc(abase + kk * 32, 16, 1024, 1), make_desc(bbase + kk * 2048, 4096, 1024, 1), 1);
        }
        wg_commit();
        if (kb > 0) { wg_wait<1>(); if (t128 == 0) mbar_arrive(bar_cons + 8 * (kb - 1)); }
      }
      wg_wait<0>();
      reg_fence(acc);
      asm volatile("barrier.cluster.wait.aligned;" ::: "memory");
      if (t128 == 0) { mbar_arrive(bar_cons + 8 * 15); mbar_arrive_remote(mapa(bar_peer, (j & 1) ^ 1)); }
      TSC(11);

#pragma unroll
      for (int i = 0; i < 28; i++) {
        const uint32_t bb = b1s[i * 4 + q];
        uint32_t p0 = hadd2_bf(pack_bf16(acc[4 * i] * r0, acc[4 * i + 1] * r0), bb);
        uint32_t p1 = hadd2_bf(pack_bf16(acc[4 * i + 2] * r1, acc[4 * i + 3] * r1), bb);
        h[i >> 1][(i & 1) * 2 + 0] = pack_bf16(gelu_tanh(bf_lo(p0)), gelu_tanh(bf_hi(p0)));
        h[i >> 1][(i & 1) * 2 + 1] = pack_bf16(gelu_tanh(bf_lo(p1)), gelu_tanh(bf_hi(p1)));
      }
    }

    const uint32_t par = (epoch + 1) & 1;
    float acc2[2][32];
    float sum[32];
    uint4 pf[3][4];
    const uint32_t peer_base = mapa(sbase + wg * 8192, (j & 1) ^ 1);
    const uint32_t peer_dfull = mapa(bar_dfull, (j & 1) ^ 1);
    uint4* my_base = reinterpret_cast<uint4*>(smem) + wg * 512 + t128;
    const uint4* in_part = &g_part[(size_t)((mb * NSPLIT + j) * 3) * 1024 + wg * 512 + t128];
    auto ld_part = [&](const uint4* p) {
      uint4 v;
      asm volatile("ld.relaxed.gpu.global.v4.u32 {%0, %1, %2, %3}, [%4];" : "=r"(v.x), "=r"(v.y), "=r"(v.z), "=r"(v.w) : "l"(p) : "memory");
      return v;
    };
    auto prefetch = [&](int k) {
#pragma unroll
      for (int c = 0; c < 4; c++) pf[k][c] = ld_part(in_part + k * 1024 + c * 128);
    };
    auto consume = [&](int k) {
#pragma unroll
      for (int c = 0; c < 4; c++) {
        uint4 v = pf[k][c];
        uint32_t it = 0;
        while ((((v.x ^ par) | (v.y ^ par) | (v.z ^ par) | (v.w ^ par)) & 1u) != 0) {
          v = ld_part(in_part + k * 1024 + c * 128);
          if (++it > (1u << 20)) asm volatile("trap;");
        }
        sum[c * 8 + 0] += bf_lo(v.x & ~1u); sum[c * 8 + 1] += bf_hi(v.x);
        sum[c * 8 + 2] += bf_lo(v.y & ~1u); sum[c * 8 + 3] += bf_hi(v.y);
        sum[c * 8 + 4] += bf_lo(v.z & ~1u); sum[c * 8 + 5] += bf_hi(v.z);
        sum[c * 8 + 6] += bf_lo(v.w & ~1u); sum[c * 8 + 7] += bf_hi(v.w);
      }
    };
    auto post_pack = [&](int st, float (&a)[32], uint4 (&v)[4]) {
      const int kind = step_kind(st), k = step_k(st);
      if (kind == 0) {
#pragma unroll
        for (int c = 0; c < 4; c++) {
          v[c].x = pack_bf16(a[c * 8 + 0], a[c * 8 + 1]); v[c].y = pack_bf16(a[c * 8 + 2], a[c * 8 + 3]);
          v[c].z = pack_bf16(a[c * 8 + 4], a[c * 8 + 5]); v[c].w = pack_bf16(a[c * 8 + 6], a[c * 8 + 7]);
        }
      } else {
#pragma unroll
        for (int c = 0; c < 4; c++) {
          const uint4 d = v[c];
          v[c].x = (pack_bf16(a[c * 8 + 0] + bf_lo(d.x), a[c * 8 + 1] + bf_hi(d.x)) & ~1u) | par;
          v[c].y = (pack_bf16(a[c * 8 + 2] + bf_lo(d.y), a[c * 8 + 3] + bf_hi(d.y)) & ~1u) | par;
          v[c].z = (pack_bf16(a[c * 8 + 4] + bf_lo(d.z), a[c * 8 + 5] + bf_hi(d.z)) & ~1u) | par;
          v[c].w = (pack_bf16(a[c * 8 + 6] + bf_lo(d.w), a[c * 8 + 7] + bf_hi(d.w)) & ~1u) | par;
        }
      }
      (void)k;
    };
    auto post_send = [&](int st, uint4 (&v)[4]) {
      const int kind = step_kind(st), k = step_k(st);
      if (kind == 0) {
        if (st == 0) mbar_wait(bar_cons + 8 * 15, 0);
        if (k >= 2) mbar_wait_cluster(bar_dack + 8 * (k - 2), 0);
#pragma unroll
        for (int c = 0; c < 4; c++) my_base[yslot_off(k & 1) / 16 + c * 128] = v[c];
        fence_async_smem();
        wg_bar(wg);
        if (t128 == 0) {
          if (st == 0) mbar_wait_cluster(bar_peer, 0);
          asm volatile("cp.async.bulk.shared::cluster.shared::cta.mbarrier::complete_tx::bytes [%0], [%1], %2, [%3];"
                       :: "r"(peer_base + uslot_off(k)), "r"(sbase + yslot_off(k & 1) + wg * 8192), "r"(8192), "r"(peer_dfull + 8 * k) : "memory");
        }
      } else {
#pragma unroll
        for (int c = 0; c < 4; c++) my_base[uslot_off(k) / 16 + c * 128] = v[c];
        fence_async_smem();
        wg_bar(wg);
        if (t128 == 0) {
          const int dest = (j + 2 * (k + 1)) & 7;
          const uint4* p = &g_part[(size_t)((mb * NSPLIT + dest) * 3 + k) * 1024 + wg * 512];
          asm volatile("cp.async.bulk.global.shared::cta.bulk_group [%0], [%1], %2;"
                       :: "l"(p), "r"(sbase + uslot_off(k) + wg * 8192), "r"(8192) : "memory");
          asm volatile("cp.async.bulk.commit_group;" ::: "memory");
        }
      }
    };
    auto issue = [&](int i) {
      mbar_wait(bar_full + 8 * (16 + 2 * i), 0);
      wg_fence();
#pragma unroll
      for (int ks = 0; ks < 7; ks++) {
        wgmma_rs_n64(acc2[i & 1], h[ks], make_desc(sbase + load_off(16 + 2 * i) + ks * 2048, 16, 1024, 1), ks != 0);
      }
      mbar_wait(bar_full + 8 * (17 + 2 * i), 0);
      wg_fence();
#pragma unroll
      for (int ks = 0; ks < 7; ks++) {
        wgmma_rs_n64(acc2[i & 1], h[7 + ks], make_desc(sbase + load_off(17 + 2 * i) + ks * 2048, 16, 1024, 1), 1);
      }
      wg_commit();
    };
    TSC(12);
    issue(0);
    issue(1);
#pragma unroll
    for (int i = 0; i < 7; i++) {
      uint4 v[4];
      if (step_kind(i) == 1) {
        mbar_wait_cluster(bar_dfull + 8 * step_k(i), 0);
#pragma unroll
        for (int c = 0; c < 4; c++) v[c] = my_base[uslot_off(step_k(i)) / 16 + c * 128];
      }
      wg_wait<1>();
      reg_fence(acc2[i & 1]);
      post_pack(i, acc2[i & 1], v);
      if (i <= 3 && t128 == 0) { mbar_arrive(bar_cons + 8 * (16 + 2 * i)); mbar_arrive(bar_cons + 8 * (17 + 2 * i)); }
      if (i + 2 < 8) issue(i + 2);
      TSC(13 + i);
      post_send(i, v);
    }
    prefetch(0); prefetch(1); prefetch(2);
    mbar_wait_cluster(bar_dfull + 8 * 3, 0);
#pragma unroll
    for (int c = 0; c < 4; c++) {
      const uint4 d = my_base[uslot_off(3) / 16 + c * 128];
      sum[c * 8 + 0] = bf_lo(d.x); sum[c * 8 + 1] = bf_hi(d.x); sum[c * 8 + 2] = bf_lo(d.y); sum[c * 8 + 3] = bf_hi(d.y);
      sum[c * 8 + 4] = bf_lo(d.z); sum[c * 8 + 5] = bf_hi(d.z); sum[c * 8 + 6] = bf_lo(d.w); sum[c * 8 + 7] = bf_hi(d.w);
    }
    consume(0);
    consume(1);
    wg_wait<0>();
    reg_fence(acc2[1]);
    TSC(20);
    consume(2);
    TSC(21);
    if (tid == 0) g_epoch[blockIdx.x] = epoch + 1;

    {
      const int row0 = mb * BM + wg * 64 + w4 * 16 + g;
      uint32_t* o0 = reinterpret_cast<uint32_t*>(out + (size_t)row0 * D_MOD + j * BN2) + q;
      uint32_t* o1 = o0 + 8 * D_MOD / 2;
#pragma unroll
      for (int i = 0; i < 8; i++) {
        const uint32_t bb = b2s[i * 4 + q];
        o0[i * 4] = hadd2_bf(pack_bf16(acc2[1][4 * i] + sum[4 * i], acc2[1][4 * i + 1] + sum[4 * i + 1]), bb);
        o1[i * 4] = hadd2_bf(pack_bf16(acc2[1][4 * i + 2] + sum[4 * i + 2], acc2[1][4 * i + 3] + sum[4 * i + 3]), bb);
      }
    }
    if (t128 == 0) asm volatile("cp.async.bulk.wait_group 0;" ::: "memory");
    TSC(26);
    TS_FLUSH;
    asm volatile("barrier.cluster.arrive.relaxed.aligned;\nbarrier.cluster.wait.aligned;" ::: "memory");
  }
}

typedef CUresult (*EncodeFn)(CUtensorMap*, CUtensorMapDataType, cuuint32_t, void*, const cuuint64_t*, const cuuint64_t*,
                             const cuuint32_t*, const cuuint32_t*, CUtensorMapInterleave, CUtensorMapSwizzle,
                             CUtensorMapL2promotion, CUtensorMapFloatOOBfill);

}

extern "C" void kernel_launch(void* const* d_in, const int* in_sizes, int n_in, void* d_out, int out_size) {
  (void)in_sizes; (void)n_in; (void)out_size;
  static CUtensorMap tm_w1, tm_w2;
  static const void* cached_w1 = nullptr; static const void* cached_w2 = nullptr; static const void* cached_x = nullptr;
  const void* w1 = d_in[1]; const void* w2 = d_in[3]; const void* xp = d_in[0];
  if (cached_w1 != w1 || cached_w2 != w2 || cached_x != xp) {
    void* fn = nullptr; cudaDriverEntryPointQueryResult st;
    cudaGetDriverEntryPoint("cuTensorMapEncodeTiled", &fn, cudaEnableDefault, &st);
    EncodeFn enc = (EncodeFn)fn;
    {
      cuuint64_t dims[2] = {(cuuint64_t)F_HID, (cuuint64_t)D_MOD};
      cuuint64_t strides[1] = {(cuuint64_t)F_HID * 2};
      cuuint32_t box[2] = {64, 32};
      cuuint32_t es[2] = {1, 1};
      enc(&tm_w1, CU_TENSOR_MAP_DATA_TYPE_BFLOAT16, 2, const_cast<void*>(w1), dims, strides, box, es,
          CU_TENSOR_MAP_INTERLEAVE_NONE, CU_TENSOR_MAP_SWIZZLE_128B, CU_TENSOR_MAP_L2_PROMOTION_L2_128B, CU_TENSOR_MAP_FLOAT_OOB_FILL_NONE);
    }
    {
      cuuint64_t dims[2] = {(cuuint64_t)D_MOD, (cuuint64_t)F_HID};
      cuuint64_t strides[1] = {(cuuint64_t)D_MOD * 2};
      cuuint32_t box[2] = {64, 112};
      cuuint32_t es[2] = {1, 1};
      enc(&tm_w2, CU_TENSOR_MAP_DATA_TYPE_BFLOAT16, 2, const_cast<void*>(w2), dims, strides, box, es,
          CU_TENSOR_MAP_INTERLEAVE_NONE, CU_TENSOR_MAP_SWIZZLE_128B, CU_TENSOR_MAP_L2_PROMOTION_L2_128B, CU_TENSOR_MAP_FLOAT_OOB_FILL_NONE);
    }
    cudaFuncSetAttribute(fused_mlp_kernel, cudaFuncAttributeMaxDynamicSharedMemorySize, SMEM_TOTAL);
    cached_w1 = w1; cached_w2 = w2; cached_x = xp;
  }
  fused_mlp_kernel<<<NMB * NSPLIT, NTHREADS, SMEM_TOTAL>>>((const __nv_bfloat16*)d_in[0], tm_w1, tm_w2,
      (const __nv_bfloat16*)d_in[2], (const __nv_bfloat16*)d_in[4], (__nv_bfloat16*)d_out);
}
```

```cpp
#include <cuda_runtime.h>
#include <cuda_bf16.h>
#include <cuda.h>
#include <stdint.h>

namespace {

constexpr int S_TOK = 2048, D_MOD = 512, F_HID = 1792;
constexpr int BM = 128, NSPLIT = 8, BF = F_HID / NSPLIT;
constexpr int BN2 = D_MOD / NSPLIT;
constexpr int NMB = S_TOK / BM;
constexpr int SLOT_BYTES = 16384;
constexpr int W1_BYTES = 16384;
constexpr int W2_BYTES = 14336;
constexpr int Y_BYTES = BM * D_MOD * 2;
constexpr int NRING = 6;
constexpr int NLOAD = 32;
constexpr int OFF_RING = Y_BYTES;
__host__ __device__ constexpr int yslot_off(int s) { return (s >> 1) * 65536 + (s & 1) * 16384; }
__host__ __device__ constexpr int uslot_off(int s) { return (s >> 1) * 65536 + 32768 + (s & 1) * 16384; }
constexpr int DSLOT_BYTES = 16384;
constexpr int OFF_BAR = OFF_RING + NRING * SLOT_BYTES;
constexpr int OFF_MEAN = OFF_BAR + 640;
constexpr int OFF_B1 = OFF_MEAN + 512;
constexpr int OFF_B2 = OFF_B1 + 1024;
constexpr int SMEM_TOTAL = OFF_B2 + 256;
constexpr int NTHREADS = 384;
static_assert(SMEM_TOTAL <= 232448, "smem");

__device__ uint4 g_part[(size_t)NMB * NSPLIT * 3 * 1024];
__device__ unsigned int g_epoch[NMB * NSPLIT];

#define TS_DECL
#define TS_FLUSH do {} while (0)
#define TS(role, idx) do {} while (0)
#define TSC(idx) do {} while (0)

__device__ __forceinline__ uint32_t smem_u32(const void* p) { return (uint32_t)__cvta_generic_to_shared(p); }
__device__ __forceinline__ uint32_t mapa(uint32_t a, uint32_t r) {
  uint32_t d; asm volatile("mapa.shared::cluster.u32 %0, %1, %2;" : "=r"(d) : "r"(a), "r"(r)); return d;
}
__device__ __forceinline__ void mbar_init(uint32_t bar, uint32_t cnt) {
  asm volatile("mbarrier.init.shared::cta.b64 [%0], %1;" :: "r"(bar), "r"(cnt) : "memory");
}
__device__ __forceinline__ void mbar_expect_tx(uint32_t bar, uint32_t bytes) {
  asm volatile("mbarrier.arrive.expect_tx.shared::cta.b64 _, [%0], %1;" :: "r"(bar), "r"(bytes) : "memory");
}
__device__ __forceinline__ void mbar_arrive(uint32_t bar) {
  asm volatile("mbarrier.arrive.shared::cta.b64 _, [%0];" :: "r"(bar) : "memory");
}
__device__ __forceinline__ void mbar_arrive_remote(uint32_t rbar) {
  asm volatile("mbarrier.arrive.release.cluster.shared::cluster.b64 _, [%0];" :: "r"(rbar) : "memory");
}
__device__ __forceinline__ void mbar_wait(uint32_t bar, uint32_t parity) {
  uint32_t done = 0; uint32_t it = 0;
  while (true) {
    asm volatile("{\n.reg .pred p;\nmbarrier.try_wait.parity.shared::cta.b64 p, [%1], %2;\nselp.u32 %0, 1, 0, p;\n}"
                 : "=r"(done) : "r"(bar), "r"(parity) : "memory");
    if (done) break;
    if (++it > (1u << 22)) asm volatile("trap;");
  }
}
__device__ __forceinline__ void mbar_wait_cluster(uint32_t bar, uint32_t parity) {
  uint32_t done = 0; uint32_t it = 0;
  while (true) {
    asm volatile("{\n.reg .pred p;\nmbarrier.try_wait.parity.acquire.cluster.shared::cta.b64 p, [%1], %2;\nselp.u32 %0, 1, 0, p;\n}"
                 : "=r"(done) : "r"(bar), "r"(parity) : "memory");
    if (done) break;
    if (++it > (1u << 22)) asm volatile("trap;");
  }
}
__device__ __forceinline__ void tma_load_3d(uint32_t dst, const CUtensorMap* tm, int c0, int c1, int c2, uint32_t bar) {
  asm volatile("cp.async.bulk.tensor.3d.shared::cluster.global.mbarrier::complete_tx::bytes [%0], [%1, {%3, %4, %5}], [%2];"
               :: "r"(dst), "l"(tm), "r"(bar), "r"(c0), "r"(c1), "r"(c2) : "memory");
}
__device__ __forceinline__ void tma_load_2d(uint32_t dst, const CUtensorMap* tm, int c0, int c1, uint32_t bar) {
  asm volatile("cp.async.bulk.tensor.2d.shared::cluster.global.mbarrier::complete_tx::bytes [%0], [%1, {%3, %4}], [%2];"
               :: "r"(dst), "l"(tm), "r"(bar), "r"(c0), "r"(c1) : "memory");
}
__device__ __forceinline__ void tma_prefetch_2d(const CUtensorMap* tm, int c0, int c1) {
  asm volatile("cp.async.bulk.prefetch.tensor.2d.L2.global.tile [%0, {%1, %2}];" :: "l"(tm), "r"(c0), "r"(c1) : "memory");
}
__device__ __forceinline__ void fence_async_smem() { asm volatile("fence.proxy.async.shared::cta;" ::: "memory"); }
__device__ __forceinline__ void wg_bar(int wg) {
  if (wg == 0) asm volatile("bar.sync 1, 128;" ::: "memory"); else asm volatile("bar.sync 2, 128;" ::: "memory");
}
__device__ __forceinline__ void wg_fence() { asm volatile("wgmma.fence.sync.aligned;" ::: "memory"); }
__device__ __forceinline__ void wg_commit() { asm volatile("wgmma.commit_group.sync.aligned;" ::: "memory"); }
template <int N> __device__ __forceinline__ void wg_wait() { asm volatile("wgmma.wait_group.sync.aligned %0;" :: "n"(N) : "memory"); }
template <int N> __device__ __forceinline__ void reg_fence(float (&d)[N]) {
#pragma unroll
  for (int i = 0; i < N; i++) asm volatile("" : "+f"(d[i]) :: "memory");
}
__device__ __forceinline__ uint64_t make_desc(uint32_t addr, uint32_t lbo, uint32_t sbo, uint32_t lt) {
  return (uint64_t)((addr & 0x3FFFF) >> 4) | ((uint64_t)(lbo >> 4) << 16) | ((uint64_t)(sbo >> 4) << 32) | ((uint64_t)lt << 62);
}
__device__ __forceinline__ uint32_t pack_bf16(float lo, float hi) {
  uint32_t r; asm("cvt.rn.bf16x2.f32 %0, %1, %2;" : "=r"(r) : "f"(hi), "f"(lo)); return r;
}
__device__ __forceinline__ float bf_lo(uint32_t v) { return __uint_as_float(v << 16); }
__device__ __forceinline__ float bf_hi(uint32_t v) { return __uint_as_float(v & 0xffff0000u); }
__device__ __forceinline__ float bf16r(float v) { return __bfloat162float(__float2bfloat16_rn(v)); }
__device__ __forceinline__ uint32_t hadd2_bf(uint32_t a, uint32_t b) {
  uint32_t r; asm("add.rn.bf16x2 %0, %1, %2;" : "=r"(r) : "r"(a), "r"(b)); return r;
}
__device__ __forceinline__ uint32_t hsub2_bf(uint32_t a, uint32_t b) {
  uint32_t r; asm("sub.rn.bf16x2 %0, %1, %2;" : "=r"(r) : "r"(a), "r"(b)); return r;
}
__device__ __forceinline__ float gelu_tanh(float u) {
  float inner = u * fmaf(0.035677408136300125f, u * u, 0.7978845608028654f);
  float th; asm("tanh.approx.f32 %0, %1;" : "=f"(th) : "f"(inner));
  float hu = 0.5f * u;
  return fmaf(hu, th, hu);
}
__device__ __forceinline__ void mma16816(float (&c)[4], uint32_t a0, uint32_t a1, uint32_t a2, uint32_t a3, uint32_t b0, uint32_t b1) {
  asm volatile("mma.sync.aligned.m16n8k16.row.col.f32.bf16.bf16.f32 {%0,%1,%2,%3}, {%4,%5,%6,%7}, {%8,%9}, {%0,%1,%2,%3};"
               : "+f"(c[0]), "+f"(c[1]), "+f"(c[2]), "+f"(c[3]) : "r"(a0), "r"(a1), "r"(a2), "r"(a3), "r"(b0), "r"(b1));
}

__device__ __forceinline__ void wgmma_ss_n224(float (&d)[112], uint64_t descA, uint64_t descB, int scaleD) {
  asm volatile("{\n.reg .pred p;\nsetp.ne.b32 p, %114, 0;\n"
    "wgmma.mma_async.sync.aligned.m64n224k16.f32.bf16.bf16 {%0, %1, %2, %3, %4, %5, %6, %7, %8, %9, %10, %11, %12, %13, %14, %15, %16, %17, %18, %19, %20, %21, %22, %23, %24, %25, %26, %27, %28, %29, %30, %31, %32, %33, %34, %35, %36, %37, %38, %39, %40, %41, %42, %43, %44, %45, %46, %47, %48, %49, %50, %51, %52, %53, %54, %55, %56, %57, %58, %59, %60, %61, %62, %63, %64, %65, %66, %67, %68, %69, %70, %71, %72, %73, %74, %75, %76, %77, %78, %79, %80, %81, %82, %83, %84, %85, %86, %87, %88, %89, %90, %91, %92, %93, %94, %95, %96, %97, %98, %99, %100, %101, %102, %103, %104, %105, %106, %107, %108, %109, %110, %111}, %112, %113, p, 1, 1, 0, 1;\n}\n"
    : "+f"(d[0]), "+f"(d[1]), "+f"(d[2]), "+f"(d[3]), "+f"(d[4]), "+f"(d[5]), "+f"(d[6]), "+f"(d[7]), "+f"(d[8]), "+f"(d[9]), "+f"(d[10]), "+f"(d[11]), "+f"(d[12]), "+f"(d[13]), "+f"(d[14]), "+f"(d[15]), "+f"(d[16]), "+f"(d[17]), "+f"(d[18]), "+f"(d[19]), "+f"(d[20]), "+f"(d[21]), "+f"(d[22]), "+f"(d[23]), "+f"(d[24]), "+f"(d[25]), "+f"(d[26]), "+f"(d[27]), "+f"(d[28]), "+f"(d[29]), "+f"(d[30]), "+f"(d[31]), "+f"(d[32]), "+f"(d[33]), "+f"(d[34]), "+f"(d[35]), "+f"(d[36]), "+f"(d[37]), "+f"(d[38]), "+f"(d[39]), "+f"(d[40]), "+f"(d[41]), "+f"(d[42]), "+f"(d[43]), "+f"(d[44]), "+f"(d[45]), "+f"(d[46]), "+f"(d[47]), "+f"(d[48]), "+f"(d[49]), "+f"(d[50]), "+f"(d[51]), "+f"(d[52]), "+f"(d[53]), "+f"(d[54]), "+f"(d[55]), "+f"(d[56]), "+f"(d[57]), "+f"(d[58]), "+f"(d[59]), "+f"(d[60]), "+f"(d[61]), "+f"(d[62]), "+f"(d[63]), "+f"(d[64]), "+f"(d[65]), "+f"(d[66]), "+f"(d[67]), "+f"(d[68]), "+f"(d[69]), "+f"(d[70]), "+f"(d[71]), "+f"(d[72]), "+f"(d[73]), "+f"(d[74]), "+f"(d[75]), "+f"(d[76]), "+f"(d[77]), "+f"(d[78]), "+f"(d[79]), "+f"(d[80]), "+f"(d[81]), "+f"(d[82]), "+f"(d[83]), "+f"(d[84]), "+f"(d[85]), "+f"(d[86]), "+f"(d[87]), "+f"(d[88]), "+f"(d[89]), "+f"(d[90]), "+f"(d[91]), "+f"(d[92]), "+f"(d[93]), "+f"(d[94]), "+f"(d[95]), "+f"(d[96]), "+f"(d[97]), "+f"(d[98]), "+f"(d[99]), "+f"(d[100]), "+f"(d[101]), "+f"(d[102]), "+f"(d[103]), "+f"(d[104]), "+f"(d[105]), "+f"(d[106]), "+f"(d[107]), "+f"(d[108]), "+f"(d[109]), "+f"(d[110]), "+f"(d[111])
    : "l"(descA), "l"(descB), "r"(scaleD));
}

__device__ __forceinline__ void wgmma_rs_n64(float (&d)[32], const uint32_t (&a)[4], uint64_t descB, int scaleD) {
  asm volatile("{\n.reg .pred p;\nsetp.ne.b32 p, %37, 0;\n"
    "wgmma.mma_async.sync.aligned.m64n64k16.f32.bf16.bf16 {%0, %1, %2, %3, %4, %5, %6, %7, %8, %9, %10, %11, %12, %13, %14, %15, %16, %17, %18, %19, %20, %21, %22, %23, %24, %25, %26, %27, %28, %29, %30, %31}, {%32, %33, %34, %35}, %36, p, 1, 1, 1;\n}\n"
    : "+f"(d[0]), "+f"(d[1]), "+f"(d[2]), "+f"(d[3]), "+f"(d[4]), "+f"(d[5]), "+f"(d[6]), "+f"(d[7]), "+f"(d[8]), "+f"(d[9]), "+f"(d[10]), "+f"(d[11]), "+f"(d[12]), "+f"(d[13]), "+f"(d[14]), "+f"(d[15]), "+f"(d[16]), "+f"(d[17]), "+f"(d[18]), "+f"(d[19]), "+f"(d[20]), "+f"(d[21]), "+f"(d[22]), "+f"(d[23]), "+f"(d[24]), "+f"(d[25]), "+f"(d[26]), "+f"(d[27]), "+f"(d[28]), "+f"(d[29]), "+f"(d[30]), "+f"(d[31])
    : "r"(a[0]), "r"(a[1]), "r"(a[2]), "r"(a[3]), "l"(descB), "r"(scaleD));
}

__device__ __forceinline__ void wgmma_rs_n224(float (&d)[112], const uint32_t (&a)[4], uint64_t descB, int scaleD) {
  asm volatile("{\n.reg .pred p;\nsetp.ne.b32 p, %117, 0;\n"
    "wgmma.mma_async.sync.aligned.m64n224k16.f32.bf16.bf16 {%0, %1, %2, %3, %4, %5, %6, %7, %8, %9, %10, %11, %12, %13, %14, %15, %16, %17, %18, %19, %20, %21, %22, %23, %24, %25, %26, %27, %28, %29, %30, %31, %32, %33, %34, %35, %36, %37, %38, %39, %40, %41, %42, %43, %44, %45, %46, %47, %48, %49, %50, %51, %52, %53, %54, %55, %56, %57, %58, %59, %60, %61, %62, %63, %64, %65, %66, %67, %68, %69, %70, %71, %72, %73, %74, %75, %76, %77, %78, %79, %80, %81, %82, %83, %84, %85, %86, %87, %88, %89, %90, %91, %92, %93, %94, %95, %96, %97, %98, %99, %100, %101, %102, %103, %104, %105, %106, %107, %108, %109, %110, %111}, {%112, %113, %114, %115}, %116, p, 1, 1, 1;\n}\n"
    : "+f"(d[0]), "+f"(d[1]), "+f"(d[2]), "+f"(d[3]), "+f"(d[4]), "+f"(d[5]), "+f"(d[6]), "+f"(d[7]), "+f"(d[8]), "+f"(d[9]), "+f"(d[10]), "+f"(d[11]), "+f"(d[12]), "+f"(d[13]), "+f"(d[14]), "+f"(d[15]), "+f"(d[16]), "+f"(d[17]), "+f"(d[18]), "+f"(d[19]), "+f"(d[20]), "+f"(d[21]), "+f"(d[22]), "+f"(d[23]), "+f"(d[24]), "+f"(d[25]), "+f"(d[26]), "+f"(d[27]), "+f"(d[28]), "+f"(d[29]), "+f"(d[30]), "+f"(d[31]), "+f"(d[32]), "+f"(d[33]), "+f"(d[34]), "+f"(d[35]), "+f"(d[36]), "+f"(d[37]), "+f"(d[38]), "+f"(d[39]), "+f"(d[40]), "+f"(d[41]), "+f"(d[42]), "+f"(d[43]), "+f"(d[44]), "+f"(d[45]), "+f"(d[46]), "+f"(d[47]), "+f"(d[48]), "+f"(d[49]), "+f"(d[50]), "+f"(d[51]), "+f"(d[52]), "+f"(d[53]), "+f"(d[54]), "+f"(d[55]), "+f"(d[56]), "+f"(d[57]), "+f"(d[58]), "+f"(d[59]), "+f"(d[60]), "+f"(d[61]), "+f"(d[62]), "+f"(d[63]), "+f"(d[64]), "+f"(d[65]), "+f"(d[66]), "+f"(d[67]), "+f"(d[68]), "+f"(d[69]), "+f"(d[70]), "+f"(d[71]), "+f"(d[72]), "+f"(d[73]), "+f"(d[74]), "+f"(d[75]), "+f"(d[76]), "+f"(d[77]), "+f"(d[78]), "+f"(d[79]), "+f"(d[80]), "+f"(d[81]), "+f"(d[82]), "+f"(d[83]), "+f"(d[84]), "+f"(d[85]), "+f"(d[86]), "+f"(d[87]), "+f"(d[88]), "+f"(d[89]), "+f"(d[90]), "+f"(d[91]), "+f"(d[92]), "+f"(d[93]), "+f"(d[94]), "+f"(d[95]), "+f"(d[96]), "+f"(d[97]), "+f"(d[98]), "+f"(d[99]), "+f"(d[100]), "+f"(d[101]), "+f"(d[102]), "+f"(d[103]), "+f"(d[104]), "+f"(d[105]), "+f"(d[106]), "+f"(d[107]), "+f"(d[108]), "+f"(d[109]), "+f"(d[110]), "+f"(d[111])
    : "r"(a[0]), "r"(a[1]), "r"(a[2]), "r"(a[3]), "l"(descB), "r"(scaleD));
}

__host__ __device__ constexpr int step_kind(int i) { return (i < 3 || i == 6) ? 0 : (i == 7 ? 2 : 1); }
__host__ __device__ constexpr int step_k(int i) { return i < 3 ? i : (i < 6 ? i - 3 : 3); }
__device__ __forceinline__ int step_slice(int i, int j) {
  const int kind = step_kind(i), k = step_k(i);
  const int base = (kind == 0) ? (j ^ 1) : j;
  return (k == 3) ? base : ((base + 2 * (k + 1)) & 7);
}

__host__ __device__ constexpr int load_off(int i) {
  return i < 6 ? OFF_RING + i * SLOT_BYTES
       : i < 10 ? yslot_off(i - 6)
       : i < 16 ? OFF_RING + (i - 10) * SLOT_BYTES
       : i < 18 ? yslot_off(i - 14)
       : i < 24 ? OFF_RING + (i - 18) * SLOT_BYTES
       : i < 26 ? yslot_off(i - 22)
       : OFF_RING + (i - 26) * SLOT_BYTES;
}
__host__ __device__ constexpr int load_dep(int i) { return i < 6 ? -1 : (i < 10 ? -2 : (i < 16 ? i - 10 : i - 8)); }

__global__ void __cluster_dims__(2, 1, 1) __launch_bounds__(NTHREADS, 1)
fused_mlp_kernel(const __nv_bfloat16* __restrict__ x, const __grid_constant__ CUtensorMap tm_w1, const __grid_constant__ CUtensorMap tm_w2,
                 const __nv_bfloat16* __restrict__ b1, const __nv_bfloat16* __restrict__ b2, __nv_bfloat16* __restrict__ out)
{
  extern __shared__ __align__(1024) unsigned char smem[];
  const uint32_t sbase = smem_u32(smem);
  const uint32_t bar_full = sbase + OFF_BAR;
  const uint32_t bar_cons = sbase + OFF_BAR + 256;
  const uint32_t bar_dfull = sbase + OFF_BAR + 528;
  const uint32_t bar_peer = sbase + OFF_BAR + 560;
  const uint32_t bar_dack = sbase + OFF_BAR + 576;
  const int tid = threadIdx.x, warp = tid >> 5, lane = tid & 31;
  const int mb = blockIdx.x >> 3, j = blockIdx.x & 7;

  TS_DECL
  TSC(0);
  if (warp >= 8) {
    asm volatile("setmaxnreg.dec.sync.aligned.u32 40;");
  if (warp == 8) {
    mbar_init(bar_full + 8 * lane, 1); mbar_init(bar_cons + 8 * lane, 2);
    if (lane < 4) mbar_init(bar_dfull + 8 * lane, 1);
    if (lane == 4) mbar_init(bar_peer, 2);
    if (lane == 6 || lane == 7) mbar_init(bar_dack + 8 * (lane - 6), 1);
    asm volatile("fence.mbarrier_init.release.cluster;" ::: "memory");
    fence_async_smem();
    __syncwarp();
    if (lane >= 4 && lane < 8) mbar_expect_tx(bar_dfull + 8 * (lane - 4), DSLOT_BYTES);
    __syncwarp();
  }
    if (warp == 10 && lane == 0) asm volatile("prefetch.tensormap [%0];" :: "l"(&tm_w2) : "memory");
    if (warp == 8 && lane == 0) {
      for (int i = 0; i < NRING; i++) {
        mbar_expect_tx(bar_full + 8 * i, W1_BYTES);
        for (int a = 0; a < 4; a++)
          tma_load_2d(sbase + OFF_RING + i * SLOT_BYTES + a * 4096, &tm_w1, j * BF + a * 64, i * 32, bar_full + 8 * i);
      }
      TS(2, 1);
      for (int t = 2 * mb; t < 2 * mb + 2; t++) {
        if (t < 16) { if (t >= NRING) for (int a = 0; a < 4; a++) tma_prefetch_2d(&tm_w1, j * BF + a * 64, t * 32); }
        else tma_prefetch_2d(&tm_w2, ((t - 16) >> 1) * 64, j * BF + ((t - 16) & 1) * 112);
      }
    }
    __syncwarp();
    asm volatile("bar.sync 0, 384;" ::: "memory");
    asm volatile("barrier.cluster.arrive.relaxed.aligned;" ::: "memory");
    if (warp == 8 && lane == 0) {
#pragma unroll
      for (int i = NRING; i < NLOAD; i++) {
        if (load_dep(i) >= 0) mbar_wait(bar_cons + 8 * load_dep(i), 0);
        TS(2, i);
        const uint32_t dst = sbase + load_off(i);
        if (i < 16) {
          mbar_expect_tx(bar_full + 8 * i, W1_BYTES);
          for (int a = 0; a < 4; a++) tma_load_2d(dst + a * 4096, &tm_w1, j * BF + a * 64, i * 32, bar_full + 8 * i);
        } else {
          mbar_expect_tx(bar_full + 8 * i, W2_BYTES);
          tma_load_2d(dst, &tm_w2, step_slice((i - 16) >> 1, j) * BN2, j * BF + ((i - 16) & 1) * 112, bar_full + 8 * i);
        }
      }
    }
    __syncwarp();
    asm volatile("barrier.cluster.wait.aligned;" ::: "memory");
    if (warp == 9 && lane == 0) {
      for (int k = 0; k < 2; k++) {
        mbar_wait_cluster(bar_dfull + 8 * k, 0);
        mbar_arrive_remote(mapa(bar_dack + 8 * k, (j & 1) ^ 1));
      }
    }
    __syncwarp();
    asm volatile("barrier.cluster.arrive.relaxed.aligned;\nbarrier.cluster.wait.aligned;" ::: "memory");
  } else {
    asm volatile("setmaxnreg.inc.sync.aligned.u32 232;");
    {
      const int wg_ = warp >> 2, w4_ = warp & 3;
      const unsigned char* xg = reinterpret_cast<const unsigned char*>(x + (size_t)(mb * BM + wg_ * 64 + w4_ * 16) * D_MOD) + (lane >> 4) * 1024 + (lane & 15) * 16;
      const uint32_t xs = sbase + wg_ * 65536 + ((lane & 15) >> 3) * 8192 + (w4_ * 16 + (lane >> 4)) * 128;
#pragma unroll
      for (int kq = 0; kq < 4; kq++) {
#pragma unroll
        for (int i = 0; i < 8; i++) {
          const uint32_t dst = xs + kq * 16384 + i * 256 + (((lane & 7) ^ ((2 * i + (lane >> 4)) & 7)) << 4);
          asm volatile("cp.async.cg.shared.global [%0], [%1], 16;" :: "r"(dst), "l"(xg + i * 2048 + kq * 256) : "memory");
        }
        asm volatile("cp.async.commit_group;" ::: "memory");
      }
    }
    TSC(29);
    const int wg = warp >> 2, w4 = warp & 3, t128 = tid & 127;
    const int q = lane & 3, g = lane >> 2;
    uint32_t* b1s = reinterpret_cast<uint32_t*>(smem + OFF_B1 + wg * 512);
    uint32_t* b2s = reinterpret_cast<uint32_t*>(smem + OFF_B2 + wg * 128);
    uint32_t bias_a = 0, bias_b = 0;
    if (t128 < BF / 2) bias_a = reinterpret_cast<const uint32_t*>(b1 + j * BF)[t128];
    if (t128 < BN2 / 2) bias_b = reinterpret_cast<const uint32_t*>(b2 + j * BN2)[t128];
    const uint32_t epoch = g_epoch[blockIdx.x];

    float r0, r1;
    uint32_t xa[16][4];
    TSC(24);
    {
      uint32_t xb[16][4];
      float cs[2][4], c0[2][4], c1[2][4];
#pragma unroll
      for (int u = 0; u < 2; u++)
#pragma unroll
        for (int e = 0; e < 4; e++) { cs[u][e] = 0.f; c0[u][e] = 0.f; c1[u][e] = 0.f; }
      const int lrow = w4 * 16 + (lane & 7) + ((lane >> 3) & 1) * 8;
      const uint32_t lbase = sbase + wg * 65536 + lrow * 128;
      const uint32_t ones = 0x3F803F80u;
#pragma unroll
      for (int ks = 0; ks < 32; ks++) {
        if (ks == 0) { asm volatile("cp.async.wait_group 3;" ::: "memory"); __syncwarp(); TSC(25); }
        if (ks == 8) { asm volatile("cp.async.wait_group 2;" ::: "memory"); __syncwarp(); }
        if (ks == 16) { asm volatile("cp.async.wait_group 1;" ::: "memory"); __syncwarp(); }
        if (ks == 24) { asm volatile("cp.async.wait_group 0;" ::: "memory"); __syncwarp(); TSC(22); }
        uint32_t (&a)[4] = ks < 16 ? xa[ks] : xb[ks - 16];
        const uint32_t addr = lbase + (ks >> 2) * 8192 + (((2 * (ks & 3) + (lane >> 4)) ^ (lane & 7)) << 4);
        asm volatile("ldmatrix.sync.aligned.m8n8.x4.shared.b16 {%0,%1,%2,%3}, [%4];" : "=r"(a[0]), "=r"(a[1]), "=r"(a[2]), "=r"(a[3]) : "r"(addr));
        mma16816(cs[ks & 1], a[0], a[1], a[2], a[3], ones, ones);
        mma16816(c0[ks & 1], a[0], a[1], a[2], a[3], a[0], a[2]);
        mma16816(c1[ks & 1], a[0], a[1], a[2], a[3], a[1], a[3]);
      }
      TSC(27);
      const int dsrc = g * 4 + (g >> 1);
      const float q0 = __shfl_sync(0xffffffffu, (g & 1) ? c0[0][1] + c0[1][1] : c0[0][0] + c0[1][0], dsrc);
      const float q1 = __shfl_sync(0xffffffffu, (g & 1) ? c1[0][3] + c1[1][3] : c1[0][2] + c1[1][2], dsrc);
      const float m0 = (cs[0][0] + cs[1][0]) * (1.0f / D_MOD), m1 = (cs[0][2] + cs[1][2]) * (1.0f / D_MOD);
      const uint32_t mm0 = pack_bf16(m0, m0), mm1 = pack_bf16(m1, m1);
#pragma unroll
      for (int ks = 16; ks < 32; ks++) {
        const uint32_t addr = lbase + (ks >> 2) * 8192 + (((2 * (ks & 3) + (lane >> 4)) ^ (lane & 7)) << 4);
        asm volatile("stmatrix.sync.aligned.m8n8.x4.shared.b16 [%0], {%1,%2,%3,%4};" :: "r"(addr),
                     "r"(hsub2_bf(xb[ks - 16][0], mm0)), "r"(hsub2_bf(xb[ks - 16][1], mm1)),
                     "r"(hsub2_bf(xb[ks - 16][2], mm0)), "r"(hsub2_bf(xb[ks - 16][3], mm1)) : "memory");
      }
#pragma unroll
      for (int ks = 0; ks < 16; ks++) {
        xa[ks][0] = hsub2_bf(xa[ks][0], mm0); xa[ks][1] = hsub2_bf(xa[ks][1], mm1);
        xa[ks][2] = hsub2_bf(xa[ks][2], mm0); xa[ks][3] = hsub2_bf(xa[ks][3], mm1);
      }
      const float v0 = fmaxf(fmaf(-m0, m0, q0 * (1.0f / D_MOD)), 0.f), v1 = fmaxf(fmaf(-m1, m1, q1 * (1.0f / D_MOD)), 0.f);
      r0 = 1.0f / bf16r(sqrtf(bf16r(bf16r(v0) + 1e-5f)));
      r1 = 1.0f / bf16r(sqrtf(bf16r(bf16r(v1) + 1e-5f)));
    }
    if (t128 < BF / 2) b1s[t128] = bias_a;
    if (t128 < BN2 / 2) b2s[t128] = bias_b;
    TSC(1);
    fence_async_smem();
    asm volatile("bar.sync 0, 384;" ::: "memory");
    asm volatile("barrier.cluster.arrive.relaxed.aligned;" ::: "memory");
    TSC(2);

    uint32_t h[14][4];
    {
      float acc[112];
#pragma unroll
      for (int kb = 0; kb < 16; kb++) {
        mbar_wait(bar_full + 8 * kb, 0);
        wg_fence();
        const uint32_t abase = sbase + wg * 65536 + (kb >> 1) * 8192 + (kb & 1) * 64;
        const uint32_t bbase = sbase + load_off(kb);
#pragma unroll
        for (int kk = 0; kk < 2; kk++) {
          if (kb < 8) wgmma_rs_n224(acc, xa[2 * kb + kk], make_desc(bbase + kk * 2048, 4096, 1024, 1), (kb | kk) != 0);
          else wgmma_ss_n224(acc, make_desc(abase + kk * 32, 16, 1024, 1), make_desc(bbase + kk * 2048, 4096, 1024, 1), 1);
        }
        wg_commit();
        if (kb > 0) { wg_wait<1>(); if (t128 == 0) mbar_arrive(bar_cons + 8 * (kb - 1)); }
      }
      wg_wait<0>();
      reg_fence(acc);
      asm volatile("barrier.cluster.wait.aligned;" ::: "memory");
      if (t128 == 0) { mbar_arrive(bar_cons + 8 * 15); mbar_arrive_remote(mapa(bar_peer, (j & 1) ^ 1)); }
      TSC(11);

#pragma unroll
      for (int i = 0; i < 28; i++) {
        const uint32_t bb = b1s[i * 4 + q];
        uint32_t p0 = hadd2_bf(pack_bf16(acc[4 * i] * r0, acc[4 * i + 1] * r0), bb);
        uint32_t p1 = hadd2_bf(pack_bf16(acc[4 * i + 2] * r1, acc[4 * i + 3] * r1), bb);
        h[i >> 1][(i & 1) * 2 + 0] = pack_bf16(gelu_tanh(bf_lo(p0)), gelu_tanh(bf_hi(p0)));
        h[i >> 1][(i & 1) * 2 + 1] = pack_bf16(gelu_tanh(bf_lo(p1)), gelu_tanh(bf_hi(p1)));
      }
    }

    const uint32_t par = (epoch + 1) & 1;
    float acc2[2][32];
    float sum[32];
    uint4 pf[3][4];
    const uint32_t peer_base = mapa(sbase + wg * 8192, (j & 1) ^ 1);
    const uint32_t peer_dfull = mapa(bar_dfull, (j & 1) ^ 1);
    uint4* my_base = reinterpret_cast<uint4*>(smem) + wg * 512 + t128;
    const uint4* in_part = &g_part[(size_t)((mb * NSPLIT + j) * 3) * 1024 + wg * 512 + t128];
    auto ld_part = [&](const uint4* p) {
      uint4 v;
      asm volatile("ld.relaxed.gpu.global.v4.u32 {%0, %1, %2, %3}, [%4];" : "=r"(v.x), "=r"(v.y), "=r"(v.z), "=r"(v.w) : "l"(p) : "memory");
      return v;
    };
    auto prefetch = [&](int k) {
#pragma unroll
      for (int c = 0; c < 4; c++) pf[k][c] = ld_part(in_part + k * 1024 + c * 128);
    };
    auto consume = [&](int k) {
#pragma unroll
      for (int c = 0; c < 4; c++) {
        uint4 v = pf[k][c];
        uint32_t it = 0;
        while ((((v.x ^ par) | (v.y ^ par) | (v.z ^ par) | (v.w ^ par)) & 1u) != 0) {
          v = ld_part(in_part + k * 1024 + c * 128);
          if (++it > (1u << 20)) asm volatile("trap;");
        }
        sum[c * 8 + 0] += bf_lo(v.x & ~1u); sum[c * 8 + 1] += bf_hi(v.x);
        sum[c * 8 + 2] += bf_lo(v.y & ~1u); sum[c * 8 + 3] += bf_hi(v.y);
        sum[c * 8 + 4] += bf_lo(v.z & ~1u); sum[c * 8 + 5] += bf_hi(v.z);
        sum[c * 8 + 6] += bf_lo(v.w & ~1u); sum[c * 8 + 7] += bf_hi(v.w);
      }
    };
    auto post_pack = [&](int st, float (&a)[32], uint4 (&v)[4]) {
      const int kind = step_kind(st), k = step_k(st);
      if (kind == 0) {
#pragma unroll
        for (int c = 0; c < 4; c++) {
          v[c].x = pack_bf16(a[c * 8 + 0], a[c * 8 + 1]); v[c].y = pack_bf16(a[c * 8 + 2], a[c * 8 + 3]);
          v[c].z = pack_bf16(a[c * 8 + 4], a[c * 8 + 5]); v[c].w = pack_bf16(a[c * 8 + 6], a[c * 8 + 7]);
        }
      } else {
#pragma unroll
        for (int c = 0; c < 4; c++) {
          const uint4 d = v[c];
          v[c].x = (pack_bf16(a[c * 8 + 0] + bf_lo(d.x), a[c * 8 + 1] + bf_hi(d.x)) & ~1u) | par;
          v[c].y = (pack_bf16(a[c * 8 + 2] + bf_lo(d.y), a[c * 8 + 3] + bf_hi(d.y)) & ~1u) | par;
          v[c].z = (pack_bf16(a[c * 8 + 4] + bf_lo(d.z), a[c * 8 + 5] + bf_hi(d.z)) & ~1u) | par;
          v[c].w = (pack_bf16(a[c * 8 + 6] + bf_lo(d.w), a[c * 8 + 7] + bf_hi(d.w)) & ~1u) | par;
        }
      }
      (void)k;
    };
    auto post_send = [&](int st, uint4 (&v)[4]) {
      const int kind = step_kind(st), k = step_k(st);
      if (kind == 0) {
        if (st == 0) mbar_wait(bar_cons + 8 * 15, 0);
        if (k >= 2) mbar_wait_cluster(bar_dack + 8 * (k - 2), 0);
#pragma unroll
        for (int c = 0; c < 4; c++) my_base[yslot_off(k & 1) / 16 + c * 128] = v[c];
        fence_async_smem();
        wg_bar(wg);
        if (t128 == 0) {
          if (st == 0) mbar_wait_cluster(bar_peer, 0);
          asm volatile("cp.async.bulk.shared::cluster.shared::cta.mbarrier::complete_tx::bytes [%0], [%1], %2, [%3];"
                       :: "r"(peer_base + uslot_off(k)), "r"(sbase + yslot_off(k & 1) + wg * 8192), "r"(8192), "r"(peer_dfull + 8 * k) : "memory");
        }
      } else {
#pragma unroll
        for (int c = 0; c < 4; c++) my_base[uslot_off(k) / 16 + c * 128] = v[c];
        fence_async_smem();
        wg_bar(wg);
        if (t128 == 0) {
          const int dest = (j + 2 * (k + 1)) & 7;
          const uint4* p = &g_part[(size_t)((mb * NSPLIT + dest) * 3 + k) * 1024 + wg * 512];
          asm volatile("cp.async.bulk.global.shared::cta.bulk_group [%0], [%1], %2;"
                       :: "l"(p), "r"(sbase + uslot_off(k) + wg * 8192), "r"(8192) : "memory");
          asm volatile("cp.async.bulk.commit_group;" ::: "memory");
        }
      }
    };
    auto issue = [&](int i) {
      mbar_wait(bar_full + 8 * (16 + 2 * i), 0);
      wg_fence();
#pragma unroll
      for (int ks = 0; ks < 7; ks++) {
        wgmma_rs_n64(acc2[i & 1], h[ks], make_desc(sbase + load_off(16 + 2 * i) + ks * 2048, 16, 1024, 1), ks != 0);
      }
      mbar_wait(bar_full + 8 * (17 + 2 * i), 0);
      wg_fence();
#pragma unroll
      for (int ks = 0; ks < 7; ks++) {
        wgmma_rs_n64(acc2[i & 1], h[7 + ks], make_desc(sbase + load_off(17 + 2 * i) + ks * 2048, 16, 1024, 1), 1);
      }
      wg_commit();
    };
    TSC(12);
    issue(0);
    issue(1);
#pragma unroll
    for (int i = 0; i < 7; i++) {
      uint4 v[4];
      if (step_kind(i) == 1) {
        mbar_wait_cluster(bar_dfull + 8 * step_k(i), 0);
#pragma unroll
        for (int c = 0; c < 4; c++) v[c] = my_base[uslot_off(step_k(i)) / 16 + c * 128];
      }
      wg_wait<1>();
      reg_fence(acc2[i & 1]);
      post_pack(i, acc2[i & 1], v);
      if (i <= 3 && t128 == 0) { mbar_arrive(bar_cons + 8 * (16 + 2 * i)); mbar_arrive(bar_cons + 8 * (17 + 2 * i)); }
      if (i + 2 < 8) issue(i + 2);
      TSC(13 + i);
      post_send(i, v);
    }
    prefetch(0); prefetch(1); prefetch(2);
    mbar_wait_cluster(bar_dfull + 8 * 3, 0);
#pragma unroll
    for (int c = 0; c < 4; c++) {
      const uint4 d = my_base[uslot_off(3) / 16 + c * 128];
      sum[c * 8 + 0] = bf_lo(d.x); sum[c * 8 + 1] = bf_hi(d.x); sum[c * 8 + 2] = bf_lo(d.y); sum[c * 8 + 3] = bf_hi(d.y);
      sum[c * 8 + 4] = bf_lo(d.z); sum[c * 8 + 5] = bf_hi(d.z); sum[c * 8 + 6] = bf_lo(d.w); sum[c * 8 + 7] = bf_hi(d.w);
    }
    consume(0);
    consume(1);
    wg_wait<0>();
    reg_fence(acc2[1]);
    TSC(20);
    consume(2);
    TSC(21);
    if (tid == 0) g_epoch[blockIdx.x] = epoch + 1;

    {
      const int row0 = mb * BM + wg * 64 + w4 * 16 + g;
      uint32_t* o0 = reinterpret_cast<uint32_t*>(out + (size_t)row0 * D_MOD + j * BN2) + q;
      uint32_t* o1 = o0 + 8 * D_MOD / 2;
#pragma unroll
      for (int i = 0; i < 8; i++) {
        const uint32_t bb = b2s[i * 4 + q];
        o0[i * 4] = hadd2_bf(pack_bf16(acc2[1][4 * i] + sum[4 * i], acc2[1][4 * i + 1] + sum[4 * i + 1]), bb);
        o1[i * 4] = hadd2_bf(pack_bf16(acc2[1][4 * i + 2] + sum[4 * i + 2], acc2[1][4 * i + 3] + sum[4 * i + 3]), bb);
      }
    }
    if (t128 == 0) asm volatile("cp.async.bulk.wait_group 0;" ::: "memory");
    TSC(26);
    TS_FLUSH;
    asm volatile("barrier.cluster.arrive.relaxed.aligned;\nbarrier.cluster.wait.aligned;" ::: "memory");
  }
}

typedef CUresult (*EncodeFn)(CUtensorMap*, CUtensorMapDataType, cuuint32_t, void*, const cuuint64_t*, const cuuint64_t*,
                             const cuuint32_t*, const cuuint32_t*, CUtensorMapInterleave, CUtensorMapSwizzle,
                             CUtensorMapL2promotion, CUtensorMapFloatOOBfill);

}

extern "C" void kernel_launch(void* const* d_in, const int* in_sizes, int n_in, void* d_out, int out_size) {
  (void)in_sizes; (void)n_in; (void)out_size;
  static CUtensorMap tm_w1, tm_w2;
  static const void* cached_w1 = nullptr; static const void* cached_w2 = nullptr; static const void* cached_x = nullptr;
  const void* w1 = d_in[1]; const void* w2 = d_in[3]; const void* xp = d_in[0];
  if (cached_w1 != w1 || cached_w2 != w2 || cached_x != xp) {
    void* fn = nullptr; cudaDriverEntryPointQueryResult st;
    cudaGetDriverEntryPoint("cuTensorMapEncodeTiled", &fn, cudaEnableDefault, &st);
    EncodeFn enc = (EncodeFn)fn;
    {
      cuuint64_t dims[2] = {(cuuint64_t)F_HID, (cuuint64_t)D_MOD};
      cuuint64_t strides[1] = {(cuuint64_t)F_HID * 2};
      cuuint32_t box[2] = {64, 32};
      cuuint32_t es[2] = {1, 1};
      enc(&tm_w1, CU_TENSOR_MAP_DATA_TYPE_BFLOAT16, 2, const_cast<void*>(w1), dims, strides, box, es,
          CU_TENSOR_MAP_INTERLEAVE_NONE, CU_TENSOR_MAP_SWIZZLE_128B, CU_TENSOR_MAP_L2_PROMOTION_L2_128B, CU_TENSOR_MAP_FLOAT_OOB_FILL_NONE);
    }
    {
      cuuint64_t dims[2] = {(cuuint64_t)D_MOD, (cuuint64_t)F_HID};
      cuuint64_t strides[1] = {(cuuint64_t)D_MOD * 2};
      cuuint32_t box[2] = {64, 112};
      cuuint32_t es[2] = {1, 1};
      enc(&tm_w2, CU_TENSOR_MAP_DATA_TYPE_BFLOAT16, 2, const_cast<void*>(w2), dims, strides, box, es,
          CU_TENSOR_MAP_INTERLEAVE_NONE, CU_TENSOR_MAP_SWIZZLE_128B, CU_TENSOR_MAP_L2_PROMOTION_L2_128B, CU_TENSOR_MAP_FLOAT_OOB_FILL_NONE);
    }
    cudaFuncSetAttribute(fused_mlp_kernel, cudaFuncAttributeMaxDynamicSharedMemorySize, SMEM_TOTAL);
    cached_w1 = w1; cached_w2 = w2; cached_x = xp;
  }
  fused_mlp_kernel<<<NMB * NSPLIT, NTHREADS, SMEM_TOTAL>>>((const __nv_bfloat16*)d_in[0], tm_w1, tm_w2,
      (const __nv_bfloat16*)d_in[2], (const __nv_bfloat16*)d_in[4], (__nv_bfloat16*)d_out);
}
```

```cpp
#include <cuda_runtime.h>
#include <cuda_bf16.h>
#include <cuda.h>
#include <stdint.h>

namespace {

constexpr int S_TOK = 2048, D_MOD = 512, F_HID = 1792;
constexpr int BM = 128, NSPLIT = 8, BF = F_HID / NSPLIT;
constexpr int BN2 = D_MOD / NSPLIT;
constexpr int NMB = S_TOK / BM;
constexpr int SLOT_BYTES = 16384;
constexpr int W1_BYTES = 14336;
constexpr int W2_BYTES = 14336;
constexpr int Y_BYTES = BM * D_MOD * 2;
constexpr int NRING = 6;
constexpr int NLOAD = 32;
constexpr int OFF_RING = Y_BYTES;
__host__ __device__ constexpr int yslot_off(int s) { return (s >> 1) * 65536 + (s & 1) * 16384; }
__host__ __device__ constexpr int uslot_off(int s) { return (s >> 1) * 65536 + 32768 + (s & 1) * 16384; }
constexpr int DSLOT_BYTES = 16384;
constexpr int OFF_BAR = OFF_RING + NRING * SLOT_BYTES;
constexpr int OFF_MEAN = OFF_BAR + 640;
constexpr int OFF_B1 = OFF_MEAN + 512;
constexpr int OFF_B2 = OFF_B1 + 1024;
constexpr int SMEM_TOTAL = OFF_B2 + 256;
constexpr int NTHREADS = 384;
static_assert(SMEM_TOTAL <= 232448, "smem");

__device__ uint4 g_part[(size_t)NMB * NSPLIT * 3 * 1024];
__device__ unsigned int g_epoch[NMB * NSPLIT];

#define TS_DECL
#define TS_FLUSH do {} while (0)
#define TS(role, idx) do {} while (0)
#define TSC(idx) do {} while (0)

__device__ __forceinline__ uint32_t smem_u32(const void* p) { return (uint32_t)__cvta_generic_to_shared(p); }
__device__ __forceinline__ uint32_t mapa(uint32_t a, uint32_t r) {
  uint32_t d; asm volatile("mapa.shared::cluster.u32 %0, %1, %2;" : "=r"(d) : "r"(a), "r"(r)); return d;
}
__device__ __forceinline__ void mbar_init(uint32_t bar, uint32_t cnt) {
  asm volatile("mbarrier.init.shared::cta.b64 [%0], %1;" :: "r"(bar), "r"(cnt) : "memory");
}
__device__ __forceinline__ void mbar_expect_tx(uint32_t bar, uint32_t bytes) {
  asm volatile("mbarrier.arrive.expect_tx.shared::cta.b64 _, [%0], %1;" :: "r"(bar), "r"(bytes) : "memory");
}
__device__ __forceinline__ void mbar_arrive(uint32_t bar) {
  asm volatile("mbarrier.arrive.shared::cta.b64 _, [%0];" :: "r"(bar) : "memory");
}
__device__ __forceinline__ void mbar_arrive_remote(uint32_t rbar) {
  asm volatile("mbarrier.arrive.release.cluster.shared::cluster.b64 _, [%0];" :: "r"(rbar) : "memory");
}
__device__ __forceinline__ void mbar_wait(uint32_t bar, uint32_t parity) {
  uint32_t done = 0; uint32_t it = 0;
  while (true) {
    asm volatile("{\n.reg .pred p;\nmbarrier.try_wait.parity.shared::cta.b64 p, [%1], %2;\nselp.u32 %0, 1, 0, p;\n}"
                 : "=r"(done) : "r"(bar), "r"(parity) : "memory");
    if (done) break;
    if (++it > (1u << 22)) asm volatile("trap;");
  }
}
__device__ __forceinline__ void mbar_wait_cluster(uint32_t bar, uint32_t parity) {
  uint32_t done = 0; uint32_t it = 0;
  while (true) {
    asm volatile("{\n.reg .pred p;\nmbarrier.try_wait.parity.acquire.cluster.shared::cta.b64 p, [%1], %2;\nselp.u32 %0, 1, 0, p;\n}"
                 : "=r"(done) : "r"(bar), "r"(parity) : "memory");
    if (done) break;
    if (++it > (1u << 22)) asm volatile("trap;");
  }
}
__device__ __forceinline__ void tma_load_3d(uint32_t dst, const CUtensorMap* tm, int c0, int c1, int c2, uint32_t bar) {
  asm volatile("cp.async.bulk.tensor.3d.shared::cluster.global.mbarrier::complete_tx::bytes [%0], [%1, {%3, %4, %5}], [%2];"
               :: "r"(dst), "l"(tm), "r"(bar), "r"(c0), "r"(c1), "r"(c2) : "memory");
}
__device__ __forceinline__ void tma_load_2d(uint32_t dst, const CUtensorMap* tm, int c0, int c1, uint32_t bar) {
  asm volatile("cp.async.bulk.tensor.2d.shared::cluster.global.mbarrier::complete_tx::bytes [%0], [%1, {%3, %4}], [%2];"
               :: "r"(dst), "l"(tm), "r"(bar), "r"(c0), "r"(c1) : "memory");
}
__device__ __forceinline__ void tma_prefetch_2d(const CUtensorMap* tm, int c0, int c1) {
  asm volatile("cp.async.bulk.prefetch.tensor.2d.L2.global.tile [%0, {%1, %2}];" :: "l"(tm), "r"(c0), "r"(c1) : "memory");
}
__device__ __forceinline__ void fence_async_smem() { asm volatile("fence.proxy.async.shared::cta;" ::: "memory"); }
__device__ __forceinline__ void wg_bar(int wg) {
  if (wg == 0) asm volatile("bar.sync 1, 128;" ::: "memory"); else asm volatile("bar.sync 2, 128;" ::: "memory");
}
__device__ __forceinline__ void wg_fence() { asm volatile("wgmma.fence.sync.aligned;" ::: "memory"); }
__device__ __forceinline__ void wg_commit() { asm volatile("wgmma.commit_group.sync.aligned;" ::: "memory"); }
template <int N> __device__ __forceinline__ void wg_wait() { asm volatile("wgmma.wait_group.sync.aligned %0;" :: "n"(N) : "memory"); }
template <int N> __device__ __forceinline__ void reg_fence(float (&d)[N]) {
#pragma unroll
  for (int i = 0; i < N; i++) asm volatile("" : "+f"(d[i]) :: "memory");
}
__device__ __forceinline__ uint64_t make_desc(uint32_t addr, uint32_t lbo, uint32_t sbo, uint32_t lt) {
  return (uint64_t)((addr & 0x3FFFF) >> 4) | ((uint64_t)(lbo >> 4) << 16) | ((uint64_t)(sbo >> 4) << 32) | ((uint64_t)lt << 62);
}
__device__ __forceinline__ uint32_t pack_bf16(float lo, float hi) {
  uint32_t r; asm("cvt.rn.bf16x2.f32 %0, %1, %2;" : "=r"(r) : "f"(hi), "f"(lo)); return r;
}
__device__ __forceinline__ float bf_lo(uint32_t v) { return __uint_as_float(v << 16); }
__device__ __forceinline__ float bf_hi(uint32_t v) { return __uint_as_float(v & 0xffff0000u); }
__device__ __forceinline__ float bf16r(float v) { return __bfloat162float(__float2bfloat16_rn(v)); }
__device__ __forceinline__ uint32_t hadd2_bf(uint32_t a, uint32_t b) {
  uint32_t r; asm("add.rn.bf16x2 %0, %1, %2;" : "=r"(r) : "r"(a), "r"(b)); return r;
}
__device__ __forceinline__ uint32_t hsub2_bf(uint32_t a, uint32_t b) {
  uint32_t r; asm("sub.rn.bf16x2 %0, %1, %2;" : "=r"(r) : "r"(a), "r"(b)); return r;
}
__device__ __forceinline__ float gelu_tanh(float u) {
  float inner = u * fmaf(0.035677408136300125f, u * u, 0.7978845608028654f);
  float th; asm("tanh.approx.f32 %0, %1;" : "=f"(th) : "f"(inner));
  float hu = 0.5f * u;
  return fmaf(hu, th, hu);
}
__device__ __forceinline__ void mma16816(float (&c)[4], uint32_t a0, uint32_t a1, uint32_t a2, uint32_t a3, uint32_t b0, uint32_t b1) {
  asm volatile("mma.sync.aligned.m16n8k16.row.col.f32.bf16.bf16.f32 {%0,%1,%2,%3}, {%4,%5,%6,%7}, {%8,%9}, {%0,%1,%2,%3};"
               : "+f"(c[0]), "+f"(c[1]), "+f"(c[2]), "+f"(c[3]) : "r"(a0), "r"(a1), "r"(a2), "r"(a3), "r"(b0), "r"(b1));
}

__device__ __forceinline__ void wgmma_ss_n224(float (&d)[112], uint64_t descA, uint64_t descB, int scaleD) {
  asm volatile("{\n.reg .pred p;\nsetp.ne.b32 p, %114, 0;\n"
    "wgmma.mma_async.sync.aligned.m64n224k16.f32.bf16.bf16 {%0, %1, %2, %3, %4, %5, %6, %7, %8, %9, %10, %11, %12, %13, %14, %15, %16, %17, %18, %19, %20, %21, %22, %23, %24, %25, %26, %27, %28, %29, %30, %31, %32, %33, %34, %35, %36, %37, %38, %39, %40, %41, %42, %43, %44, %45, %46, %47, %48, %49, %50, %51, %52, %53, %54, %55, %56, %57, %58, %59, %60, %61, %62, %63, %64, %65, %66, %67, %68, %69, %70, %71, %72, %73, %74, %75, %76, %77, %78, %79, %80, %81, %82, %83, %84, %85, %86, %87, %88, %89, %90, %91, %92, %93, %94, %95, %96, %97, %98, %99, %100, %101, %102, %103, %104, %105, %106, %107, %108, %109, %110, %111}, %112, %113, p, 1, 1, 0, 1;\n}\n"
    : "+f"(d[0]), "+f"(d[1]), "+f"(d[2]), "+f"(d[3]), "+f"(d[4]), "+f"(d[5]), "+f"(d[6]), "+f"(d[7]), "+f"(d[8]), "+f"(d[9]), "+f"(d[10]), "+f"(d[11]), "+f"(d[12]), "+f"(d[13]), "+f"(d[14]), "+f"(d[15]), "+f"(d[16]), "+f"(d[17]), "+f"(d[18]), "+f"(d[19]), "+f"(d[20]), "+f"(d[21]), "+f"(d[22]), "+f"(d[23]), "+f"(d[24]), "+f"(d[25]), "+f"(d[26]), "+f"(d[27]), "+f"(d[28]), "+f"(d[29]), "+f"(d[30]), "+f"(d[31]), "+f"(d[32]), "+f"(d[33]), "+f"(d[34]), "+f"(d[35]), "+f"(d[36]), "+f"(d[37]), "+f"(d[38]), "+f"(d[39]), "+f"(d[40]), "+f"(d[41]), "+f"(d[42]), "+f"(d[43]), "+f"(d[44]), "+f"(d[45]), "+f"(d[46]), "+f"(d[47]), "+f"(d[48]), "+f"(d[49]), "+f"(d[50]), "+f"(d[51]), "+f"(d[52]), "+f"(d[53]), "+f"(d[54]), "+f"(d[55]), "+f"(d[56]), "+f"(d[57]), "+f"(d[58]), "+f"(d[59]), "+f"(d[60]), "+f"(d[61]), "+f"(d[62]), "+f"(d[63]), "+f"(d[64]), "+f"(d[65]), "+f"(d[66]), "+f"(d[67]), "+f"(d[68]), "+f"(d[69]), "+f"(d[70]), "+f"(d[71]), "+f"(d[72]), "+f"(d[73]), "+f"(d[74]), "+f"(d[75]), "+f"(d[76]), "+f"(d[77]), "+f"(d[78]), "+f"(d[79]), "+f"(d[80]), "+f"(d[81]), "+f"(d[82]), "+f"(d[83]), "+f"(d[84]), "+f"(d[85]), "+f"(d[86]), "+f"(d[87]), "+f"(d[88]), "+f"(d[89]), "+f"(d[90]), "+f"(d[91]), "+f"(d[92]), "+f"(d[93]), "+f"(d[94]), "+f"(d[95]), "+f"(d[96]), "+f"(d[97]), "+f"(d[98]), "+f"(d[99]), "+f"(d[100]), "+f"(d[101]), "+f"(d[102]), "+f"(d[103]), "+f"(d[104]), "+f"(d[105]), "+f"(d[106]), "+f"(d[107]), "+f"(d[108]), "+f"(d[109]), "+f"(d[110]), "+f"(d[111])
    : "l"(descA), "l"(descB), "r"(scaleD));
}

__device__ __forceinline__ void wgmma_rs_n64(float (&d)[32], const uint32_t (&a)[4], uint64_t descB, int scaleD) {
  asm volatile("{\n.reg .pred p;\nsetp.ne.b32 p, %37, 0;\n"
    "wgmma.mma_async.sync.aligned.m64n64k16.f32.bf16.bf16 {%0, %1, %2, %3, %4, %5, %6, %7, %8, %9, %10, %11, %12, %13, %14, %15, %16, %17, %18, %19, %20, %21, %22, %23, %24, %25, %26, %27, %28, %29, %30, %31}, {%32, %33, %34, %35}, %36, p, 1, 1, 1;\n}\n"
    : "+f"(d[0]), "+f"(d[1]), "+f"(d[2]), "+f"(d[3]), "+f"(d[4]), "+f"(d[5]), "+f"(d[6]), "+f"(d[7]), "+f"(d[8]), "+f"(d[9]), "+f"(d[10]), "+f"(d[11]), "+f"(d[12]), "+f"(d[13]), "+f"(d[14]), "+f"(d[15]), "+f"(d[16]), "+f"(d[17]), "+f"(d[18]), "+f"(d[19]), "+f"(d[20]), "+f"(d[21]), "+f"(d[22]), "+f"(d[23]), "+f"(d[24]), "+f"(d[25]), "+f"(d[26]), "+f"(d[27]), "+f"(d[28]), "+f"(d[29]), "+f"(d[30]), "+f"(d[31])
    : "r"(a[0]), "r"(a[1]), "r"(a[2]), "r"(a[3]), "l"(descB), "r"(scaleD));
}

__device__ __forceinline__ void wgmma_rs_n224(float (&d)[112], const uint32_t (&a)[4], uint64_t descB, int scaleD) {
  asm volatile("{\n.reg .pred p;\nsetp.ne.b32 p, %117, 0;\n"
    "wgmma.mma_async.sync.aligned.m64n224k16.f32.bf16.bf16 {%0, %1, %2, %3, %4, %5, %6, %7, %8, %9, %10, %11, %12, %13, %14, %15, %16, %17, %18, %19, %20, %21, %22, %23, %24, %25, %26, %27, %28, %29, %30, %31, %32, %33, %34, %35, %36, %37, %38, %39, %40, %41, %42, %43, %44, %45, %46, %47, %48, %49, %50, %51, %52, %53, %54, %55, %56, %57, %58, %59, %60, %61, %62, %63, %64, %65, %66, %67, %68, %69, %70, %71, %72, %73, %74, %75, %76, %77, %78, %79, %80, %81, %82, %83, %84, %85, %86, %87, %88, %89, %90, %91, %92, %93, %94, %95, %96, %97, %98, %99, %100, %101, %102, %103, %104, %105, %106, %107, %108, %109, %110, %111}, {%112, %113, %114, %115}, %116, p, 1, 1, 1;\n}\n"
    : "+f"(d[0]), "+f"(d[1]), "+f"(d[2]), "+f"(d[3]), "+f"(d[4]), "+f"(d[5]), "+f"(d[6]), "+f"(d[7]), "+f"(d[8]), "+f"(d[9]), "+f"(d[10]), "+f"(d[11]), "+f"(d[12]), "+f"(d[13]), "+f"(d[14]), "+f"(d[15]), "+f"(d[16]), "+f"(d[17]), "+f"(d[18]), "+f"(d[19]), "+f"(d[20]), "+f"(d[21]), "+f"(d[22]), "+f"(d[23]), "+f"(d[24]), "+f"(d[25]), "+f"(d[26]), "+f"(d[27]), "+f"(d[28]), "+f"(d[29]), "+f"(d[30]), "+f"(d[31]), "+f"(d[32]), "+f"(d[33]), "+f"(d[34]), "+f"(d[35]), "+f"(d[36]), "+f"(d[37]), "+f"(d[38]), "+f"(d[39]), "+f"(d[40]), "+f"(d[41]), "+f"(d[42]), "+f"(d[43]), "+f"(d[44]), "+f"(d[45]), "+f"(d[46]), "+f"(d[47]), "+f"(d[48]), "+f"(d[49]), "+f"(d[50]), "+f"(d[51]), "+f"(d[52]), "+f"(d[53]), "+f"(d[54]), "+f"(d[55]), "+f"(d[56]), "+f"(d[57]), "+f"(d[58]), "+f"(d[59]), "+f"(d[60]), "+f"(d[61]), "+f"(d[62]), "+f"(d[63]), "+f"(d[64]), "+f"(d[65]), "+f"(d[66]), "+f"(d[67]), "+f"(d[68]), "+f"(d[69]), "+f"(d[70]), "+f"(d[71]), "+f"(d[72]), "+f"(d[73]), "+f"(d[74]), "+f"(d[75]), "+f"(d[76]), "+f"(d[77]), "+f"(d[78]), "+f"(d[79]), "+f"(d[80]), "+f"(d[81]), "+f"(d[82]), "+f"(d[83]), "+f"(d[84]), "+f"(d[85]), "+f"(d[86]), "+f"(d[87]), "+f"(d[88]), "+f"(d[89]), "+f"(d[90]), "+f"(d[91]), "+f"(d[92]), "+f"(d[93]), "+f"(d[94]), "+f"(d[95]), "+f"(d[96]), "+f"(d[97]), "+f"(d[98]), "+f"(d[99]), "+f"(d[100]), "+f"(d[101]), "+f"(d[102]), "+f"(d[103]), "+f"(d[104]), "+f"(d[105]), "+f"(d[106]), "+f"(d[107]), "+f"(d[108]), "+f"(d[109]), "+f"(d[110]), "+f"(d[111])
    : "r"(a[0]), "r"(a[1]), "r"(a[2]), "r"(a[3]), "l"(descB), "r"(scaleD));
}

__host__ __device__ constexpr int step_kind(int i) { return (i < 3 || i == 6) ? 0 : (i == 7 ? 2 : 1); }
__host__ __device__ constexpr int step_k(int i) { return i < 3 ? i : (i < 6 ? i - 3 : 3); }
__device__ __forceinline__ int step_slice(int i, int j) {
  const int kind = step_kind(i), k = step_k(i);
  const int base = (kind == 0) ? (j ^ 1) : j;
  return (k == 3) ? base : ((base + 2 * (k + 1)) & 7);
}

__host__ __device__ constexpr int load_off(int i) {
  return i < 6 ? OFF_RING + i * SLOT_BYTES
       : i < 10 ? yslot_off(i - 6)
       : i < 16 ? OFF_RING + (i - 10) * SLOT_BYTES
       : i < 18 ? yslot_off(i - 14)
       : i < 24 ? OFF_RING + (i - 18) * SLOT_BYTES
       : i < 26 ? yslot_off(i - 22)
       : OFF_RING + (i - 26) * SLOT_BYTES;
}
__host__ __device__ constexpr int load_dep(int i) { return i < 6 ? -1 : (i < 10 ? -2 : (i < 16 ? i - 10 : i - 8)); }

__global__ void __cluster_dims__(2, 1, 1) __launch_bounds__(NTHREADS, 1)
fused_mlp_kernel(const __nv_bfloat16* __restrict__ x, const __grid_constant__ CUtensorMap tm_w1, const __grid_constant__ CUtensorMap tm_w2,
                 const __nv_bfloat16* __restrict__ w1, const __nv_bfloat16* __restrict__ w2,
                 const __nv_bfloat16* __restrict__ b1, const __nv_bfloat16* __restrict__ b2, __nv_bfloat16* __restrict__ out)
{
  extern __shared__ __align__(1024) unsigned char smem[];
  const uint32_t sbase = smem_u32(smem);
  const uint32_t bar_full = sbase + OFF_BAR;
  const uint32_t bar_cons = sbase + OFF_BAR + 256;
  const uint32_t bar_dfull = sbase + OFF_BAR + 528;
  const uint32_t bar_peer = sbase + OFF_BAR + 560;
  const uint32_t bar_dack = sbase + OFF_BAR + 576;
  const int tid = threadIdx.x, warp = tid >> 5, lane = tid & 31;
  const int mb = blockIdx.x >> 3, j = blockIdx.x & 7;

  TS_DECL
  TSC(0);
  if (warp >= 8) {
    asm volatile("setmaxnreg.dec.sync.aligned.u32 40;");
  if (warp == 8) {
    mbar_init(bar_full + 8 * lane, 1); mbar_init(bar_cons + 8 * lane, 2);
    if (lane < 4) mbar_init(bar_dfull + 8 * lane, 1);
    if (lane == 4) mbar_init(bar_peer, 2);
    if (lane == 6 || lane == 7) mbar_init(bar_dack + 8 * (lane - 6), 1);
    asm volatile("fence.mbarrier_init.release.cluster;" ::: "memory");
    fence_async_smem();
    __syncwarp();
    if (lane >= 4 && lane < 8) mbar_expect_tx(bar_dfull + 8 * (lane - 4), DSLOT_BYTES);
    __syncwarp();
  }
    if (warp == 9 && lane == 0)
      asm volatile("cp.async.bulk.prefetch.L2.global [%0], %1;" :: "l"(reinterpret_cast<const unsigned char*>(w1) + (size_t)blockIdx.x * 14336), "r"(14336) : "memory");
    if (warp == 11 && lane == 0)
      asm volatile("cp.async.bulk.prefetch.L2.global [%0], %1;" :: "l"(reinterpret_cast<const unsigned char*>(w2) + (size_t)blockIdx.x * 14336), "r"(14336) : "memory");
    if (warp == 10 && lane == 0) asm volatile("prefetch.tensormap [%0];" :: "l"(&tm_w2) : "memory");
    if (warp == 8 && lane == 0) {
      for (int i = 0; i < NRING; i++) {
        mbar_expect_tx(bar_full + 8 * i, W1_BYTES);
        tma_load_3d(sbase + OFF_RING + i * SLOT_BYTES, &tm_w1, 0, i * 32, j * 7, bar_full + 8 * i);
      }
      TS(2, 1);
    }
    __syncwarp();
    asm volatile("bar.sync 0, 384;" ::: "memory");
    asm volatile("barrier.cluster.arrive.relaxed.aligned;" ::: "memory");
    if (warp == 8 && lane == 0) {
#pragma unroll
      for (int i = NRING; i < NLOAD; i++) {
        if (load_dep(i) >= 0) mbar_wait(bar_cons + 8 * load_dep(i), 0);
        TS(2, i);
        const uint32_t dst = sbase + load_off(i);
        if (i < 16) {
          mbar_expect_tx(bar_full + 8 * i, W1_BYTES);
          tma_load_3d(dst, &tm_w1, 0, i * 32, j * 7, bar_full + 8 * i);
        } else {
          mbar_expect_tx(bar_full + 8 * i, W2_BYTES);
          tma_load_2d(dst, &tm_w2, step_slice((i - 16) >> 1, j) * BN2, j * BF + ((i - 16) & 1) * 112, bar_full + 8 * i);
        }
      }
    }
    __syncwarp();
    asm volatile("barrier.cluster.wait.aligned;" ::: "memory");
    if (warp == 9 && lane == 0) {
      for (int k = 0; k < 2; k++) {
        mbar_wait_cluster(bar_dfull + 8 * k, 0);
        mbar_arrive_remote(mapa(bar_dack + 8 * k, (j & 1) ^ 1));
      }
    }
    __syncwarp();
    asm volatile("barrier.cluster.arrive.relaxed.aligned;\nbarrier.cluster.wait.aligned;" ::: "memory");
  } else {
    asm volatile("setmaxnreg.inc.sync.aligned.u32 232;");
    {
      const int wg_ = warp >> 2, w4_ = warp & 3;
      const unsigned char* xg = reinterpret_cast<const unsigned char*>(x + (size_t)(mb * BM + wg_ * 64 + w4_ * 16) * D_MOD) + (lane >> 4) * 1024 + (lane & 15) * 16;
      const uint32_t xs = sbase + wg_ * 65536 + ((lane & 15) >> 3) * 8192 + (w4_ * 16 + (lane >> 4)) * 128;
#pragma unroll
      for (int kq = 0; kq < 4; kq++) {
#pragma unroll
        for (int i = 0; i < 8; i++) {
          const uint32_t dst = xs + kq * 16384 + i * 256 + (((lane & 7) ^ ((2 * i + (lane >> 4)) & 7)) << 4);
          asm volatile("cp.async.cg.shared.global [%0], [%1], 16;" :: "r"(dst), "l"(xg + i * 2048 + kq * 256) : "memory");
        }
        asm volatile("cp.async.commit_group;" ::: "memory");
      }
    }
    TSC(29);
    const int wg = warp >> 2, w4 = warp & 3, t128 = tid & 127;
    const int q = lane & 3, g = lane >> 2;
    uint32_t* b1s = reinterpret_cast<uint32_t*>(smem + OFF_B1 + wg * 512);
    uint32_t* b2s = reinterpret_cast<uint32_t*>(smem + OFF_B2 + wg * 128);
    uint32_t bias_a = 0, bias_b = 0;
    if (t128 < BF / 2) bias_a = reinterpret_cast<const uint32_t*>(b1 + j * BF)[t128];
    if (t128 < BN2 / 2) bias_b = reinterpret_cast<const uint32_t*>(b2 + j * BN2)[t128];
    const uint32_t epoch = g_epoch[blockIdx.x];

    float r0, r1;
    uint32_t xa[16][4];
    TSC(24);
    {
      uint32_t xb[16][4];
      float cs[2][4], c0[2][4], c1[2][4];
#pragma unroll
      for (int u = 0; u < 2; u++)
#pragma unroll
        for (int e = 0; e < 4; e++) { cs[u][e] = 0.f; c0[u][e] = 0.f; c1[u][e] = 0.f; }
      const int lrow = w4 * 16 + (lane & 7) + ((lane >> 3) & 1) * 8;
      const uint32_t lbase = sbase + wg * 65536 + lrow * 128;
      const uint32_t ones = 0x3F803F80u;
#pragma unroll
      for (int ks = 0; ks < 32; ks++) {
        if (ks == 0) { asm volatile("cp.async.wait_group 3;" ::: "memory"); __syncwarp(); TSC(25); }
        if (ks == 8) { asm volatile("cp.async.wait_group 2;" ::: "memory"); __syncwarp(); }
        if (ks == 16) { asm volatile("cp.async.wait_group 1;" ::: "memory"); __syncwarp(); }
        if (ks == 24) { asm volatile("cp.async.wait_group 0;" ::: "memory"); __syncwarp(); TSC(22); }
        uint32_t (&a)[4] = ks < 16 ? xa[ks] : xb[ks - 16];
        const uint32_t addr = lbase + (ks >> 2) * 8192 + (((2 * (ks & 3) + (lane >> 4)) ^ (lane & 7)) << 4);
        asm volatile("ldmatrix.sync.aligned.m8n8.x4.shared.b16 {%0,%1,%2,%3}, [%4];" : "=r"(a[0]), "=r"(a[1]), "=r"(a[2]), "=r"(a[3]) : "r"(addr));
        mma16816(cs[ks & 1], a[0], a[1], a[2], a[3], ones, ones);
        mma16816(c0[ks & 1], a[0], a[1], a[2], a[3], a[0], a[2]);
        mma16816(c1[ks & 1], a[0], a[1], a[2], a[3], a[1], a[3]);
      }
      TSC(27);
      const int dsrc = g * 4 + (g >> 1);
      const float q0 = __shfl_sync(0xffffffffu, (g & 1) ? c0[0][1] + c0[1][1] : c0[0][0] + c0[1][0], dsrc);
      const float q1 = __shfl_sync(0xffffffffu, (g & 1) ? c1[0][3] + c1[1][3] : c1[0][2] + c1[1][2], dsrc);
      const float m0 = (cs[0][0] + cs[1][0]) * (1.0f / D_MOD), m1 = (cs[0][2] + cs[1][2]) * (1.0f / D_MOD);
      const uint32_t mm0 = pack_bf16(m0, m0), mm1 = pack_bf16(m1, m1);
#pragma unroll
      for (int ks = 16; ks < 32; ks++) {
        const uint32_t addr = lbase + (ks >> 2) * 8192 + (((2 * (ks & 3) + (lane >> 4)) ^ (lane & 7)) << 4);
        asm volatile("stmatrix.sync.aligned.m8n8.x4.shared.b16 [%0], {%1,%2,%3,%4};" :: "r"(addr),
                     "r"(hsub2_bf(xb[ks - 16][0], mm0)), "r"(hsub2_bf(xb[ks - 16][1], mm1)),
                     "r"(hsub2_bf(xb[ks - 16][2], mm0)), "r"(hsub2_bf(xb[ks - 16][3], mm1)) : "memory");
      }
#pragma unroll
      for (int ks = 0; ks < 16; ks++) {
        xa[ks][0] = hsub2_bf(xa[ks][0], mm0); xa[ks][1] = hsub2_bf(xa[ks][1], mm1);
        xa[ks][2] = hsub2_bf(xa[ks][2], mm0); xa[ks][3] = hsub2_bf(xa[ks][3], mm1);
      }
      const float v0 = fmaxf(fmaf(-m0, m0, q0 * (1.0f / D_MOD)), 0.f), v1 = fmaxf(fmaf(-m1, m1, q1 * (1.0f / D_MOD)), 0.f);
      r0 = 1.0f / bf16r(sqrtf(bf16r(bf16r(v0) + 1e-5f)));
      r1 = 1.0f / bf16r(sqrtf(bf16r(bf16r(v1) + 1e-5f)));
    }
    if (t128 < BF / 2) b1s[t128] = bias_a;
    if (t128 < BN2 / 2) b2s[t128] = bias_b;
    TSC(1);
    fence_async_smem();
    asm volatile("bar.sync 0, 384;" ::: "memory");
    asm volatile("barrier.cluster.arrive.relaxed.aligned;" ::: "memory");
    TSC(2);

    uint32_t h[14][4];
    {
      float acc[112];
#pragma unroll
      for (int kb = 0; kb < 16; kb++) {
        mbar_wait(bar_full + 8 * kb, 0);
        wg_fence();
        const uint32_t abase = sbase + wg * 65536 + (kb >> 1) * 8192 + (kb & 1) * 64;
        const uint32_t bbase = sbase + load_off(kb);
#pragma unroll
        for (int kk = 0; kk < 2; kk++) {
          if (kb < 8) wgmma_rs_n224(acc, xa[2 * kb + kk], make_desc(bbase + kk * 1024, 2048, 512, 2), (kb | kk) != 0);
          else wgmma_ss_n224(acc, make_desc(abase + kk * 32, 16, 1024, 1), make_desc(bbase + kk * 1024, 2048, 512, 2), 1);
        }
        wg_commit();
        if (kb > 0) { wg_wait<1>(); if (t128 == 0) mbar_arrive(bar_cons + 8 * (kb - 1)); }
      }
      wg_wait<0>();
      reg_fence(acc);
      asm volatile("barrier.cluster.wait.aligned;" ::: "memory");
      if (t128 == 0) { mbar_arrive(bar_cons + 8 * 15); mbar_arrive_remote(mapa(bar_peer, (j & 1) ^ 1)); }
      TSC(11);

#pragma unroll
      for (int i = 0; i < 28; i++) {
        const uint32_t bb = b1s[i * 4 + q];
        uint32_t p0 = hadd2_bf(pack_bf16(acc[4 * i] * r0, acc[4 * i + 1] * r0), bb);
        uint32_t p1 = hadd2_bf(pack_bf16(acc[4 * i + 2] * r1, acc[4 * i + 3] * r1), bb);
        h[i >> 1][(i & 1) * 2 + 0] = pack_bf16(gelu_tanh(bf_lo(p0)), gelu_tanh(bf_hi(p0)));
        h[i >> 1][(i & 1) * 2 + 1] = pack_bf16(gelu_tanh(bf_lo(p1)), gelu_tanh(bf_hi(p1)));
      }
    }

    const uint32_t par = (epoch + 1) & 1;
    float acc2[2][32];
    float sum[32];
    uint4 pf[3][4];
    const uint32_t peer_base = mapa(sbase + wg * 8192, (j & 1) ^ 1);
    const uint32_t peer_dfull = mapa(bar_dfull, (j & 1) ^ 1);
    uint4* my_base = reinterpret_cast<uint4*>(smem) + wg * 512 + t128;
    const uint4* in_part = &g_part[(size_t)((mb * NSPLIT + j) * 3) * 1024 + wg * 512 + t128];
    auto ld_part = [&](const uint4* p) {
      uint4 v;
      asm volatile("ld.relaxed.gpu.global.v4.u32 {%0, %1, %2, %3}, [%4];" : "=r"(v.x), "=r"(v.y), "=r"(v.z), "=r"(v.w) : "l"(p) : "memory");
      return v;
    };
    auto prefetch = [&](int k) {
#pragma unroll
      for (int c = 0; c < 4; c++) pf[k][c] = ld_part(in_part + k * 1024 + c * 128);
    };
    auto consume = [&](int k) {
#pragma unroll
      for (int c = 0; c < 4; c++) {
        uint4 v = pf[k][c];
        uint32_t it = 0;
        while ((((v.x ^ par) | (v.y ^ par) | (v.z ^ par) | (v.w ^ par)) & 1u) != 0) {
          v = ld_part(in_part + k * 1024 + c * 128);
          if (++it > (1u << 20)) asm volatile("trap;");
        }
        sum[c * 8 + 0] += bf_lo(v.x & ~1u); sum[c * 8 + 1] += bf_hi(v.x);
        sum[c * 8 + 2] += bf_lo(v.y & ~1u); sum[c * 8 + 3] += bf_hi(v.y);
        sum[c * 8 + 4] += bf_lo(v.z & ~1u); sum[c * 8 + 5] += bf_hi(v.z);
        sum[c * 8 + 6] += bf_lo(v.w & ~1u); sum[c * 8 + 7] += bf_hi(v.w);
      }
    };
    auto post_pack = [&](int st, float (&a)[32], uint4 (&v)[4]) {
      const int kind = step_kind(st), k = step_k(st);
      if (kind == 0) {
#pragma unroll
        for (int c = 0; c < 4; c++) {
          v[c].x = pack_bf16(a[c * 8 + 0], a[c * 8 + 1]); v[c].y = pack_bf16(a[c * 8 + 2], a[c * 8 + 3]);
          v[c].z = pack_bf16(a[c * 8 + 4], a[c * 8 + 5]); v[c].w = pack_bf16(a[c * 8 + 6], a[c * 8 + 7]);
        }
      } else {
#pragma unroll
        for (int c = 0; c < 4; c++) {
          const uint4 d = v[c];
          v[c].x = (pack_bf16(a[c * 8 + 0] + bf_lo(d.x), a[c * 8 + 1] + bf_hi(d.x)) & ~1u) | par;
          v[c].y = (pack_bf16(a[c * 8 + 2] + bf_lo(d.y), a[c * 8 + 3] + bf_hi(d.y)) & ~1u) | par;
          v[c].z = (pack_bf16(a[c * 8 + 4] + bf_lo(d.z), a[c * 8 + 5] + bf_hi(d.z)) & ~1u) | par;
          v[c].w = (pack_bf16(a[c * 8 + 6] + bf_lo(d.w), a[c * 8 + 7] + bf_hi(d.w)) & ~1u) | par;
        }
      }
      (void)k;
    };
    auto post_send = [&](int st, uint4 (&v)[4]) {
      const int kind = step_kind(st), k = step_k(st);
      if (kind == 0) {
        if (st == 0) mbar_wait(bar_cons + 8 * 15, 0);
        if (k >= 2) mbar_wait_cluster(bar_dack + 8 * (k - 2), 0);
#pragma unroll
        for (int c = 0; c < 4; c++) my_base[yslot_off(k & 1) / 16 + c * 128] = v[c];
        fence_async_smem();
        wg_bar(wg);
        if (t128 == 0) {
          if (st == 0) mbar_wait_cluster(bar_peer, 0);
          asm volatile("cp.async.bulk.shared::cluster.shared::cta.mbarrier::complete_tx::bytes [%0], [%1], %2, [%3];"
                       :: "r"(peer_base + uslot_off(k)), "r"(sbase + yslot_off(k & 1) + wg * 8192), "r"(8192), "r"(peer_dfull + 8 * k) : "memory");
        }
      } else {
#pragma unroll
        for (int c = 0; c < 4; c++) my_base[uslot_off(k) / 16 + c * 128] = v[c];
        fence_async_smem();
        wg_bar(wg);
        if (t128 == 0) {
          const int dest = (j + 2 * (k + 1)) & 7;
          const uint4* p = &g_part[(size_t)((mb * NSPLIT + dest) * 3 + k) * 1024 + wg * 512];
          asm volatile("cp.async.bulk.global.shared::cta.bulk_group [%0], [%1], %2;"
                       :: "l"(p), "r"(sbase + uslot_off(k) + wg * 8192), "r"(8192) : "memory");
          asm volatile("cp.async.bulk.commit_group;" ::: "memory");
        }
      }
    };
    auto issue = [&](int i) {
      mbar_wait(bar_full + 8 * (16 + 2 * i), 0);
      wg_fence();
#pragma unroll
      for (int ks = 0; ks < 7; ks++) {
        wgmma_rs_n64(acc2[i & 1], h[ks], make_desc(sbase + load_off(16 + 2 * i) + ks * 2048, 16, 1024, 1), ks != 0);
      }
      mbar_wait(bar_full + 8 * (17 + 2 * i), 0);
      wg_fence();
#pragma unroll
      for (int ks = 0; ks < 7; ks++) {
        wgmma_rs_n64(acc2[i & 1], h[7 + ks], make_desc(sbase + load_off(17 + 2 * i) + ks * 2048, 16, 1024, 1), 1);
      }
      wg_commit();
    };
    TSC(12);
    issue(0);
    issue(1);
#pragma unroll
    for (int i = 0; i < 7; i++) {
      uint4 v[4];
      if (step_kind(i) == 1) {
        mbar_wait_cluster(bar_dfull + 8 * step_k(i), 0);
#pragma unroll
        for (int c = 0; c < 4; c++) v[c] = my_base[uslot_off(step_k(i)) / 16 + c * 128];
      }
      wg_wait<1>();
      reg_fence(acc2[i & 1]);
      post_pack(i, acc2[i & 1], v);
      if (i <= 3 && t128 == 0) { mbar_arrive(bar_cons + 8 * (16 + 2 * i)); mbar_arrive(bar_cons + 8 * (17 + 2 * i)); }
      if (i + 2 < 8) issue(i + 2);
      TSC(13 + i);
      post_send(i, v);
    }
    prefetch(0); prefetch(1); prefetch(2);
    mbar_wait_cluster(bar_dfull + 8 * 3, 0);
#pragma unroll
    for (int c = 0; c < 4; c++) {
      const uint4 d = my_base[uslot_off(3) / 16 + c * 128];
      sum[c * 8 + 0] = bf_lo(d.x); sum[c * 8 + 1] = bf_hi(d.x); sum[c * 8 + 2] = bf_lo(d.y); sum[c * 8 + 3] = bf_hi(d.y);
      sum[c * 8 + 4] = bf_lo(d.z); sum[c * 8 + 5] = bf_hi(d.z); sum[c * 8 + 6] = bf_lo(d.w); sum[c * 8 + 7] = bf_hi(d.w);
    }
    consume(0);
    consume(1);
    wg_wait<0>();
    reg_fence(acc2[1]);
    TSC(20);
    consume(2);
    TSC(21);
    if (tid == 0) g_epoch[blockIdx.x] = epoch + 1;

    {
      const int row0 = mb * BM + wg * 64 + w4 * 16 + g;
      uint32_t* o0 = reinterpret_cast<uint32_t*>(out + (size_t)row0 * D_MOD + j * BN2) + q;
      uint32_t* o1 = o0 + 8 * D_MOD / 2;
#pragma unroll
      for (int i = 0; i < 8; i++) {
        const uint32_t bb = b2s[i * 4 + q];
        o0[i * 4] = hadd2_bf(pack_bf16(acc2[1][4 * i] + sum[4 * i], acc2[1][4 * i + 1] + sum[4 * i + 1]), bb);
        o1[i * 4] = hadd2_bf(pack_bf16(acc2[1][4 * i + 2] + sum[4 * i + 2], acc2[1][4 * i + 3] + sum[4 * i + 3]), bb);
      }
    }
    if (t128 == 0) asm volatile("cp.async.bulk.wait_group 0;" ::: "memory");
    TSC(26);
    TS_FLUSH;
    asm volatile("barrier.cluster.arrive.relaxed.aligned;\nbarrier.cluster.wait.aligned;" ::: "memory");
  }
}

typedef CUresult (*EncodeFn)(CUtensorMap*, CUtensorMapDataType, cuuint32_t, void*, const cuuint64_t*, const cuuint64_t*,
                             const cuuint32_t*, const cuuint32_t*, CUtensorMapInterleave, CUtensorMapSwizzle,
                             CUtensorMapL2promotion, CUtensorMapFloatOOBfill);

}

extern "C" void kernel_launch(void* const* d_in, const int* in_sizes, int n_in, void* d_out, int out_size) {
  (void)in_sizes; (void)n_in; (void)out_size;
  static CUtensorMap tm_w1, tm_w2;
  static const void* cached_w1 = nullptr; static const void* cached_w2 = nullptr; static const void* cached_x = nullptr;
  const void* w1 = d_in[1]; const void* w2 = d_in[3]; const void* xp = d_in[0];
  if (cached_w1 != w1 || cached_w2 != w2 || cached_x != xp) {
    void* fn = nullptr; cudaDriverEntryPointQueryResult st;
    cudaGetDriverEntryPoint("cuTensorMapEncodeTiled", &fn, cudaEnableDefault, &st);
    EncodeFn enc = (EncodeFn)fn;
    {
      cuuint64_t dims[3] = {32, (cuuint64_t)D_MOD, (cuuint64_t)(F_HID / 32)};
      cuuint64_t strides[2] = {(cuuint64_t)F_HID * 2, 64};
      cuuint32_t box[3] = {32, 32, 7};
      cuuint32_t es[3] = {1, 1, 1};
      enc(&tm_w1, CU_TENSOR_MAP_DATA_TYPE_BFLOAT16, 3, const_cast<void*>(w1), dims, strides, box, es,
          CU_TENSOR_MAP_INTERLEAVE_NONE, CU_TENSOR_MAP_SWIZZLE_64B, CU_TENSOR_MAP_L2_PROMOTION_L2_128B, CU_TENSOR_MAP_FLOAT_OOB_FILL_NONE);
    }
    {
      cuuint64_t dims[2] = {(cuuint64_t)D_MOD, (cuuint64_t)F_HID};
      cuuint64_t strides[1] = {(cuuint64_t)D_MOD * 2};
      cuuint32_t box[2] = {64, 112};
      cuuint32_t es[2] = {1, 1};
      enc(&tm_w2, CU_TENSOR_MAP_DATA_TYPE_BFLOAT16, 2, const_cast<void*>(w2), dims, strides, box, es,
          CU_TENSOR_MAP_INTERLEAVE_NONE, CU_TENSOR_MAP_SWIZZLE_128B, CU_TENSOR_MAP_L2_PROMOTION_L2_128B, CU_TENSOR_MAP_FLOAT_OOB_FILL_NONE);
    }
    cudaFuncSetAttribute(fused_mlp_kernel, cudaFuncAttributeMaxDynamicSharedMemorySize, SMEM_TOTAL);
    cached_w1 = w1; cached_w2 = w2; cached_x = xp;
  }
  fused_mlp_kernel<<<NMB * NSPLIT, NTHREADS, SMEM_TOTAL>>>((const __nv_bfloat16*)d_in[0], tm_w1, tm_w2,
      (const __nv_bfloat16*)d_in[1], (const __nv_bfloat16*)d_in[3], (const __nv_bfloat16*)d_in[2], (const __nv_bfloat16*)d_in[4], (__nv_bfloat16*)d_out);
}
```

```cpp
#include <cuda_runtime.h>
#include <cuda_bf16.h>
#include <cuda.h>
#include <stdint.h>

namespace {

constexpr int S_TOK = 2048, D_MOD = 512, F_HID = 1792;
constexpr int BM = 128, NSPLIT = 8, BF = F_HID / NSPLIT;
constexpr int BN2 = D_MOD / NSPLIT;
constexpr int NMB = S_TOK / BM;
constexpr int SLOT_BYTES = 16384;
constexpr int W1_BYTES = 14336;
constexpr int W2_BYTES = 14336;
constexpr int Y_BYTES = BM * D_MOD * 2;
constexpr int NRING = 6;
constexpr int NLOAD = 32;
constexpr int OFF_RING = Y_BYTES;
__host__ __device__ constexpr int yslot_off(int s) { return (s >> 1) * 65536 + (s & 1) * 16384; }
__host__ __device__ constexpr int uslot_off(int s) { return (s >> 1) * 65536 + 32768 + (s & 1) * 16384; }
constexpr int DSLOT_BYTES = 16384;
constexpr int OFF_BAR = OFF_RING + NRING * SLOT_BYTES;
constexpr int OFF_MEAN = OFF_BAR + 640;
constexpr int OFF_B1 = OFF_MEAN + 512;
constexpr int OFF_B2 = OFF_B1 + 1024;
constexpr int SMEM_TOTAL = OFF_B2 + 256;
constexpr int NTHREADS = 384;
static_assert(SMEM_TOTAL <= 232448, "smem");

__device__ uint4 g_part[(size_t)NMB * NSPLIT * 3 * 1024];
__device__ unsigned int g_epoch[NMB * NSPLIT];

#define TS_DECL
#define TS_FLUSH do {} while (0)
#define TS(role, idx) do {} while (0)
#define TSC(idx) do {} while (0)

__device__ __forceinline__ uint32_t smem_u32(const void* p) { return (uint32_t)__cvta_generic_to_shared(p); }
__device__ __forceinline__ uint32_t mapa(uint32_t a, uint32_t r) {
  uint32_t d; asm volatile("mapa.shared::cluster.u32 %0, %1, %2;" : "=r"(d) : "r"(a), "r"(r)); return d;
}
__device__ __forceinline__ void mbar_init(uint32_t bar, uint32_t cnt) {
  asm volatile("mbarrier.init.shared::cta.b64 [%0], %1;" :: "r"(bar), "r"(cnt) : "memory");
}
__device__ __forceinline__ void mbar_expect_tx(uint32_t bar, uint32_t bytes) {
  asm volatile("mbarrier.arrive.expect_tx.shared::cta.b64 _, [%0], %1;" :: "r"(bar), "r"(bytes) : "memory");
}
__device__ __forceinline__ void mbar_arrive(uint32_t bar) {
  asm volatile("mbarrier.arrive.shared::cta.b64 _, [%0];" :: "r"(bar) : "memory");
}
__device__ __forceinline__ void mbar_arrive_remote(uint32_t rbar) {
  asm volatile("mbarrier.arrive.release.cluster.shared::cluster.b64 _, [%0];" :: "r"(rbar) : "memory");
}
__device__ __forceinline__ void mbar_wait(uint32_t bar, uint32_t parity) {
  uint32_t done = 0; uint32_t it = 0;
  while (true) {
    asm volatile("{\n.reg .pred p;\nmbarrier.try_wait.parity.shared::cta.b64 p, [%1], %2;\nselp.u32 %0, 1, 0, p;\n}"
                 : "=r"(done) : "r"(bar), "r"(parity) : "memory");
    if (done) break;
    if (++it > (1u << 22)) asm volatile("trap;");
  }
}
__device__ __forceinline__ void mbar_wait_cluster(uint32_t bar, uint32_t parity) {
  uint32_t done = 0; uint32_t it = 0;
  while (true) {
    asm volatile("{\n.reg .pred p;\nmbarrier.try_wait.parity.acquire.cluster.shared::cta.b64 p, [%1], %2;\nselp.u32 %0, 1, 0, p;\n}"
                 : "=r"(done) : "r"(bar), "r"(parity) : "memory");
    if (done) break;
    if (++it > (1u << 22)) asm volatile("trap;");
  }
}
__device__ __forceinline__ void tma_load_3d(uint32_t dst, const CUtensorMap* tm, int c0, int c1, int c2, uint32_t bar) {
  asm volatile("cp.async.bulk.tensor.3d.shared::cluster.global.mbarrier::complete_tx::bytes [%0], [%1, {%3, %4, %5}], [%2];"
               :: "r"(dst), "l"(tm), "r"(bar), "r"(c0), "r"(c1), "r"(c2) : "memory");
}
__device__ __forceinline__ void tma_load_2d(uint32_t dst, const CUtensorMap* tm, int c0, int c1, uint32_t bar) {
  asm volatile("cp.async.bulk.tensor.2d.shared::cluster.global.mbarrier::complete_tx::bytes [%0], [%1, {%3, %4}], [%2];"
               :: "r"(dst), "l"(tm), "r"(bar), "r"(c0), "r"(c1) : "memory");
}
__device__ __forceinline__ void tma_prefetch_2d(const CUtensorMap* tm, int c0, int c1) {
  asm volatile("cp.async.bulk.prefetch.tensor.2d.L2.global.tile [%0, {%1, %2}];" :: "l"(tm), "r"(c0), "r"(c1) : "memory");
}
__device__ __forceinline__ void fence_async_smem() { asm volatile("fence.proxy.async.shared::cta;" ::: "memory"); }
__device__ __forceinline__ void wg_bar(int wg) {
  if (wg == 0) asm volatile("bar.sync 1, 128;" ::: "memory"); else asm volatile("bar.sync 2, 128;" ::: "memory");
}
__device__ __forceinline__ void wg_fence() { asm volatile("wgmma.fence.sync.aligned;" ::: "memory"); }
__device__ __forceinline__ void wg_commit() { asm volatile("wgmma.commit_group.sync.aligned;" ::: "memory"); }
template <int N> __device__ __forceinline__ void wg_wait() { asm volatile("wgmma.wait_group.sync.aligned %0;" :: "n"(N) : "memory"); }
template <int N> __device__ __forceinline__ void reg_fence(float (&d)[N]) {
#pragma unroll
  for (int i = 0; i < N; i++) asm volatile("" : "+f"(d[i]) :: "memory");
}
__device__ __forceinline__ uint64_t make_desc(uint32_t addr, uint32_t lbo, uint32_t sbo, uint32_t lt) {
  return (uint64_t)((addr & 0x3FFFF) >> 4) | ((uint64_t)(lbo >> 4) << 16) | ((uint64_t)(sbo >> 4) << 32) | ((uint64_t)lt << 62);
}
__device__ __forceinline__ uint32_t pack_bf16(float lo, float hi) {
  uint32_t r; asm("cvt.rn.bf16x2.f32 %0, %1, %2;" : "=r"(r) : "f"(hi), "f"(lo)); return r;
}
__device__ __forceinline__ float bf_lo(uint32_t v) { return __uint_as_float(v << 16); }
__device__ __forceinline__ float bf_hi(uint32_t v) { return __uint_as_float(v & 0xffff0000u); }
__device__ __forceinline__ float bf16r(float v) { return __bfloat162float(__float2bfloat16_rn(v)); }
__device__ __forceinline__ uint32_t hadd2_bf(uint32_t a, uint32_t b) {
  uint32_t r; asm("add.rn.bf16x2 %0, %1, %2;" : "=r"(r) : "r"(a), "r"(b)); return r;
}
__device__ __forceinline__ uint32_t hsub2_bf(uint32_t a, uint32_t b) {
  uint32_t r; asm("sub.rn.bf16x2 %0, %1, %2;" : "=r"(r) : "r"(a), "r"(b)); return r;
}
__device__ __forceinline__ float gelu_tanh(float u) {
  float inner = u * fmaf(0.035677408136300125f, u * u, 0.7978845608028654f);
  float th; asm("tanh.approx.f32 %0, %1;" : "=f"(th) : "f"(inner));
  float hu = 0.5f * u;
  return fmaf(hu, th, hu);
}
__device__ __forceinline__ void mma16816(float (&c)[4], uint32_t a0, uint32_t a1, uint32_t a2, uint32_t a3, uint32_t b0, uint32_t b1) {
  asm volatile("mma.sync.aligned.m16n8k16.row.col.f32.bf16.bf16.f32 {%0,%1,%2,%3}, {%4,%5,%6,%7}, {%8,%9}, {%0,%1,%2,%3};"
               : "+f"(c[0]), "+f"(c[1]), "+f"(c[2]), "+f"(c[3]) : "r"(a0), "r"(a1), "r"(a2), "r"(a3), "r"(b0), "r"(b1));
}

__device__ __forceinline__ void wgmma_ss_n224(float (&d)[112], uint64_t descA, uint64_t descB, int scaleD) {
  asm volatile("{\n.reg .pred p;\nsetp.ne.b32 p, %114, 0;\n"
    "wgmma.mma_async.sync.aligned.m64n224k16.f32.bf16.bf16 {%0, %1, %2, %3, %4, %5, %6, %7, %8, %9, %10, %11, %12, %13, %14, %15, %16, %17, %18, %19, %20, %21, %22, %23, %24, %25, %26, %27, %28, %29, %30, %31, %32, %33, %34, %35, %36, %37, %38, %39, %40, %41, %42, %43, %44, %45, %46, %47, %48, %49, %50, %51, %52, %53, %54, %55, %56, %57, %58, %59, %60, %61, %62, %63, %64, %65, %66, %67, %68, %69, %70, %71, %72, %73, %74, %75, %76, %77, %78, %79, %80, %81, %82, %83, %84, %85, %86, %87, %88, %89, %90, %91, %92, %93, %94, %95, %96, %97, %98, %99, %100, %101, %102, %103, %104, %105, %106, %107, %108, %109, %110, %111}, %112, %113, p, 1, 1, 0, 1;\n}\n"
    : "+f"(d[0]), "+f"(d[1]), "+f"(d[2]), "+f"(d[3]), "+f"(d[4]), "+f"(d[5]), "+f"(d[6]), "+f"(d[7]), "+f"(d[8]), "+f"(d[9]), "+f"(d[10]), "+f"(d[11]), "+f"(d[12]), "+f"(d[13]), "+f"(d[14]), "+f"(d[15]), "+f"(d[16]), "+f"(d[17]), "+f"(d[18]), "+f"(d[19]), "+f"(d[20]), "+f"(d[21]), "+f"(d[22]), "+f"(d[23]), "+f"(d[24]), "+f"(d[25]), "+f"(d[26]), "+f"(d[27]), "+f"(d[28]), "+f"(d[29]), "+f"(d[30]), "+f"(d[31]), "+f"(d[32]), "+f"(d[33]), "+f"(d[34]), "+f"(d[35]), "+f"(d[36]), "+f"(d[37]), "+f"(d[38]), "+f"(d[39]), "+f"(d[40]), "+f"(d[41]), "+f"(d[42]), "+f"(d[43]), "+f"(d[44]), "+f"(d[45]), "+f"(d[46]), "+f"(d[47]), "+f"(d[48]), "+f"(d[49]), "+f"(d[50]), "+f"(d[51]), "+f"(d[52]), "+f"(d[53]), "+f"(d[54]), "+f"(d[55]), "+f"(d[56]), "+f"(d[57]), "+f"(d[58]), "+f"(d[59]), "+f"(d[60]), "+f"(d[61]), "+f"(d[62]), "+f"(d[63]), "+f"(d[64]), "+f"(d[65]), "+f"(d[66]), "+f"(d[67]), "+f"(d[68]), "+f"(d[69]), "+f"(d[70]), "+f"(d[71]), "+f"(d[72]), "+f"(d[73]), "+f"(d[74]), "+f"(d[75]), "+f"(d[76]), "+f"(d[77]), "+f"(d[78]), "+f"(d[79]), "+f"(d[80]), "+f"(d[81]), "+f"(d[82]), "+f"(d[83]), "+f"(d[84]), "+f"(d[85]), "+f"(d[86]), "+f"(d[87]), "+f"(d[88]), "+f"(d[89]), "+f"(d[90]), "+f"(d[91]), "+f"(d[92]), "+f"(d[93]), "+f"(d[94]), "+f"(d[95]), "+f"(d[96]), "+f"(d[97]), "+f"(d[98]), "+f"(d[99]), "+f"(d[100]), "+f"(d[101]), "+f"(d[102]), "+f"(d[103]), "+f"(d[104]), "+f"(d[105]), "+f"(d[106]), "+f"(d[107]), "+f"(d[108]), "+f"(d[109]), "+f"(d[110]), "+f"(d[111])
    : "l"(descA), "l"(descB), "r"(scaleD));
}

__device__ __forceinline__ void wgmma_rs_n64(float (&d)[32], const uint32_t (&a)[4], uint64_t descB, int scaleD) {
  asm volatile("{\n.reg .pred p;\nsetp.ne.b32 p, %37, 0;\n"
    "wgmma.mma_async.sync.aligned.m64n64k16.f32.bf16.bf16 {%0, %1, %2, %3, %4, %5, %6, %7, %8, %9, %10, %11, %12, %13, %14, %15, %16, %17, %18, %19, %20, %21, %22, %23, %24, %25, %26, %27, %28, %29, %30, %31}, {%32, %33, %34, %35}, %36, p, 1, 1, 1;\n}\n"
    : "+f"(d[0]), "+f"(d[1]), "+f"(d[2]), "+f"(d[3]), "+f"(d[4]), "+f"(d[5]), "+f"(d[6]), "+f"(d[7]), "+f"(d[8]), "+f"(d[9]), "+f"(d[10]), "+f"(d[11]), "+f"(d[12]), "+f"(d[13]), "+f"(d[14]), "+f"(d[15]), "+f"(d[16]), "+f"(d[17]), "+f"(d[18]), "+f"(d[19]), "+f"(d[20]), "+f"(d[21]), "+f"(d[22]), "+f"(d[23]), "+f"(d[24]), "+f"(d[25]), "+f"(d[26]), "+f"(d[27]), "+f"(d[28]), "+f"(d[29]), "+f"(d[30]), "+f"(d[31])
    : "r"(a[0]), "r"(a[1]), "r"(a[2]), "r"(a[3]), "l"(descB), "r"(scaleD));
}

__device__ __forceinline__ void wgmma_rs_n224(float (&d)[112], const uint32_t (&a)[4], uint64_t descB, int scaleD) {
  asm volatile("{\n.reg .pred p;\nsetp.ne.b32 p, %117, 0;\n"
    "wgmma.mma_async.sync.aligned.m64n224k16.f32.bf16.bf16 {%0, %1, %2, %3, %4, %5, %6, %7, %8, %9, %10, %11, %12, %13, %14, %15, %16, %17, %18, %19, %20, %21, %22, %23, %24, %25, %26, %27, %28, %29, %30, %31, %32, %33, %34, %35, %36, %37, %38, %39, %40, %41, %42, %43, %44, %45, %46, %47, %48, %49, %50, %51, %52, %53, %54, %55, %56, %57, %58, %59, %60, %61, %62, %63, %64, %65, %66, %67, %68, %69, %70, %71, %72, %73, %74, %75, %76, %77, %78, %79, %80, %81, %82, %83, %84, %85, %86, %87, %88, %89, %90, %91, %92, %93, %94, %95, %96, %97, %98, %99, %100, %101, %102, %103, %104, %105, %106, %107, %108, %109, %110, %111}, {%112, %113, %114, %115}, %116, p, 1, 1, 1;\n}\n"
    : "+f"(d[0]), "+f"(d[1]), "+f"(d[2]), "+f"(d[3]), "+f"(d[4]), "+f"(d[5]), "+f"(d[6]), "+f"(d[7]), "+f"(d[8]), "+f"(d[9]), "+f"(d[10]), "+f"(d[11]), "+f"(d[12]), "+f"(d[13]), "+f"(d[14]), "+f"(d[15]), "+f"(d[16]), "+f"(d[17]), "+f"(d[18]), "+f"(d[19]), "+f"(d[20]), "+f"(d[21]), "+f"(d[22]), "+f"(d[23]), "+f"(d[24]), "+f"(d[25]), "+f"(d[26]), "+f"(d[27]), "+f"(d[28]), "+f"(d[29]), "+f"(d[30]), "+f"(d[31]), "+f"(d[32]), "+f"(d[33]), "+f"(d[34]), "+f"(d[35]), "+f"(d[36]), "+f"(d[37]), "+f"(d[38]), "+f"(d[39]), "+f"(d[40]), "+f"(d[41]), "+f"(d[42]), "+f"(d[43]), "+f"(d[44]), "+f"(d[45]), "+f"(d[46]), "+f"(d[47]), "+f"(d[48]), "+f"(d[49]), "+f"(d[50]), "+f"(d[51]), "+f"(d[52]), "+f"(d[53]), "+f"(d[54]), "+f"(d[55]), "+f"(d[56]), "+f"(d[57]), "+f"(d[58]), "+f"(d[59]), "+f"(d[60]), "+f"(d[61]), "+f"(d[62]), "+f"(d[63]), "+f"(d[64]), "+f"(d[65]), "+f"(d[66]), "+f"(d[67]), "+f"(d[68]), "+f"(d[69]), "+f"(d[70]), "+f"(d[71]), "+f"(d[72]), "+f"(d[73]), "+f"(d[74]), "+f"(d[75]), "+f"(d[76]), "+f"(d[77]), "+f"(d[78]), "+f"(d[79]), "+f"(d[80]), "+f"(d[81]), "+f"(d[82]), "+f"(d[83]), "+f"(d[84]), "+f"(d[85]), "+f"(d[86]), "+f"(d[87]), "+f"(d[88]), "+f"(d[89]), "+f"(d[90]), "+f"(d[91]), "+f"(d[92]), "+f"(d[93]), "+f"(d[94]), "+f"(d[95]), "+f"(d[96]), "+f"(d[97]), "+f"(d[98]), "+f"(d[99]), "+f"(d[100]), "+f"(d[101]), "+f"(d[102]), "+f"(d[103]), "+f"(d[104]), "+f"(d[105]), "+f"(d[106]), "+f"(d[107]), "+f"(d[108]), "+f"(d[109]), "+f"(d[110]), "+f"(d[111])
    : "r"(a[0]), "r"(a[1]), "r"(a[2]), "r"(a[3]), "l"(descB), "r"(scaleD));
}

__host__ __device__ constexpr int step_kind(int i) { return (i < 3 || i == 6) ? 0 : (i == 7 ? 2 : 1); }
__host__ __device__ constexpr int step_k(int i) { return i < 3 ? i : (i < 6 ? i - 3 : 3); }
__device__ __forceinline__ int step_slice(int i, int j) {
  const int kind = step_kind(i), k = step_k(i);
  const int base = (kind == 0) ? (j ^ 1) : j;
  return (k == 3) ? base : ((base + 2 * (k + 1)) & 7);
}

__host__ __device__ constexpr int load_off(int i) {
  return i < 6 ? OFF_RING + i * SLOT_BYTES
       : i < 10 ? yslot_off(i - 6)
       : i < 16 ? OFF_RING + (i - 10) * SLOT_BYTES
       : i < 18 ? yslot_off(i - 14)
       : i < 24 ? OFF_RING + (i - 18) * SLOT_BYTES
       : i < 26 ? yslot_off(i - 22)
       : OFF_RING + (i - 26) * SLOT_BYTES;
}
__host__ __device__ constexpr int load_dep(int i) { return i < 6 ? -1 : (i < 10 ? -2 : (i < 16 ? i - 10 : i - 8)); }

__global__ void __cluster_dims__(2, 1, 1) __launch_bounds__(NTHREADS, 1)
fused_mlp_kernel(const __grid_constant__ CUtensorMap tm_x, const __grid_constant__ CUtensorMap tm_w1, const __grid_constant__ CUtensorMap tm_w2,
                 const __nv_bfloat16* __restrict__ w1, const __nv_bfloat16* __restrict__ w2,
                 const __nv_bfloat16* __restrict__ b1, const __nv_bfloat16* __restrict__ b2, __nv_bfloat16* __restrict__ out)
{
  extern __shared__ __align__(1024) unsigned char smem[];
  const uint32_t sbase = smem_u32(smem);
  const uint32_t bar_full = sbase + OFF_BAR;
  const uint32_t bar_cons = sbase + OFF_BAR + 256;
  const uint32_t bar_dfull = sbase + OFF_BAR + 528;
  const uint32_t bar_peer = sbase + OFF_BAR + 560;
  const uint32_t bar_x = sbase + OFF_BAR + 592;
  const uint32_t bar_ln = sbase + OFF_BAR + 568;
  const uint32_t bar_dack = sbase + OFF_BAR + 576;
  const int tid = threadIdx.x, warp = tid >> 5, lane = tid & 31;
  const int mb = blockIdx.x >> 3, j = blockIdx.x & 7;

  TS_DECL
  TSC(0);
  if (warp >= 8) {
    asm volatile("setmaxnreg.dec.sync.aligned.u32 40;");
  if (warp == 8) {
    mbar_init(bar_full + 8 * lane, 1); mbar_init(bar_cons + 8 * lane, 2);
    if (lane < 4) mbar_init(bar_dfull + 8 * lane, 1);
    if (lane == 4) mbar_init(bar_peer, 2);
    if (lane == 5) mbar_init(bar_ln, 2);
    if (lane >= 8 && lane < 12) mbar_init(bar_x + 8 * (lane - 8), 1);
    if (lane == 6 || lane == 7) mbar_init(bar_dack + 8 * (lane - 6), 1);
    asm volatile("fence.mbarrier_init.release.cluster;" ::: "memory");
    fence_async_smem();
    __syncwarp();
    if (lane >= 4 && lane < 8) mbar_expect_tx(bar_dfull + 8 * (lane - 4), DSLOT_BYTES);
    __syncwarp();
  }
    asm volatile("bar.sync 0, 384;" ::: "memory");
    if (warp == 9 && lane == 0)
      asm volatile("cp.async.bulk.prefetch.L2.global [%0], %1;" :: "l"(reinterpret_cast<const unsigned char*>(w1) + (size_t)blockIdx.x * 14336), "r"(14336) : "memory");
    if (warp == 11 && lane == 0)
      asm volatile("cp.async.bulk.prefetch.L2.global [%0], %1;" :: "l"(reinterpret_cast<const unsigned char*>(w2) + (size_t)blockIdx.x * 14336), "r"(14336) : "memory");
    if (warp == 10 && lane == 0) asm volatile("prefetch.tensormap [%0];" :: "l"(&tm_w2) : "memory");
    if (warp == 8 && lane == 0) {
      for (int kq = 0; kq < 4; kq++) {
        mbar_expect_tx(bar_x + 8 * kq, 32768);
        tma_load_3d(sbase + kq * 16384, &tm_x, 0, mb * BM, 2 * kq, bar_x + 8 * kq);
        tma_load_3d(sbase + 65536 + kq * 16384, &tm_x, 0, mb * BM + 64, 2 * kq, bar_x + 8 * kq);
      }
      for (int i = 0; i < NRING; i++) {
        mbar_expect_tx(bar_full + 8 * i, W1_BYTES);
        tma_load_3d(sbase + OFF_RING + i * SLOT_BYTES, &tm_w1, 0, i * 32, j * 7, bar_full + 8 * i);
      }
      TS(2, 1);
    }
    __syncwarp();
    asm volatile("barrier.cluster.arrive.relaxed.aligned;" ::: "memory");
    if (warp == 8 && lane == 0) {
#pragma unroll
      for (int i = NRING; i < NLOAD; i++) {
        if (load_dep(i) >= 0) mbar_wait(bar_cons + 8 * load_dep(i), 0); else if (i == NRING) mbar_wait(bar_ln, 0);
        TS(2, i);
        const uint32_t dst = sbase + load_off(i);
        if (i < 16) {
          mbar_expect_tx(bar_full + 8 * i, W1_BYTES);
          tma_load_3d(dst, &tm_w1, 0, i * 32, j * 7, bar_full + 8 * i);
        } else {
          mbar_expect_tx(bar_full + 8 * i, W2_BYTES);
          tma_load_2d(dst, &tm_w2, step_slice((i - 16) >> 1, j) * BN2, j * BF + ((i - 16) & 1) * 112, bar_full + 8 * i);
        }
      }
    }
    __syncwarp();
    asm volatile("barrier.cluster.wait.aligned;" ::: "memory");
    if (warp == 9 && lane == 0) {
      for (int k = 0; k < 2; k++) {
        mbar_wait_cluster(bar_dfull + 8 * k, 0);
        mbar_arrive_remote(mapa(bar_dack + 8 * k, (j & 1) ^ 1));
      }
    }
    __syncwarp();
    asm volatile("barrier.cluster.arrive.relaxed.aligned;\nbarrier.cluster.wait.aligned;" ::: "memory");
  } else {
    asm volatile("setmaxnreg.inc.sync.aligned.u32 232;");
    asm volatile("bar.sync 0, 384;" ::: "memory");
    TSC(29);
    const int wg = warp >> 2, w4 = warp & 3, t128 = tid & 127;
    const int q = lane & 3, g = lane >> 2;
    uint32_t* b1s = reinterpret_cast<uint32_t*>(smem + OFF_B1 + wg * 512);
    uint32_t* b2s = reinterpret_cast<uint32_t*>(smem + OFF_B2 + wg * 128);
    uint32_t bias_a = 0, bias_b = 0;
    if (t128 < BF / 2) bias_a = reinterpret_cast<const uint32_t*>(b1 + j * BF)[t128];
    if (t128 < BN2 / 2) bias_b = reinterpret_cast<const uint32_t*>(b2 + j * BN2)[t128];
    const uint32_t epoch = g_epoch[blockIdx.x];

    float r0, r1;
    uint32_t xa[16][4];
    TSC(24);
    {
      uint32_t xb[16][4];
      float cs[2][4], c0[2][4], c1[2][4];
#pragma unroll
      for (int u = 0; u < 2; u++)
#pragma unroll
        for (int e = 0; e < 4; e++) { cs[u][e] = 0.f; c0[u][e] = 0.f; c1[u][e] = 0.f; }
      const int lrow = w4 * 16 + (lane & 7) + ((lane >> 3) & 1) * 8;
      const uint32_t lbase = sbase + wg * 65536 + lrow * 128;
      const uint32_t ones = 0x3F803F80u;
#pragma unroll
      for (int ks = 0; ks < 32; ks++) {
        if ((ks & 7) == 0) { mbar_wait(bar_x + 8 * (ks >> 3), 0); if (ks == 0) TSC(25); if (ks == 24) TSC(22); }
        uint32_t (&a)[4] = ks < 16 ? xa[ks] : xb[ks - 16];
        const uint32_t addr = lbase + (ks >> 2) * 8192 + (((2 * (ks & 3) + (lane >> 4)) ^ (lane & 7)) << 4);
        asm volatile("ldmatrix.sync.aligned.m8n8.x4.shared.b16 {%0,%1,%2,%3}, [%4];" : "=r"(a[0]), "=r"(a[1]), "=r"(a[2]), "=r"(a[3]) : "r"(addr));
        mma16816(cs[ks & 1], a[0], a[1], a[2], a[3], ones, ones);
        mma16816(c0[ks & 1], a[0], a[1], a[2], a[3], a[0], a[2]);
        mma16816(c1[ks & 1], a[0], a[1], a[2], a[3], a[1], a[3]);
      }
      TSC(27);
      const int dsrc = g * 4 + (g >> 1);
      const float q0 = __shfl_sync(0xffffffffu, (g & 1) ? c0[0][1] + c0[1][1] : c0[0][0] + c0[1][0], dsrc);
      const float q1 = __shfl_sync(0xffffffffu, (g & 1) ? c1[0][3] + c1[1][3] : c1[0][2] + c1[1][2], dsrc);
      const float m0 = (cs[0][0] + cs[1][0]) * (1.0f / D_MOD), m1 = (cs[0][2] + cs[1][2]) * (1.0f / D_MOD);
      const uint32_t mm0 = pack_bf16(m0, m0), mm1 = pack_bf16(m1, m1);
#pragma unroll
      for (int ks = 16; ks < 32; ks++) {
        const uint32_t addr = lbase + (ks >> 2) * 8192 + (((2 * (ks & 3) + (lane >> 4)) ^ (lane & 7)) << 4);
        asm volatile("stmatrix.sync.aligned.m8n8.x4.shared.b16 [%0], {%1,%2,%3,%4};" :: "r"(addr),
                     "r"(hsub2_bf(xb[ks - 16][0], mm0)), "r"(hsub2_bf(xb[ks - 16][1], mm1)),
                     "r"(hsub2_bf(xb[ks - 16][2], mm0)), "r"(hsub2_bf(xb[ks - 16][3], mm1)) : "memory");
      }
#pragma unroll
      for (int ks = 0; ks < 16; ks++) {
        xa[ks][0] = hsub2_bf(xa[ks][0], mm0); xa[ks][1] = hsub2_bf(xa[ks][1], mm1);
        xa[ks][2] = hsub2_bf(xa[ks][2], mm0); xa[ks][3] = hsub2_bf(xa[ks][3], mm1);
      }
      const float v0 = fmaxf(fmaf(-m0, m0, q0 * (1.0f / D_MOD)), 0.f), v1 = fmaxf(fmaf(-m1, m1, q1 * (1.0f / D_MOD)), 0.f);
      r0 = 1.0f / bf16r(sqrtf(bf16r(bf16r(v0) + 1e-5f)));
      r1 = 1.0f / bf16r(sqrtf(bf16r(bf16r(v1) + 1e-5f)));
    }
    if (t128 < BF / 2) b1s[t128] = bias_a;
    if (t128 < BN2 / 2) b2s[t128] = bias_b;
    TSC(1);
    fence_async_smem();
    wg_bar(wg);
    if (t128 == 0) mbar_arrive(bar_ln);
    asm volatile("barrier.cluster.arrive.relaxed.aligned;" ::: "memory");
    TSC(2);

    uint32_t h[14][4];
    {
      float acc[112];
#pragma unroll
      for (int kb = 0; kb < 16; kb++) {
        mbar_wait(bar_full + 8 * kb, 0);
        wg_fence();
        const uint32_t abase = sbase + wg * 65536 + (kb >> 1) * 8192 + (kb & 1) * 64;
        const uint32_t bbase = sbase + load_off(kb);
#pragma unroll
        for (int kk = 0; kk < 2; kk++) {
          if (kb < 8) wgmma_rs_n224(acc, xa[2 * kb + kk], make_desc(bbase + kk * 1024, 2048, 512, 2), (kb | kk) != 0);
          else wgmma_ss_n224(acc, make_desc(abase + kk * 32, 16, 1024, 1), make_desc(bbase + kk * 1024, 2048, 512, 2), 1);
        }
        wg_commit();
        if (kb > 0) { wg_wait<1>(); if (t128 == 0) mbar_arrive(bar_cons + 8 * (kb - 1)); }
      }
      wg_wait<0>();
      reg_fence(acc);
      asm volatile("barrier.cluster.wait.aligned;" ::: "memory");
      if (t128 == 0) { mbar_arrive(bar_cons + 8 * 15); mbar_arrive_remote(mapa(bar_peer, (j & 1) ^ 1)); }
      TSC(11);

#pragma unroll
      for (int i = 0; i < 28; i++) {
        const uint32_t bb = b1s[i * 4 + q];
        uint32_t p0 = hadd2_bf(pack_bf16(acc[4 * i] * r0, acc[4 * i + 1] * r0), bb);
        uint32_t p1 = hadd2_bf(pack_bf16(acc[4 * i + 2] * r1, acc[4 * i + 3] * r1), bb);
        h[i >> 1][(i & 1) * 2 + 0] = pack_bf16(gelu_tanh(bf_lo(p0)), gelu_tanh(bf_hi(p0)));
        h[i >> 1][(i & 1) * 2 + 1] = pack_bf16(gelu_tanh(bf_lo(p1)), gelu_tanh(bf_hi(p1)));
      }
    }

    const uint32_t par = (epoch + 1) & 1;
    float acc2[2][32];
    float sum[32];
    uint4 pf[3][4];
    const uint32_t peer_base = mapa(sbase + wg * 8192, (j & 1) ^ 1);
    const uint32_t peer_dfull = mapa(bar_dfull, (j & 1) ^ 1);
    uint4* my_base = reinterpret_cast<uint4*>(smem) + wg * 512 + t128;
    const uint4* in_part = &g_part[(size_t)((mb * NSPLIT + j) * 3) * 1024 + wg * 512 + t128];
    auto ld_part = [&](const uint4* p) {
      uint4 v;
      asm volatile("ld.relaxed.gpu.global.v4.u32 {%0, %1, %2, %3}, [%4];" : "=r"(v.x), "=r"(v.y), "=r"(v.z), "=r"(v.w) : "l"(p) : "memory");
      return v;
    };
    auto prefetch = [&](int k) {
#pragma unroll
      for (int c = 0; c < 4; c++) pf[k][c] = ld_part(in_part + k * 1024 + c * 128);
    };
    auto consume = [&](int k) {
#pragma unroll
      for (int c = 0; c < 4; c++) {
        uint4 v = pf[k][c];
        uint32_t it = 0;
        while ((((v.x ^ par) | (v.y ^ par) | (v.z ^ par) | (v.w ^ par)) & 1u) != 0) {
          v = ld_part(in_part + k * 1024 + c * 128);
          if (++it > (1u << 20)) asm volatile("trap;");
        }
        sum[c * 8 + 0] += bf_lo(v.x & ~1u); sum[c * 8 + 1] += bf_hi(v.x);
        sum[c * 8 + 2] += bf_lo(v.y & ~1u); sum[c * 8 + 3] += bf_hi(v.y);
        sum[c * 8 + 4] += bf_lo(v.z & ~1u); sum[c * 8 + 5] += bf_hi(v.z);
        sum[c * 8 + 6] += bf_lo(v.w & ~1u); sum[c * 8 + 7] += bf_hi(v.w);
      }
    };
    auto post_pack = [&](int st, float (&a)[32], uint4 (&v)[4]) {
      const int kind = step_kind(st), k = step_k(st);
      if (kind == 0) {
#pragma unroll
        for (int c = 0; c < 4; c++) {
          v[c].x = pack_bf16(a[c * 8 + 0], a[c * 8 + 1]); v[c].y = pack_bf16(a[c * 8 + 2], a[c * 8 + 3]);
          v[c].z = pack_bf16(a[c * 8 + 4], a[c * 8 + 5]); v[c].w = pack_bf16(a[c * 8 + 6], a[c * 8 + 7]);
        }
      } else {
#pragma unroll
        for (int c = 0; c < 4; c++) {
          const uint4 d = v[c];
          v[c].x = (pack_bf16(a[c * 8 + 0] + bf_lo(d.x), a[c * 8 + 1] + bf_hi(d.x)) & ~1u) | par;
          v[c].y = (pack_bf16(a[c * 8 + 2] + bf_lo(d.y), a[c * 8 + 3] + bf_hi(d.y)) & ~1u) | par;
          v[c].z = (pack_bf16(a[c * 8 + 4] + bf_lo(d.z), a[c * 8 + 5] + bf_hi(d.z)) & ~1u) | par;
          v[c].w = (pack_bf16(a[c * 8 + 6] + bf_lo(d.w), a[c * 8 + 7] + bf_hi(d.w)) & ~1u) | par;
        }
      }
      (void)k;
    };
    auto post_send = [&](int st, uint4 (&v)[4]) {
      const int kind = step_kind(st), k = step_k(st);
      if (kind == 0) {
        if (st == 0) mbar_wait(bar_cons + 8 * 15, 0);
        if (k >= 2) mbar_wait_cluster(bar_dack + 8 * (k - 2), 0);
#pragma unroll
        for (int c = 0; c < 4; c++) my_base[yslot_off(k & 1) / 16 + c * 128] = v[c];
        fence_async_smem();
        wg_bar(wg);
        if (t128 == 0) {
          if (st == 0) mbar_wait_cluster(bar_peer, 0);
          asm volatile("cp.async.bulk.shared::cluster.shared::cta.mbarrier::complete_tx::bytes [%0], [%1], %2, [%3];"
                       :: "r"(peer_base + uslot_off(k)), "r"(sbase + yslot_off(k & 1) + wg * 8192), "r"(8192), "r"(peer_dfull + 8 * k) : "memory");
        }
      } else {
#pragma unroll
        for (int c = 0; c < 4; c++) my_base[uslot_off(k) / 16 + c * 128] = v[c];
        fence_async_smem();
        wg_bar(wg);
        if (t128 == 0) {
          const int dest = (j + 2 * (k + 1)) & 7;
          const uint4* p = &g_part[(size_t)((mb * NSPLIT + dest) * 3 + k) * 1024 + wg * 512];
          asm volatile("cp.async.bulk.global.shared::cta.bulk_group [%0], [%1], %2;"
                       :: "l"(p), "r"(sbase + uslot_off(k) + wg * 8192), "r"(8192) : "memory");
          asm volatile("cp.async.bulk.commit_group;" ::: "memory");
        }
      }
    };
    auto issue = [&](int i) {
      mbar_wait(bar_full + 8 * (16 + 2 * i), 0);
      wg_fence();
#pragma unroll
      for (int ks = 0; ks < 7; ks++) {
        wgmma_rs_n64(acc2[i & 1], h[ks], make_desc(sbase + load_off(16 + 2 * i) + ks * 2048, 16, 1024, 1), ks != 0);
      }
      mbar_wait(bar_full + 8 * (17 + 2 * i), 0);
      wg_fence();
#pragma unroll
      for (int ks = 0; ks < 7; ks++) {
        wgmma_rs_n64(acc2[i & 1], h[7 + ks], make_desc(sbase + load_off(17 + 2 * i) + ks * 2048, 16, 1024, 1), 1);
      }
      wg_commit();
    };
    TSC(12);
    issue(0);
    issue(1);
#pragma unroll
    for (int i = 0; i < 7; i++) {
      uint4 v[4];
      if (step_kind(i) == 1) {
        mbar_wait_cluster(bar_dfull + 8 * step_k(i), 0);
#pragma unroll
        for (int c = 0; c < 4; c++) v[c] = my_base[uslot_off(step_k(i)) / 16 + c * 128];
      }
      wg_wait<1>();
      reg_fence(acc2[i & 1]);
      post_pack(i, acc2[i & 1], v);
      if (i <= 3 && t128 == 0) { mbar_arrive(bar_cons + 8 * (16 + 2 * i)); mbar_arrive(bar_cons + 8 * (17 + 2 * i)); }
      if (i + 2 < 8) issue(i + 2);
      TSC(13 + i);
      post_send(i, v);
    }
    prefetch(0); prefetch(1); prefetch(2);
    mbar_wait_cluster(bar_dfull + 8 * 3, 0);
#pragma unroll
    for (int c = 0; c < 4; c++) {
      const uint4 d = my_base[uslot_off(3) / 16 + c * 128];
      sum[c * 8 + 0] = bf_lo(d.x); sum[c * 8 + 1] = bf_hi(d.x); sum[c * 8 + 2] = bf_lo(d.y); sum[c * 8 + 3] = bf_hi(d.y);
      sum[c * 8 + 4] = bf_lo(d.z); sum[c * 8 + 5] = bf_hi(d.z); sum[c * 8 + 6] = bf_lo(d.w); sum[c * 8 + 7] = bf_hi(d.w);
    }
    consume(0);
    consume(1);
    wg_wait<0>();
    reg_fence(acc2[1]);
    TSC(20);
    consume(2);
    TSC(21);
    if (tid == 0) g_epoch[blockIdx.x] = epoch + 1;

    {
      const int row0 = mb * BM + wg * 64 + w4 * 16 + g;
      uint32_t* o0 = reinterpret_cast<uint32_t*>(out + (size_t)row0 * D_MOD + j * BN2) + q;
      uint32_t* o1 = o0 + 8 * D_MOD / 2;
#pragma unroll
      for (int i = 0; i < 8; i++) {
        const uint32_t bb = b2s[i * 4 + q];
        o0[i * 4] = hadd2_bf(pack_bf16(acc2[1][4 * i] + sum[4 * i], acc2[1][4 * i + 1] + sum[4 * i + 1]), bb);
        o1[i * 4] = hadd2_bf(pack_bf16(acc2[1][4 * i + 2] + sum[4 * i + 2], acc2[1][4 * i + 3] + sum[4 * i + 3]), bb);
      }
    }
    if (t128 == 0) asm volatile("cp.async.bulk.wait_group 0;" ::: "memory");
    TSC(26);
    TS_FLUSH;
    asm volatile("barrier.cluster.arrive.relaxed.aligned;\nbarrier.cluster.wait.aligned;" ::: "memory");
  }
}

typedef CUresult (*EncodeFn)(CUtensorMap*, CUtensorMapDataType, cuuint32_t, void*, const cuuint64_t*, const cuuint64_t*,
                             const cuuint32_t*, const cuuint32_t*, CUtensorMapInterleave, CUtensorMapSwizzle,
                             CUtensorMapL2promotion, CUtensorMapFloatOOBfill);

}

extern "C" void kernel_launch(void* const* d_in, const int* in_sizes, int n_in, void* d_out, int out_size) {
  (void)in_sizes; (void)n_in; (void)out_size;
  static CUtensorMap tm_x, tm_w1, tm_w2;
  static const void* cached_w1 = nullptr; static const void* cached_w2 = nullptr; static const void* cached_x = nullptr;
  const void* w1 = d_in[1]; const void* w2 = d_in[3]; const void* xp = d_in[0];
  if (cached_w1 != w1 || cached_w2 != w2 || cached_x != xp) {
    void* fn = nullptr; cudaDriverEntryPointQueryResult st;
    cudaGetDriverEntryPoint("cuTensorMapEncodeTiled", &fn, cudaEnableDefault, &st);
    EncodeFn enc = (EncodeFn)fn;
    {
      cuuint64_t dims[3] = {64, (cuuint64_t)S_TOK, (cuuint64_t)(D_MOD / 64)};
      cuuint64_t strides[2] = {(cuuint64_t)D_MOD * 2, 128};
      cuuint32_t box[3] = {64, 64, 2};
      cuuint32_t es[3] = {1, 1, 1};
      enc(&tm_x, CU_TENSOR_MAP_DATA_TYPE_BFLOAT16, 3, const_cast<void*>(xp), dims, strides, box, es,
          CU_TENSOR_MAP_INTERLEAVE_NONE, CU_TENSOR_MAP_SWIZZLE_128B, CU_TENSOR_MAP_L2_PROMOTION_L2_128B, CU_TENSOR_MAP_FLOAT_OOB_FILL_NONE);
    }
    {
      cuuint64_t dims[3] = {32, (cuuint64_t)D_MOD, (cuuint64_t)(F_HID / 32)};
      cuuint64_t strides[2] = {(cuuint64_t)F_HID * 2, 64};
      cuuint32_t box[3] = {32, 32, 7};
      cuuint32_t es[3] = {1, 1, 1};
      enc(&tm_w1, CU_TENSOR_MAP_DATA_TYPE_BFLOAT16, 3, const_cast<void*>(w1), dims, strides, box, es,
          CU_TENSOR_MAP_INTERLEAVE_NONE, CU_TENSOR_MAP_SWIZZLE_64B, CU_TENSOR_MAP_L2_PROMOTION_L2_128B, CU_TENSOR_MAP_FLOAT_OOB_FILL_NONE);
    }
    {
      cuuint64_t dims[2] = {(cuuint64_t)D_MOD, (cuuint64_t)F_HID};
      cuuint64_t strides[1] = {(cuuint64_t)D_MOD * 2};
      cuuint32_t box[2] = {64, 112};
      cuuint32_t es[2] = {1, 1};
      enc(&tm_w2, CU_TENSOR_MAP_DATA_TYPE_BFLOAT16, 2, const_cast<void*>(w2), dims, strides, box, es,
          CU_TENSOR_MAP_INTERLEAVE_NONE, CU_TENSOR_MAP_SWIZZLE_128B, CU_TENSOR_MAP_L2_PROMOTION_L2_128B, CU_TENSOR_MAP_FLOAT_OOB_FILL_NONE);
    }
    cudaFuncSetAttribute(fused_mlp_kernel, cudaFuncAttributeMaxDynamicSharedMemorySize, SMEM_TOTAL);
    cached_w1 = w1; cached_w2 = w2; cached_x = xp;
  }
  fused_mlp_kernel<<<NMB * NSPLIT, NTHREADS, SMEM_TOTAL>>>(tm_x, tm_w1, tm_w2,
      (const __nv_bfloat16*)d_in[1], (const __nv_bfloat16*)d_in[3], (const __nv_bfloat16*)d_in[2], (const __nv_bfloat16*)d_in[4], (__nv_bfloat16*)d_out);
}
```

```cpp
#include <cuda_runtime.h>
#include <cuda_bf16.h>
#include <cuda.h>
#include <stdint.h>

namespace {

constexpr int S_TOK = 2048, D_MOD = 512, F_HID = 1792;
constexpr int BM = 128, NSPLIT = 8, BF = F_HID / NSPLIT;
constexpr int BN2 = D_MOD / NSPLIT;
constexpr int NMB = S_TOK / BM;
constexpr int SLOT_BYTES = 16384;
constexpr int W1_BYTES = 14336;
constexpr int W2_BYTES = 14336;
constexpr int Y_BYTES = BM * D_MOD * 2;
constexpr int NRING = 6;
constexpr int NLOAD = 32;
constexpr int OFF_RING = Y_BYTES;
__host__ __device__ constexpr int yslot_off(int s) { return (s >> 1) * 65536 + (s & 1) * 16384; }
__host__ __device__ constexpr int uslot_off(int s) { return (s >> 1) * 65536 + 32768 + (s & 1) * 16384; }
constexpr int DSLOT_BYTES = 16384;
constexpr int OFF_BAR = OFF_RING + NRING * SLOT_BYTES;
constexpr int OFF_MEAN = OFF_BAR + 640;
constexpr int OFF_B1 = OFF_MEAN + 512;
constexpr int OFF_B2 = OFF_B1 + 1024;
constexpr int SMEM_TOTAL = OFF_B2 + 256;
constexpr int NTHREADS = 384;
static_assert(SMEM_TOTAL <= 232448, "smem");

__device__ uint4 g_part[(size_t)NMB * NSPLIT * 3 * 1024];
__device__ unsigned int g_epoch[NMB * NSPLIT];

#define TS_DECL
#define TS_FLUSH do {} while (0)
#define TS(role, idx) do {} while (0)
#define TSC(idx) do {} while (0)

__device__ __forceinline__ uint32_t smem_u32(const void* p) { return (uint32_t)__cvta_generic_to_shared(p); }
__device__ __forceinline__ uint32_t mapa(uint32_t a, uint32_t r) {
  uint32_t d; asm volatile("mapa.shared::cluster.u32 %0, %1, %2;" : "=r"(d) : "r"(a), "r"(r)); return d;
}
__device__ __forceinline__ void mbar_init(uint32_t bar, uint32_t cnt) {
  asm volatile("mbarrier.init.shared::cta.b64 [%0], %1;" :: "r"(bar), "r"(cnt) : "memory");
}
__device__ __forceinline__ void mbar_expect_tx(uint32_t bar, uint32_t bytes) {
  asm volatile("mbarrier.arrive.expect_tx.shared::cta.b64 _, [%0], %1;" :: "r"(bar), "r"(bytes) : "memory");
}
__device__ __forceinline__ void mbar_arrive(uint32_t bar) {
  asm volatile("mbarrier.arrive.shared::cta.b64 _, [%0];" :: "r"(bar) : "memory");
}
__device__ __forceinline__ void mbar_arrive_remote(uint32_t rbar) {
  asm volatile("mbarrier.arrive.release.cluster.shared::cluster.b64 _, [%0];" :: "r"(rbar) : "memory");
}
__device__ __forceinline__ void mbar_wait(uint32_t bar, uint32_t parity) {
  uint32_t done = 0; uint32_t it = 0;
  while (true) {
    asm volatile("{\n.reg .pred p;\nmbarrier.try_wait.parity.shared::cta.b64 p, [%1], %2;\nselp.u32 %0, 1, 0, p;\n}"
                 : "=r"(done) : "r"(bar), "r"(parity) : "memory");
    if (done) break;
    if (++it > (1u << 22)) asm volatile("trap;");
  }
}
__device__ __forceinline__ void mbar_wait_cluster(uint32_t bar, uint32_t parity) {
  uint32_t done = 0; uint32_t it = 0;
  while (true) {
    asm volatile("{\n.reg .pred p;\nmbarrier.try_wait.parity.acquire.cluster.shared::cta.b64 p, [%1], %2;\nselp.u32 %0, 1, 0, p;\n}"
                 : "=r"(done) : "r"(bar), "r"(parity) : "memory");
    if (done) break;
    if (++it > (1u << 22)) asm volatile("trap;");
  }
}
__device__ __forceinline__ void tma_load_3d(uint32_t dst, const CUtensorMap* tm, int c0, int c1, int c2, uint32_t bar) {
  asm volatile("cp.async.bulk.tensor.3d.shared::cluster.global.mbarrier::complete_tx::bytes [%0], [%1, {%3, %4, %5}], [%2];"
               :: "r"(dst), "l"(tm), "r"(bar), "r"(c0), "r"(c1), "r"(c2) : "memory");
}
__device__ __forceinline__ void tma_load_2d(uint32_t dst, const CUtensorMap* tm, int c0, int c1, uint32_t bar) {
  asm volatile("cp.async.bulk.tensor.2d.shared::cluster.global.mbarrier::complete_tx::bytes [%0], [%1, {%3, %4}], [%2];"
               :: "r"(dst), "l"(tm), "r"(bar), "r"(c0), "r"(c1) : "memory");
}
__device__ __forceinline__ void tma_prefetch_2d(const CUtensorMap* tm, int c0, int c1) {
  asm volatile("cp.async.bulk.prefetch.tensor.2d.L2.global.tile [%0, {%1, %2}];" :: "l"(tm), "r"(c0), "r"(c1) : "memory");
}
__device__ __forceinline__ void fence_async_smem() { asm volatile("fence.proxy.async.shared::cta;" ::: "memory"); }
__device__ __forceinline__ void wg_bar(int wg) {
  if (wg == 0) asm volatile("bar.sync 1, 128;" ::: "memory"); else asm volatile("bar.sync 2, 128;" ::: "memory");
}
__device__ __forceinline__ void wg_fence() { asm volatile("wgmma.fence.sync.aligned;" ::: "memory"); }
__device__ __forceinline__ void wg_commit() { asm volatile("wgmma.commit_group.sync.aligned;" ::: "memory"); }
template <int N> __device__ __forceinline__ void wg_wait() { asm volatile("wgmma.wait_group.sync.aligned %0;" :: "n"(N) : "memory"); }
template <int N> __device__ __forceinline__ void reg_fence(float (&d)[N]) {
#pragma unroll
  for (int i = 0; i < N; i++) asm volatile("" : "+f"(d[i]) :: "memory");
}
__device__ __forceinline__ uint64_t make_desc(uint32_t addr, uint32_t lbo, uint32_t sbo, uint32_t lt) {
  return (uint64_t)((addr & 0x3FFFF) >> 4) | ((uint64_t)(lbo >> 4) << 16) | ((uint64_t)(sbo >> 4) << 32) | ((uint64_t)lt << 62);
}
__device__ __forceinline__ uint32_t pack_bf16(float lo, float hi) {
  uint32_t r; asm("cvt.rn.bf16x2.f32 %0, %1, %2;" : "=r"(r) : "f"(hi), "f"(lo)); return r;
}
__device__ __forceinline__ float bf_lo(uint32_t v) { return __uint_as_float(v << 16); }
__device__ __forceinline__ float bf_hi(uint32_t v) { return __uint_as_float(v & 0xffff0000u); }
__device__ __forceinline__ float bf16r(float v) { return __bfloat162float(__float2bfloat16_rn(v)); }
__device__ __forceinline__ uint32_t hadd2_bf(uint32_t a, uint32_t b) {
  uint32_t r; asm("add.rn.bf16x2 %0, %1, %2;" : "=r"(r) : "r"(a), "r"(b)); return r;
}
__device__ __forceinline__ uint32_t hsub2_bf(uint32_t a, uint32_t b) {
  uint32_t r; asm("sub.rn.bf16x2 %0, %1, %2;" : "=r"(r) : "r"(a), "r"(b)); return r;
}
__device__ __forceinline__ float gelu_tanh(float u) {
  float inner = u * fmaf(0.035677408136300125f, u * u, 0.7978845608028654f);
  float th; asm("tanh.approx.f32 %0, %1;" : "=f"(th) : "f"(inner));
  float hu = 0.5f * u;
  return fmaf(hu, th, hu);
}
__device__ __forceinline__ void mma16816(float (&c)[4], uint32_t a0, uint32_t a1, uint32_t a2, uint32_t a3, uint32_t b0, uint32_t b1) {
  asm volatile("mma.sync.aligned.m16n8k16.row.col.f32.bf16.bf16.f32 {%0,%1,%2,%3}, {%4,%5,%6,%7}, {%8,%9}, {%0,%1,%2,%3};"
               : "+f"(c[0]), "+f"(c[1]), "+f"(c[2]), "+f"(c[3]) : "r"(a0), "r"(a1), "r"(a2), "r"(a3), "r"(b0), "r"(b1));
}

__device__ __forceinline__ void wgmma_ss_n224(float (&d)[112], uint64_t descA, uint64_t descB, int scaleD) {
  asm volatile("{\n.reg .pred p;\nsetp.ne.b32 p, %114, 0;\n"
    "wgmma.mma_async.sync.aligned.m64n224k16.f32.bf16.bf16 {%0, %1, %2, %3, %4, %5, %6, %7, %8, %9, %10, %11, %12, %13, %14, %15, %16, %17, %18, %19, %20, %21, %22, %23, %24, %25, %26, %27, %28, %29, %30, %31, %32, %33, %34, %35, %36, %37, %38, %39, %40, %41, %42, %43, %44, %45, %46, %47, %48, %49, %50, %51, %52, %53, %54, %55, %56, %57, %58, %59, %60, %61, %62, %63, %64, %65, %66, %67, %68, %69, %70, %71, %72, %73, %74, %75, %76, %77, %78, %79, %80, %81, %82, %83, %84, %85, %86, %87, %88, %89, %90, %91, %92, %93, %94, %95, %96, %97, %98, %99, %100, %101, %102, %103, %104, %105, %106, %107, %108, %109, %110, %111}, %112, %113, p, 1, 1, 0, 1;\n}\n"
    : "+f"(d[0]), "+f"(d[1]), "+f"(d[2]), "+f"(d[3]), "+f"(d[4]), "+f"(d[5]), "+f"(d[6]), "+f"(d[7]), "+f"(d[8]), "+f"(d[9]), "+f"(d[10]), "+f"(d[11]), "+f"(d[12]), "+f"(d[13]), "+f"(d[14]), "+f"(d[15]), "+f"(d[16]), "+f"(d[17]), "+f"(d[18]), "+f"(d[19]), "+f"(d[20]), "+f"(d[21]), "+f"(d[22]), "+f"(d[23]), "+f"(d[24]), "+f"(d[25]), "+f"(d[26]), "+f"(d[27]), "+f"(d[28]), "+f"(d[29]), "+f"(d[30]), "+f"(d[31]), "+f"(d[32]), "+f"(d[33]), "+f"(d[34]), "+f"(d[35]), "+f"(d[36]), "+f"(d[37]), "+f"(d[38]), "+f"(d[39]), "+f"(d[40]), "+f"(d[41]), "+f"(d[42]), "+f"(d[43]), "+f"(d[44]), "+f"(d[45]), "+f"(d[46]), "+f"(d[47]), "+f"(d[48]), "+f"(d[49]), "+f"(d[50]), "+f"(d[51]), "+f"(d[52]), "+f"(d[53]), "+f"(d[54]), "+f"(d[55]), "+f"(d[56]), "+f"(d[57]), "+f"(d[58]), "+f"(d[59]), "+f"(d[60]), "+f"(d[61]), "+f"(d[62]), "+f"(d[63]), "+f"(d[64]), "+f"(d[65]), "+f"(d[66]), "+f"(d[67]), "+f"(d[68]), "+f"(d[69]), "+f"(d[70]), "+f"(d[71]), "+f"(d[72]), "+f"(d[73]), "+f"(d[74]), "+f"(d[75]), "+f"(d[76]), "+f"(d[77]), "+f"(d[78]), "+f"(d[79]), "+f"(d[80]), "+f"(d[81]), "+f"(d[82]), "+f"(d[83]), "+f"(d[84]), "+f"(d[85]), "+f"(d[86]), "+f"(d[87]), "+f"(d[88]), "+f"(d[89]), "+f"(d[90]), "+f"(d[91]), "+f"(d[92]), "+f"(d[93]), "+f"(d[94]), "+f"(d[95]), "+f"(d[96]), "+f"(d[97]), "+f"(d[98]), "+f"(d[99]), "+f"(d[100]), "+f"(d[101]), "+f"(d[102]), "+f"(d[103]), "+f"(d[104]), "+f"(d[105]), "+f"(d[106]), "+f"(d[107]), "+f"(d[108]), "+f"(d[109]), "+f"(d[110]), "+f"(d[111])
    : "l"(descA), "l"(descB), "r"(scaleD));
}

__device__ __forceinline__ void wgmma_rs_n64(float (&d)[32], const uint32_t (&a)[4], uint64_t descB, int scaleD) {
  asm volatile("{\n.reg .pred p;\nsetp.ne.b32 p, %37, 0;\n"
    "wgmma.mma_async.sync.aligned.m64n64k16.f32.bf16.bf16 {%0, %1, %2, %3, %4, %5, %6, %7, %8, %9, %10, %11, %12, %13, %14, %15, %16, %17, %18, %19, %20, %21, %22, %23, %24, %25, %26, %27, %28, %29, %30, %31}, {%32, %33, %34, %35}, %36, p, 1, 1, 1;\n}\n"
    : "+f"(d[0]), "+f"(d[1]), "+f"(d[2]), "+f"(d[3]), "+f"(d[4]), "+f"(d[5]), "+f"(d[6]), "+f"(d[7]), "+f"(d[8]), "+f"(d[9]), "+f"(d[10]), "+f"(d[11]), "+f"(d[12]), "+f"(d[13]), "+f"(d[14]), "+f"(d[15]), "+f"(d[16]), "+f"(d[17]), "+f"(d[18]), "+f"(d[19]), "+f"(d[20]), "+f"(d[21]), "+f"(d[22]), "+f"(d[23]), "+f"(d[24]), "+f"(d[25]), "+f"(d[26]), "+f"(d[27]), "+f"(d[28]), "+f"(d[29]), "+f"(d[30]), "+f"(d[31])
    : "r"(a[0]), "r"(a[1]), "r"(a[2]), "r"(a[3]), "l"(descB), "r"(scaleD));
}

__device__ __forceinline__ void wgmma_rs_n224(float (&d)[112], const uint32_t (&a)[4], uint64_t descB, int scaleD) {
  asm volatile("{\n.reg .pred p;\nsetp.ne.b32 p, %117, 0;\n"
    "wgmma.mma_async.sync.aligned.m64n224k16.f32.bf16.bf16 {%0, %1, %2, %3, %4, %5, %6, %7, %8, %9, %10, %11, %12, %13, %14, %15, %16, %17, %18, %19, %20, %21, %22, %23, %24, %25, %26, %27, %28, %29, %30, %31, %32, %33, %34, %35, %36, %37, %38, %39, %40, %41, %42, %43, %44, %45, %46, %47, %48, %49, %50, %51, %52, %53, %54, %55, %56, %57, %58, %59, %60, %61, %62, %63, %64, %65, %66, %67, %68, %69, %70, %71, %72, %73, %74, %75, %76, %77, %78, %79, %80, %81, %82, %83, %84, %85, %86, %87, %88, %89, %90, %91, %92, %93, %94, %95, %96, %97, %98, %99, %100, %101, %102, %103, %104, %105, %106, %107, %108, %109, %110, %111}, {%112, %113, %114, %115}, %116, p, 1, 1, 1;\n}\n"
    : "+f"(d[0]), "+f"(d[1]), "+f"(d[2]), "+f"(d[3]), "+f"(d[4]), "+f"(d[5]), "+f"(d[6]), "+f"(d[7]), "+f"(d[8]), "+f"(d[9]), "+f"(d[10]), "+f"(d[11]), "+f"(d[12]), "+f"(d[13]), "+f"(d[14]), "+f"(d[15]), "+f"(d[16]), "+f"(d[17]), "+f"(d[18]), "+f"(d[19]), "+f"(d[20]), "+f"(d[21]), "+f"(d[22]), "+f"(d[23]), "+f"(d[24]), "+f"(d[25]), "+f"(d[26]), "+f"(d[27]), "+f"(d[28]), "+f"(d[29]), "+f"(d[30]), "+f"(d[31]), "+f"(d[32]), "+f"(d[33]), "+f"(d[34]), "+f"(d[35]), "+f"(d[36]), "+f"(d[37]), "+f"(d[38]), "+f"(d[39]), "+f"(d[40]), "+f"(d[41]), "+f"(d[42]), "+f"(d[43]), "+f"(d[44]), "+f"(d[45]), "+f"(d[46]), "+f"(d[47]), "+f"(d[48]), "+f"(d[49]), "+f"(d[50]), "+f"(d[51]), "+f"(d[52]), "+f"(d[53]), "+f"(d[54]), "+f"(d[55]), "+f"(d[56]), "+f"(d[57]), "+f"(d[58]), "+f"(d[59]), "+f"(d[60]), "+f"(d[61]), "+f"(d[62]), "+f"(d[63]), "+f"(d[64]), "+f"(d[65]), "+f"(d[66]), "+f"(d[67]), "+f"(d[68]), "+f"(d[69]), "+f"(d[70]), "+f"(d[71]), "+f"(d[72]), "+f"(d[73]), "+f"(d[74]), "+f"(d[75]), "+f"(d[76]), "+f"(d[77]), "+f"(d[78]), "+f"(d[79]), "+f"(d[80]), "+f"(d[81]), "+f"(d[82]), "+f"(d[83]), "+f"(d[84]), "+f"(d[85]), "+f"(d[86]), "+f"(d[87]), "+f"(d[88]), "+f"(d[89]), "+f"(d[90]), "+f"(d[91]), "+f"(d[92]), "+f"(d[93]), "+f"(d[94]), "+f"(d[95]), "+f"(d[96]), "+f"(d[97]), "+f"(d[98]), "+f"(d[99]), "+f"(d[100]), "+f"(d[101]), "+f"(d[102]), "+f"(d[103]), "+f"(d[104]), "+f"(d[105]), "+f"(d[106]), "+f"(d[107]), "+f"(d[108]), "+f"(d[109]), "+f"(d[110]), "+f"(d[111])
    : "r"(a[0]), "r"(a[1]), "r"(a[2]), "r"(a[3]), "l"(descB), "r"(scaleD));
}

__host__ __device__ constexpr int step_kind(int i) { return (i < 3 || i == 6) ? 0 : (i == 7 ? 2 : 1); }
__host__ __device__ constexpr int step_k(int i) { return i < 3 ? i : (i < 6 ? i - 3 : 3); }
__device__ __forceinline__ int step_slice(int i, int j) {
  const int kind = step_kind(i), k = step_k(i);
  const int base = (kind == 0) ? (j ^ 1) : j;
  return (k == 3) ? base : ((base + 2 * (k + 1)) & 7);
}

__host__ __device__ constexpr int load_off(int i) {
  return i < 6 ? OFF_RING + i * SLOT_BYTES
       : i < 10 ? yslot_off(i - 6)
       : i < 16 ? OFF_RING + (i - 10) * SLOT_BYTES
       : i < 18 ? yslot_off(i - 14)
       : i < 24 ? OFF_RING + (i - 18) * SLOT_BYTES
       : i < 26 ? yslot_off(i - 22)
       : OFF_RING + (i - 26) * SLOT_BYTES;
}
__host__ __device__ constexpr int load_dep(int i) { return i < 6 ? -1 : (i < 10 ? -2 : (i < 16 ? i - 10 : i - 8)); }

__global__ void __cluster_dims__(2, 1, 1) __launch_bounds__(NTHREADS, 1)
fused_mlp_kernel(const __grid_constant__ CUtensorMap tm_x, const __grid_constant__ CUtensorMap tm_w1, const __grid_constant__ CUtensorMap tm_w2,
                 const __nv_bfloat16* __restrict__ w1, const __nv_bfloat16* __restrict__ w2,
                 const __nv_bfloat16* __restrict__ b1, const __nv_bfloat16* __restrict__ b2, __nv_bfloat16* __restrict__ out)
{
  extern __shared__ __align__(1024) unsigned char smem[];
  const uint32_t sbase = smem_u32(smem);
  const uint32_t bar_full = sbase + OFF_BAR;
  const uint32_t bar_cons = sbase + OFF_BAR + 256;
  const uint32_t bar_dfull = sbase + OFF_BAR + 528;
  const uint32_t bar_peer = sbase + OFF_BAR + 560;
  const uint32_t bar_x = sbase + OFF_BAR + 592;
  const uint32_t bar_ln = sbase + OFF_BAR + 568;
  const uint32_t bar_dack = sbase + OFF_BAR + 576;
  const int tid = threadIdx.x, warp = tid >> 5, lane = tid & 31;
  const int mb = blockIdx.x >> 3, j = blockIdx.x & 7;

  TS_DECL
  TSC(0);
  if (warp >= 8) {
    asm volatile("setmaxnreg.dec.sync.aligned.u32 40;");
  if (warp == 8) {
    mbar_init(bar_full + 8 * lane, 1); mbar_init(bar_cons + 8 * lane, 2);
    if (lane < 4) mbar_init(bar_dfull + 8 * lane, 1);
    if (lane == 4) mbar_init(bar_peer, 2);
    if (lane == 5) mbar_init(bar_ln, 2);
    if (lane >= 8 && lane < 12) mbar_init(bar_x + 8 * (lane - 8), 1);
    if (lane == 6 || lane == 7) mbar_init(bar_dack + 8 * (lane - 6), 1);
    asm volatile("fence.mbarrier_init.release.cluster;" ::: "memory");
    fence_async_smem();
    __syncwarp();
    if (lane >= 4 && lane < 8) mbar_expect_tx(bar_dfull + 8 * (lane - 4), DSLOT_BYTES);
    __syncwarp();
  }
    asm volatile("bar.sync 0, 384;" ::: "memory");
    if (warp == 8 && lane == 0) {
      for (int kq = 0; kq < 4; kq++) {
        mbar_expect_tx(bar_x + 8 * kq, 32768);
        tma_load_3d(sbase + kq * 16384, &tm_x, 0, mb * BM, 2 * kq, bar_x + 8 * kq);
        tma_load_3d(sbase + 65536 + kq * 16384, &tm_x, 0, mb * BM + 64, 2 * kq, bar_x + 8 * kq);
      }
      for (int i = 0; i < NRING; i++) {
        mbar_expect_tx(bar_full + 8 * i, W1_BYTES);
        tma_load_3d(sbase + OFF_RING + i * SLOT_BYTES, &tm_w1, 0, i * 32, j * 7, bar_full + 8 * i);
      }
      asm volatile("cp.async.bulk.prefetch.L2.global [%0], %1;" :: "l"(reinterpret_cast<const unsigned char*>(w1) + (size_t)blockIdx.x * 14336), "r"(14336) : "memory");
      asm volatile("cp.async.bulk.prefetch.L2.global [%0], %1;" :: "l"(reinterpret_cast<const unsigned char*>(w2) + (size_t)blockIdx.x * 14336), "r"(14336) : "memory");
      TS(2, 1);
    }
    __syncwarp();
    asm volatile("barrier.cluster.arrive.relaxed.aligned;" ::: "memory");
    if (warp == 8 && lane == 0) {
#pragma unroll
      for (int i = NRING; i < NLOAD; i++) {
        if (load_dep(i) >= 0) mbar_wait(bar_cons + 8 * load_dep(i), 0); else if (i == NRING) mbar_wait(bar_ln, 0);
        TS(2, i);
        const uint32_t dst = sbase + load_off(i);
        if (i < 16) {
          mbar_expect_tx(bar_full + 8 * i, W1_BYTES);
          tma_load_3d(dst, &tm_w1, 0, i * 32, j * 7, bar_full + 8 * i);
        } else {
          mbar_expect_tx(bar_full + 8 * i, W2_BYTES);
          tma_load_2d(dst, &tm_w2, step_slice((i - 16) >> 1, j) * BN2, j * BF + ((i - 16) & 1) * 112, bar_full + 8 * i);
        }
      }
    }
    __syncwarp();
    asm volatile("barrier.cluster.wait.aligned;" ::: "memory");
    if (warp == 9 && lane == 0) {
      for (int k = 0; k < 2; k++) {
        mbar_wait_cluster(bar_dfull + 8 * k, 0);
        mbar_arrive_remote(mapa(bar_dack + 8 * k, (j & 1) ^ 1));
      }
    }
    __syncwarp();
    asm volatile("barrier.cluster.arrive.relaxed.aligned;\nbarrier.cluster.wait.aligned;" ::: "memory");
  } else {
    asm volatile("setmaxnreg.inc.sync.aligned.u32 232;");
    asm volatile("bar.sync 0, 384;" ::: "memory");
    TSC(29);
    const int wg = warp >> 2, w4 = warp & 3, t128 = tid & 127;
    const int q = lane & 3, g = lane >> 2;
    uint32_t* b1s = reinterpret_cast<uint32_t*>(smem + OFF_B1 + wg * 512);
    uint32_t* b2s = reinterpret_cast<uint32_t*>(smem + OFF_B2 + wg * 128);
    uint32_t bias_a = 0, bias_b = 0, epoch;

    float r0, r1;
    uint32_t xa[16][4];
    TSC(24);
    {
      uint32_t xb[16][4];
      float cs[2][4], c0[2][4], c1[2][4];
#pragma unroll
      for (int u = 0; u < 2; u++)
#pragma unroll
        for (int e = 0; e < 4; e++) { cs[u][e] = 0.f; c0[u][e] = 0.f; c1[u][e] = 0.f; }
      const int lrow = w4 * 16 + (lane & 7) + ((lane >> 3) & 1) * 8;
      const uint32_t lbase = sbase + wg * 65536 + lrow * 128;
      const uint32_t ones = 0x3F803F80u;
#pragma unroll
      for (int ks = 0; ks < 32; ks++) {
        if ((ks & 7) == 0) { mbar_wait(bar_x + 8 * (ks >> 3), 0); if (ks == 0) TSC(25); if (ks == 24) TSC(22); }
        uint32_t (&a)[4] = ks < 16 ? xa[ks] : xb[ks - 16];
        const uint32_t addr = lbase + (ks >> 2) * 8192 + (((2 * (ks & 3) + (lane >> 4)) ^ (lane & 7)) << 4);
        asm volatile("ldmatrix.sync.aligned.m8n8.x4.shared.b16 {%0,%1,%2,%3}, [%4];" : "=r"(a[0]), "=r"(a[1]), "=r"(a[2]), "=r"(a[3]) : "r"(addr));
        mma16816(cs[ks & 1], a[0], a[1], a[2], a[3], ones, ones);
        mma16816(c0[ks & 1], a[0], a[1], a[2], a[3], a[0], a[2]);
        mma16816(c1[ks & 1], a[0], a[1], a[2], a[3], a[1], a[3]);
      }
      TSC(27);
      if (t128 < BF / 2) bias_a = reinterpret_cast<const uint32_t*>(b1 + j * BF)[t128];
      if (t128 < BN2 / 2) bias_b = reinterpret_cast<const uint32_t*>(b2 + j * BN2)[t128];
      epoch = g_epoch[blockIdx.x];
      const int dsrc = g * 4 + (g >> 1);
      const float q0 = __shfl_sync(0xffffffffu, (g & 1) ? c0[0][1] + c0[1][1] : c0[0][0] + c0[1][0], dsrc);
      const float q1 = __shfl_sync(0xffffffffu, (g & 1) ? c1[0][3] + c1[1][3] : c1[0][2] + c1[1][2], dsrc);
      const float m0 = (cs[0][0] + cs[1][0]) * (1.0f / D_MOD), m1 = (cs[0][2] + cs[1][2]) * (1.0f / D_MOD);
      const uint32_t mm0 = pack_bf16(m0, m0), mm1 = pack_bf16(m1, m1);
#pragma unroll
      for (int ks = 16; ks < 32; ks++) {
        const uint32_t addr = lbase + (ks >> 2) * 8192 + (((2 * (ks & 3) + (lane >> 4)) ^ (lane & 7)) << 4);
        asm volatile("stmatrix.sync.aligned.m8n8.x4.shared.b16 [%0], {%1,%2,%3,%4};" :: "r"(addr),
                     "r"(hsub2_bf(xb[ks - 16][0], mm0)), "r"(hsub2_bf(xb[ks - 16][1], mm1)),
                     "r"(hsub2_bf(xb[ks - 16][2], mm0)), "r"(hsub2_bf(xb[ks - 16][3], mm1)) : "memory");
      }
#pragma unroll
      for (int ks = 0; ks < 16; ks++) {
        xa[ks][0] = hsub2_bf(xa[ks][0], mm0); xa[ks][1] = hsub2_bf(xa[ks][1], mm1);
        xa[ks][2] = hsub2_bf(xa[ks][2], mm0); xa[ks][3] = hsub2_bf(xa[ks][3], mm1);
      }
      const float v0 = fmaxf(fmaf(-m0, m0, q0 * (1.0f / D_MOD)), 0.f), v1 = fmaxf(fmaf(-m1, m1, q1 * (1.0f / D_MOD)), 0.f);
      r0 = 1.0f / bf16r(sqrtf(bf16r(bf16r(v0) + 1e-5f)));
      r1 = 1.0f / bf16r(sqrtf(bf16r(bf16r(v1) + 1e-5f)));
    }
    TSC(1);
    fence_async_smem();
    wg_bar(wg);
    if (t128 == 0) mbar_arrive(bar_ln);
    asm volatile("barrier.cluster.arrive.relaxed.aligned;" ::: "memory");
    TSC(2);

    uint32_t h[14][4];
    {
      float acc[112];
#pragma unroll
      for (int kb = 0; kb < 16; kb++) {
        mbar_wait(bar_full + 8 * kb, 0);
        wg_fence();
        const uint32_t abase = sbase + wg * 65536 + (kb >> 1) * 8192 + (kb & 1) * 64;
        const uint32_t bbase = sbase + load_off(kb);
#pragma unroll
        for (int kk = 0; kk < 2; kk++) {
          if (kb < 8) wgmma_rs_n224(acc, xa[2 * kb + kk], make_desc(bbase + kk * 1024, 2048, 512, 2), (kb | kk) != 0);
          else wgmma_ss_n224(acc, make_desc(abase + kk * 32, 16, 1024, 1), make_desc(bbase + kk * 1024, 2048, 512, 2), 1);
        }
        wg_commit();
        if (kb > 0) { wg_wait<1>(); if (t128 == 0) mbar_arrive(bar_cons + 8 * (kb - 1)); }
      }
      if (t128 < BF / 2) b1s[t128] = bias_a;
      if (t128 < BN2 / 2) b2s[t128] = bias_b;
      wg_bar(wg);
      wg_wait<0>();
      reg_fence(acc);
      asm volatile("barrier.cluster.wait.aligned;" ::: "memory");
      if (t128 == 0) { mbar_arrive(bar_cons + 8 * 15); mbar_arrive_remote(mapa(bar_peer, (j & 1) ^ 1)); }
      TSC(11);

#pragma unroll
      for (int i = 0; i < 28; i++) {
        const uint32_t bb = b1s[i * 4 + q];
        uint32_t p0 = hadd2_bf(pack_bf16(acc[4 * i] * r0, acc[4 * i + 1] * r0), bb);
        uint32_t p1 = hadd2_bf(pack_bf16(acc[4 * i + 2] * r1, acc[4 * i + 3] * r1), bb);
        h[i >> 1][(i & 1) * 2 + 0] = pack_bf16(gelu_tanh(bf_lo(p0)), gelu_tanh(bf_hi(p0)));
        h[i >> 1][(i & 1) * 2 + 1] = pack_bf16(gelu_tanh(bf_lo(p1)), gelu_tanh(bf_hi(p1)));
      }
    }

    const uint32_t par = (epoch + 1) & 1;
    float acc2[2][32];
    float sum[32];
    uint4 pf[3][4];
    const uint32_t peer_base = mapa(sbase + wg * 8192, (j & 1) ^ 1);
    const uint32_t peer_dfull = mapa(bar_dfull, (j & 1) ^ 1);
    uint4* my_base = reinterpret_cast<uint4*>(smem) + wg * 512 + t128;
    const uint4* in_part = &g_part[(size_t)((mb * NSPLIT + j) * 3) * 1024 + wg * 512 + t128];
    auto ld_part = [&](const uint4* p) {
      uint4 v;
      asm volatile("ld.relaxed.gpu.global.v4.u32 {%0, %1, %2, %3}, [%4];" : "=r"(v.x), "=r"(v.y), "=r"(v.z), "=r"(v.w) : "l"(p) : "memory");
      return v;
    };
    auto prefetch = [&](int k) {
#pragma unroll
      for (int c = 0; c < 4; c++) pf[k][c] = ld_part(in_part + k * 1024 + c * 128);
    };
    auto consume = [&](int k) {
#pragma unroll
      for (int c = 0; c < 4; c++) {
        uint4 v = pf[k][c];
        uint32_t it = 0;
        while ((((v.x ^ par) | (v.y ^ par) | (v.z ^ par) | (v.w ^ par)) & 1u) != 0) {
          v = ld_part(in_part + k * 1024 + c * 128);
          if (++it > (1u << 20)) asm volatile("trap;");
        }
        sum[c * 8 + 0] += bf_lo(v.x & ~1u); sum[c * 8 + 1] += bf_hi(v.x);
        sum[c * 8 + 2] += bf_lo(v.y & ~1u); sum[c * 8 + 3] += bf_hi(v.y);
        sum[c * 8 + 4] += bf_lo(v.z & ~1u); sum[c * 8 + 5] += bf_hi(v.z);
        sum[c * 8 + 6] += bf_lo(v.w & ~1u); sum[c * 8 + 7] += bf_hi(v.w);
      }
    };
    auto post_pack = [&](int st, float (&a)[32], uint4 (&v)[4]) {
      const int kind = step_kind(st), k = step_k(st);
      if (kind == 0) {
#pragma unroll
        for (int c = 0; c < 4; c++) {
          v[c].x = pack_bf16(a[c * 8 + 0], a[c * 8 + 1]); v[c].y = pack_bf16(a[c * 8 + 2], a[c * 8 + 3]);
          v[c].z = pack_bf16(a[c * 8 + 4], a[c * 8 + 5]); v[c].w = pack_bf16(a[c * 8 + 6], a[c * 8 + 7]);
        }
      } else {
#pragma unroll
        for (int c = 0; c < 4; c++) {
          const uint4 d = v[c];
          v[c].x = (pack_bf16(a[c * 8 + 0] + bf_lo(d.x), a[c * 8 + 1] + bf_hi(d.x)) & ~1u) | par;
          v[c].y = (pack_bf16(a[c * 8 + 2] + bf_lo(d.y), a[c * 8 + 3] + bf_hi(d.y)) & ~1u) | par;
          v[c].z = (pack_bf16(a[c * 8 + 4] + bf_lo(d.z), a[c * 8 + 5] + bf_hi(d.z)) & ~1u) | par;
          v[c].w = (pack_bf16(a[c * 8 + 6] + bf_lo(d.w), a[c * 8 + 7] + bf_hi(d.w)) & ~1u) | par;
        }
      }
      (void)k;
    };
    auto post_send = [&](int st, uint4 (&v)[4]) {
      const int kind = step_kind(st), k = step_k(st);
      if (kind == 0) {
        if (st == 0) mbar_wait(bar_cons + 8 * 15, 0);
        if (k >= 2) mbar_wait_cluster(bar_dack + 8 * (k - 2), 0);
#pragma unroll
        for (int c = 0; c < 4; c++) my_base[yslot_off(k & 1) / 16 + c * 128] = v[c];
        fence_async_smem();
        wg_bar(wg);
        if (t128 == 0) {
          if (st == 0) mbar_wait_cluster(bar_peer, 0);
          asm volatile("cp.async.bulk.shared::cluster.shared::cta.mbarrier::complete_tx::bytes [%0], [%1], %2, [%3];"
                       :: "r"(peer_base + uslot_off(k)), "r"(sbase + yslot_off(k & 1) + wg * 8192), "r"(8192), "r"(peer_dfull + 8 * k) : "memory");
        }
      } else {
#pragma unroll
        for (int c = 0; c < 4; c++) my_base[uslot_off(k) / 16 + c * 128] = v[c];
        fence_async_smem();
        wg_bar(wg);
        if (t128 == 0) {
          const int dest = (j + 2 * (k + 1)) & 7;
          const uint4* p = &g_part[(size_t)((mb * NSPLIT + dest) * 3 + k) * 1024 + wg * 512];
          asm volatile("cp.async.bulk.global.shared::cta.bulk_group [%0], [%1], %2;"
                       :: "l"(p), "r"(sbase + uslot_off(k) + wg * 8192), "r"(8192) : "memory");
          asm volatile("cp.async.bulk.commit_group;" ::: "memory");
        }
      }
    };
    auto issue = [&](int i) {
      mbar_wait(bar_full + 8 * (16 + 2 * i), 0);
      wg_fence();
#pragma unroll
      for (int ks = 0; ks < 7; ks++) {
        wgmma_rs_n64(acc2[i & 1], h[ks], make_desc(sbase + load_off(16 + 2 * i) + ks * 2048, 16, 1024, 1), ks != 0);
      }
      mbar_wait(bar_full + 8 * (17 + 2 * i), 0);
      wg_fence();
#pragma unroll
      for (int ks = 0; ks < 7; ks++) {
        wgmma_rs_n64(acc2[i & 1], h[7 + ks], make_desc(sbase + load_off(17 + 2 * i) + ks * 2048, 16, 1024, 1), 1);
      }
      wg_commit();
    };
    TSC(12);
    issue(0);
    issue(1);
#pragma unroll
    for (int i = 0; i < 7; i++) {
      uint4 v[4];
      if (step_kind(i) == 1) {
        mbar_wait_cluster(bar_dfull + 8 * step_k(i), 0);
#pragma unroll
        for (int c = 0; c < 4; c++) v[c] = my_base[uslot_off(step_k(i)) / 16 + c * 128];
      }
      wg_wait<1>();
      reg_fence(acc2[i & 1]);
      post_pack(i, acc2[i & 1], v);
      if (i <= 3 && t128 == 0) { mbar_arrive(bar_cons + 8 * (16 + 2 * i)); mbar_arrive(bar_cons + 8 * (17 + 2 * i)); }
      if (i + 2 < 8) issue(i + 2);
      TSC(13 + i);
      post_send(i, v);
    }
    prefetch(0); prefetch(1); prefetch(2);
    mbar_wait_cluster(bar_dfull + 8 * 3, 0);
#pragma unroll
    for (int c = 0; c < 4; c++) {
      const uint4 d = my_base[uslot_off(3) / 16 + c * 128];
      sum[c * 8 + 0] = bf_lo(d.x); sum[c * 8 + 1] = bf_hi(d.x); sum[c * 8 + 2] = bf_lo(d.y); sum[c * 8 + 3] = bf_hi(d.y);
      sum[c * 8 + 4] = bf_lo(d.z); sum[c * 8 + 5] = bf_hi(d.z); sum[c * 8 + 6] = bf_lo(d.w); sum[c * 8 + 7] = bf_hi(d.w);
    }
    consume(0);
    consume(1);
    wg_wait<0>();
    reg_fence(acc2[1]);
    TSC(20);
    consume(2);
    TSC(21);
    if (tid == 0) g_epoch[blockIdx.x] = epoch + 1;

    {
      const int row0 = mb * BM + wg * 64 + w4 * 16 + g;
      uint32_t* o0 = reinterpret_cast<uint32_t*>(out + (size_t)row0 * D_MOD + j * BN2) + q;
      uint32_t* o1 = o0 + 8 * D_MOD / 2;
#pragma unroll
      for (int i = 0; i < 8; i++) {
        const uint32_t bb = b2s[i * 4 + q];
        o0[i * 4] = hadd2_bf(pack_bf16(acc2[1][4 * i] + sum[4 * i], acc2[1][4 * i + 1] + sum[4 * i + 1]), bb);
        o1[i * 4] = hadd2_bf(pack_bf16(acc2[1][4 * i + 2] + sum[4 * i + 2], acc2[1][4 * i + 3] + sum[4 * i + 3]), bb);
      }
    }
    if (t128 == 0) asm volatile("cp.async.bulk.wait_group 0;" ::: "memory");
    TSC(26);
    TS_FLUSH;
    asm volatile("barrier.cluster.arrive.relaxed.aligned;\nbarrier.cluster.wait.aligned;" ::: "memory");
  }
}

typedef CUresult (*EncodeFn)(CUtensorMap*, CUtensorMapDataType, cuuint32_t, void*, const cuuint64_t*, const cuuint64_t*,
                             const cuuint32_t*, const cuuint32_t*, CUtensorMapInterleave, CUtensorMapSwizzle,
                             CUtensorMapL2promotion, CUtensorMapFloatOOBfill);

}

extern "C" void kernel_launch(void* const* d_in, const int* in_sizes, int n_in, void* d_out, int out_size) {
  (void)in_sizes; (void)n_in; (void)out_size;
  static CUtensorMap tm_x, tm_w1, tm_w2;
  static const void* cached_w1 = nullptr; static const void* cached_w2 = nullptr; static const void* cached_x = nullptr;
  const void* w1 = d_in[1]; const void* w2 = d_in[3]; const void* xp = d_in[0];
  if (cached_w1 != w1 || cached_w2 != w2 || cached_x != xp) {
    void* fn = nullptr; cudaDriverEntryPointQueryResult st;
    cudaGetDriverEntryPoint("cuTensorMapEncodeTiled", &fn, cudaEnableDefault, &st);
    EncodeFn enc = (EncodeFn)fn;
    {
      cuuint64_t dims[3] = {64, (cuuint64_t)S_TOK, (cuuint64_t)(D_MOD / 64)};
      cuuint64_t strides[2] = {(cuuint64_t)D_MOD * 2, 128};
      cuuint32_t box[3] = {64, 64, 2};
      cuuint32_t es[3] = {1, 1, 1};
      enc(&tm_x, CU_TENSOR_MAP_DATA_TYPE_BFLOAT16, 3, const_cast<void*>(xp), dims, strides, box, es,
          CU_TENSOR_MAP_INTERLEAVE_NONE, CU_TENSOR_MAP_SWIZZLE_128B, CU_TENSOR_MAP_L2_PROMOTION_L2_128B, CU_TENSOR_MAP_FLOAT_OOB_FILL_NONE);
    }
    {
      cuuint64_t dims[3] = {32, (cuuint64_t)D_MOD, (cuuint64_t)(F_HID / 32)};
      cuuint64_t strides[2] = {(cuuint64_t)F_HID * 2, 64};
      cuuint32_t box[3] = {32, 32, 7};
      cuuint32_t es[3] = {1, 1, 1};
      enc(&tm_w1, CU_TENSOR_MAP_DATA_TYPE_BFLOAT16, 3, const_cast<void*>(w1), dims, strides, box, es,
          CU_TENSOR_MAP_INTERLEAVE_NONE, CU_TENSOR_MAP_SWIZZLE_64B, CU_TENSOR_MAP_L2_PROMOTION_L2_128B, CU_TENSOR_MAP_FLOAT_OOB_FILL_NONE);
    }
    {
      cuuint64_t dims[2] = {(cuuint64_t)D_MOD, (cuuint64_t)F_HID};
      cuuint64_t strides[1] = {(cuuint64_t)D_MOD * 2};
      cuuint32_t box[2] = {64, 112};
      cuuint32_t es[2] = {1, 1};
      enc(&tm_w2, CU_TENSOR_MAP_DATA_TYPE_BFLOAT16, 2, const_cast<void*>(w2), dims, strides, box, es,
          CU_TENSOR_MAP_INTERLEAVE_NONE, CU_TENSOR_MAP_SWIZZLE_128B, CU_TENSOR_MAP_L2_PROMOTION_L2_128B, CU_TENSOR_MAP_FLOAT_OOB_FILL_NONE);
    }
    cudaFuncSetAttribute(fused_mlp_kernel, cudaFuncAttributeMaxDynamicSharedMemorySize, SMEM_TOTAL);
    cached_w1 = w1; cached_w2 = w2; cached_x = xp;
  }
  fused_mlp_kernel<<<NMB * NSPLIT, NTHREADS, SMEM_TOTAL>>>(tm_x, tm_w1, tm_w2,
      (const __nv_bfloat16*)d_in[1], (const __nv_bfloat16*)d_in[3], (const __nv_bfloat16*)d_in[2], (const __nv_bfloat16*)d_in[4], (__nv_bfloat16*)d_out);
}
```

```cpp
#include <cuda_runtime.h>
#include <cuda_bf16.h>
#include <cuda.h>
#include <stdint.h>

namespace {

constexpr int S_TOK = 2048, D_MOD = 512, F_HID = 1792;
constexpr int BM = 128, NSPLIT = 8, BF = F_HID / NSPLIT;
constexpr int BN2 = D_MOD / NSPLIT;
constexpr int NMB = S_TOK / BM;
constexpr int SLOT_BYTES = 16384;
constexpr int W1_BYTES = 14336;
constexpr int W2_BYTES = 14336;
constexpr int Y_BYTES = BM * D_MOD * 2;
constexpr int NRING = 6;
constexpr int NLOAD = 32;
constexpr int OFF_RING = Y_BYTES;
__host__ __device__ constexpr int yslot_off(int s) { return (s >> 1) * 65536 + (s & 1) * 16384; }
__host__ __device__ constexpr int uslot_off(int s) { return (s >> 1) * 65536 + 32768 + (s & 1) * 16384; }
constexpr int DSLOT_BYTES = 16384;
constexpr int OFF_BAR = OFF_RING + NRING * SLOT_BYTES;
constexpr int OFF_MEAN = OFF_BAR + 640;
constexpr int OFF_B1 = OFF_MEAN + 512;
constexpr int OFF_B2 = OFF_B1 + 1024;
constexpr int SMEM_TOTAL = OFF_B2 + 256;
constexpr int NTHREADS = 384;
static_assert(SMEM_TOTAL <= 232448, "smem");

struct __align__(128) Mailbox { uint4 part[3 * 1024]; unsigned int epoch; unsigned int pad[31]; };
__device__ Mailbox g_box[NMB * NSPLIT];

#define TS_DECL
#define TS_FLUSH do {} while (0)
#define TS(role, idx) do {} while (0)
#define TSC(idx) do {} while (0)

__device__ __forceinline__ uint32_t smem_u32(const void* p) { return (uint32_t)__cvta_generic_to_shared(p); }
__device__ __forceinline__ uint32_t mapa(uint32_t a, uint32_t r) {
  uint32_t d; asm volatile("mapa.shared::cluster.u32 %0, %1, %2;" : "=r"(d) : "r"(a), "r"(r)); return d;
}
__device__ __forceinline__ void mbar_init(uint32_t bar, uint32_t cnt) {
  asm volatile("mbarrier.init.shared::cta.b64 [%0], %1;" :: "r"(bar), "r"(cnt) : "memory");
}
__device__ __forceinline__ void mbar_expect_tx(uint32_t bar, uint32_t bytes) {
  asm volatile("mbarrier.arrive.expect_tx.shared::cta.b64 _, [%0], %1;" :: "r"(bar), "r"(bytes) : "memory");
}
__device__ __forceinline__ void mbar_arrive(uint32_t bar) {
  asm volatile("mbarrier.arrive.shared::cta.b64 _, [%0];" :: "r"(bar) : "memory");
}
__device__ __forceinline__ void mbar_arrive_remote(uint32_t rbar) {
  asm volatile("mbarrier.arrive.release.cluster.shared::cluster.b64 _, [%0];" :: "r"(rbar) : "memory");
}
__device__ __forceinline__ void mbar_wait(uint32_t bar, uint32_t parity) {
  uint32_t done = 0; uint32_t it = 0;
  while (true) {
    asm volatile("{\n.reg .pred p;\nmbarrier.try_wait.parity.shared::cta.b64 p, [%1], %2;\nselp.u32 %0, 1, 0, p;\n}"
                 : "=r"(done) : "r"(bar), "r"(parity) : "memory");
    if (done) break;
    if (++it > (1u << 22)) asm volatile("trap;");
  }
}
__device__ __forceinline__ void mbar_wait_cluster(uint32_t bar, uint32_t parity) {
  uint32_t done = 0; uint32_t it = 0;
  while (true) {
    asm volatile("{\n.reg .pred p;\nmbarrier.try_wait.parity.acquire.cluster.shared::cta.b64 p, [%1], %2;\nselp.u32 %0, 1, 0, p;\n}"
                 : "=r"(done) : "r"(bar), "r"(parity) : "memory");
    if (done) break;
    if (++it > (1u << 22)) asm volatile("trap;");
  }
}
__device__ __forceinline__ void tma_load_3d(uint32_t dst, const CUtensorMap* tm, int c0, int c1, int c2, uint32_t bar) {
  asm volatile("cp.async.bulk.tensor.3d.shared::cluster.global.mbarrier::complete_tx::bytes [%0], [%1, {%3, %4, %5}], [%2];"
               :: "r"(dst), "l"(tm), "r"(bar), "r"(c0), "r"(c1), "r"(c2) : "memory");
}
__device__ __forceinline__ void tma_load_2d(uint32_t dst, const CUtensorMap* tm, int c0, int c1, uint32_t bar) {
  asm volatile("cp.async.bulk.tensor.2d.shared::cluster.global.mbarrier::complete_tx::bytes [%0], [%1, {%3, %4}], [%2];"
               :: "r"(dst), "l"(tm), "r"(bar), "r"(c0), "r"(c1) : "memory");
}
__device__ __forceinline__ void tma_prefetch_2d(const CUtensorMap* tm, int c0, int c1) {
  asm volatile("cp.async.bulk.prefetch.tensor.2d.L2.global.tile [%0, {%1, %2}];" :: "l"(tm), "r"(c0), "r"(c1) : "memory");
}
__device__ __forceinline__ void fence_async_smem() { asm volatile("fence.proxy.async.shared::cta;" ::: "memory"); }
__device__ __forceinline__ void wg_bar(int wg) {
  if (wg == 0) asm volatile("bar.sync 1, 128;" ::: "memory"); else asm volatile("bar.sync 2, 128;" ::: "memory");
}
__device__ __forceinline__ void wg_fence() { asm volatile("wgmma.fence.sync.aligned;" ::: "memory"); }
__device__ __forceinline__ void wg_commit() { asm volatile("wgmma.commit_group.sync.aligned;" ::: "memory"); }
template <int N> __device__ __forceinline__ void wg_wait() { asm volatile("wgmma.wait_group.sync.aligned %0;" :: "n"(N) : "memory"); }
template <int N> __device__ __forceinline__ void reg_fence(float (&d)[N]) {
#pragma unroll
  for (int i = 0; i < N; i++) asm volatile("" : "+f"(d[i]) :: "memory");
}
__device__ __forceinline__ uint64_t make_desc(uint32_t addr, uint32_t lbo, uint32_t sbo, uint32_t lt) {
  return (uint64_t)((addr & 0x3FFFF) >> 4) | ((uint64_t)(lbo >> 4) << 16) | ((uint64_t)(sbo >> 4) << 32) | ((uint64_t)lt << 62);
}
__device__ __forceinline__ uint32_t pack_bf16(float lo, float hi) {
  uint32_t r; asm("cvt.rn.bf16x2.f32 %0, %1, %2;" : "=r"(r) : "f"(hi), "f"(lo)); return r;
}
__device__ __forceinline__ float bf_lo(uint32_t v) { return __uint_as_float(v << 16); }
__device__ __forceinline__ float bf_hi(uint32_t v) { return __uint_as_float(v & 0xffff0000u); }
__device__ __forceinline__ float bf16r(float v) { return __bfloat162float(__float2bfloat16_rn(v)); }
__device__ __forceinline__ uint32_t hadd2_bf(uint32_t a, uint32_t b) {
  uint32_t r; asm("add.rn.bf16x2 %0, %1, %2;" : "=r"(r) : "r"(a), "r"(b)); return r;
}
__device__ __forceinline__ uint32_t hsub2_bf(uint32_t a, uint32_t b) {
  uint32_t r; asm("sub.rn.bf16x2 %0, %1, %2;" : "=r"(r) : "r"(a), "r"(b)); return r;
}
__device__ __forceinline__ float gelu_tanh(float u) {
  float inner = u * fmaf(0.035677408136300125f, u * u, 0.7978845608028654f);
  float th; asm("tanh.approx.f32 %0, %1;" : "=f"(th) : "f"(inner));
  float hu = 0.5f * u;
  return fmaf(hu, th, hu);
}
__device__ __forceinline__ void mma16816(float (&c)[4], uint32_t a0, uint32_t a1, uint32_t a2, uint32_t a3, uint32_t b0, uint32_t b1) {
  asm volatile("mma.sync.aligned.m16n8k16.row.col.f32.bf16.bf16.f32 {%0,%1,%2,%3}, {%4,%5,%6,%7}, {%8,%9}, {%0,%1,%2,%3};"
               : "+f"(c[0]), "+f"(c[1]), "+f"(c[2]), "+f"(c[3]) : "r"(a0), "r"(a1), "r"(a2), "r"(a3), "r"(b0), "r"(b1));
}

__device__ __forceinline__ void wgmma_ss_n224(float (&d)[112], uint64_t descA, uint64_t descB, int scaleD) {
  asm volatile("{\n.reg .pred p;\nsetp.ne.b32 p, %114, 0;\n"
    "wgmma.mma_async.sync.aligned.m64n224k16.f32.bf16.bf16 {%0, %1, %2, %3, %4, %5, %6, %7, %8, %9, %10, %11, %12, %13, %14, %15, %16, %17, %18, %19, %20, %21, %22, %23, %24, %25, %26, %27, %28, %29, %30, %31, %32, %33, %34, %35, %36, %37, %38, %39, %40, %41, %42, %43, %44, %45, %46, %47, %48, %49, %50, %51, %52, %53, %54, %55, %56, %57, %58, %59, %60, %61, %62, %63, %64, %65, %66, %67, %68, %69, %70, %71, %72, %73, %74, %75, %76, %77, %78, %79, %80, %81, %82, %83, %84, %85, %86, %87, %88, %89, %90, %91, %92, %93, %94, %95, %96, %97, %98, %99, %100, %101, %102, %103, %104, %105, %106, %107, %108, %109, %110, %111}, %112, %113, p, 1, 1, 0, 1;\n}\n"
    : "+f"(d[0]), "+f"(d[1]), "+f"(d[2]), "+f"(d[3]), "+f"(d[4]), "+f"(d[5]), "+f"(d[6]), "+f"(d[7]), "+f"(d[8]), "+f"(d[9]), "+f"(d[10]), "+f"(d[11]), "+f"(d[12]), "+f"(d[13]), "+f"(d[14]), "+f"(d[15]), "+f"(d[16]), "+f"(d[17]), "+f"(d[18]), "+f"(d[19]), "+f"(d[20]), "+f"(d[21]), "+f"(d[22]), "+f"(d[23]), "+f"(d[24]), "+f"(d[25]), "+f"(d[26]), "+f"(d[27]), "+f"(d[28]), "+f"(d[29]), "+f"(d[30]), "+f"(d[31]), "+f"(d[32]), "+f"(d[33]), "+f"(d[34]), "+f"(d[35]), "+f"(d[36]), "+f"(d[37]), "+f"(d[38]), "+f"(d[39]), "+f"(d[40]), "+f"(d[41]), "+f"(d[42]), "+f"(d[43]), "+f"(d[44]), "+f"(d[45]), "+f"(d[46]), "+f"(d[47]), "+f"(d[48]), "+f"(d[49]), "+f"(d[50]), "+f"(d[51]), "+f"(d[52]), "+f"(d[53]), "+f"(d[54]), "+f"(d[55]), "+f"(d[56]), "+f"(d[57]), "+f"(d[58]), "+f"(d[59]), "+f"(d[60]), "+f"(d[61]), "+f"(d[62]), "+f"(d[63]), "+f"(d[64]), "+f"(d[65]), "+f"(d[66]), "+f"(d[67]), "+f"(d[68]), "+f"(d[69]), "+f"(d[70]), "+f"(d[71]), "+f"(d[72]), "+f"(d[73]), "+f"(d[74]), "+f"(d[75]), "+f"(d[76]), "+f"(d[77]), "+f"(d[78]), "+f"(d[79]), "+f"(d[80]), "+f"(d[81]), "+f"(d[82]), "+f"(d[83]), "+f"(d[84]), "+f"(d[85]), "+f"(d[86]), "+f"(d[87]), "+f"(d[88]), "+f"(d[89]), "+f"(d[90]), "+f"(d[91]), "+f"(d[92]), "+f"(d[93]), "+f"(d[94]), "+f"(d[95]), "+f"(d[96]), "+f"(d[97]), "+f"(d[98]), "+f"(d[99]), "+f"(d[100]), "+f"(d[101]), "+f"(d[102]), "+f"(d[103]), "+f"(d[104]), "+f"(d[105]), "+f"(d[106]), "+f"(d[107]), "+f"(d[108]), "+f"(d[109]), "+f"(d[110]), "+f"(d[111])
    : "l"(descA), "l"(descB), "r"(scaleD));
}

__device__ __forceinline__ void wgmma_rs_n64(float (&d)[32], const uint32_t (&a)[4], uint64_t descB, int scaleD) {
  asm volatile("{\n.reg .pred p;\nsetp.ne.b32 p, %37, 0;\n"
    "wgmma.mma_async.sync.aligned.m64n64k16.f32.bf16.bf16 {%0, %1, %2, %3, %4, %5, %6, %7, %8, %9, %10, %11, %12, %13, %14, %15, %16, %17, %18, %19, %20, %21, %22, %23, %24, %25, %26, %27, %28, %29, %30, %31}, {%32, %33, %34, %35}, %36, p, 1, 1, 1;\n}\n"
    : "+f"(d[0]), "+f"(d[1]), "+f"(d[2]), "+f"(d[3]), "+f"(d[4]), "+f"(d[5]), "+f"(d[6]), "+f"(d[7]), "+f"(d[8]), "+f"(d[9]), "+f"(d[10]), "+f"(d[11]), "+f"(d[12]), "+f"(d[13]), "+f"(d[14]), "+f"(d[15]), "+f"(d[16]), "+f"(d[17]), "+f"(d[18]), "+f"(d[19]), "+f"(d[20]), "+f"(d[21]), "+f"(d[22]), "+f"(d[23]), "+f"(d[24]), "+f"(d[25]), "+f"(d[26]), "+f"(d[27]), "+f"(d[28]), "+f"(d[29]), "+f"(d[30]), "+f"(d[31])
    : "r"(a[0]), "r"(a[1]), "r"(a[2]), "r"(a[3]), "l"(descB), "r"(scaleD));
}

__device__ __forceinline__ void wgmma_rs_n224(float (&d)[112], const uint32_t (&a)[4], uint64_t descB, int scaleD) {
  asm volatile("{\n.reg .pred p;\nsetp.ne.b32 p, %117, 0;\n"
    "wgmma.mma_async.sync.aligned.m64n224k16.f32.bf16.bf16 {%0, %1, %2, %3, %4, %5, %6, %7, %8, %9, %10, %11, %12, %13, %14, %15, %16, %17, %18, %19, %20, %21, %22, %23, %24, %25, %26, %27, %28, %29, %30, %31, %32, %33, %34, %35, %36, %37, %38, %39, %40, %41, %42, %43, %44, %45, %46, %47, %48, %49, %50, %51, %52, %53, %54, %55, %56, %57, %58, %59, %60, %61, %62, %63, %64, %65, %66, %67, %68, %69, %70, %71, %72, %73, %74, %75, %76, %77, %78, %79, %80, %81, %82, %83, %84, %85, %86, %87, %88, %89, %90, %91, %92, %93, %94, %95, %96, %97, %98, %99, %100, %101, %102, %103, %104, %105, %106, %107, %108, %109, %110, %111}, {%112, %113, %114, %115}, %116, p, 1, 1, 1;\n}\n"
    : "+f"(d[0]), "+f"(d[1]), "+f"(d[2]), "+f"(d[3]), "+f"(d[4]), "+f"(d[5]), "+f"(d[6]), "+f"(d[7]), "+f"(d[8]), "+f"(d[9]), "+f"(d[10]), "+f"(d[11]), "+f"(d[12]), "+f"(d[13]), "+f"(d[14]), "+f"(d[15]), "+f"(d[16]), "+f"(d[17]), "+f"(d[18]), "+f"(d[19]), "+f"(d[20]), "+f"(d[21]), "+f"(d[22]), "+f"(d[23]), "+f"(d[24]), "+f"(d[25]), "+f"(d[26]), "+f"(d[27]), "+f"(d[28]), "+f"(d[29]), "+f"(d[30]), "+f"(d[31]), "+f"(d[32]), "+f"(d[33]), "+f"(d[34]), "+f"(d[35]), "+f"(d[36]), "+f"(d[37]), "+f"(d[38]), "+f"(d[39]), "+f"(d[40]), "+f"(d[41]), "+f"(d[42]), "+f"(d[43]), "+f"(d[44]), "+f"(d[45]), "+f"(d[46]), "+f"(d[47]), "+f"(d[48]), "+f"(d[49]), "+f"(d[50]), "+f"(d[51]), "+f"(d[52]), "+f"(d[53]), "+f"(d[54]), "+f"(d[55]), "+f"(d[56]), "+f"(d[57]), "+f"(d[58]), "+f"(d[59]), "+f"(d[60]), "+f"(d[61]), "+f"(d[62]), "+f"(d[63]), "+f"(d[64]), "+f"(d[65]), "+f"(d[66]), "+f"(d[67]), "+f"(d[68]), "+f"(d[69]), "+f"(d[70]), "+f"(d[71]), "+f"(d[72]), "+f"(d[73]), "+f"(d[74]), "+f"(d[75]), "+f"(d[76]), "+f"(d[77]), "+f"(d[78]), "+f"(d[79]), "+f"(d[80]), "+f"(d[81]), "+f"(d[82]), "+f"(d[83]), "+f"(d[84]), "+f"(d[85]), "+f"(d[86]), "+f"(d[87]), "+f"(d[88]), "+f"(d[89]), "+f"(d[90]), "+f"(d[91]), "+f"(d[92]), "+f"(d[93]), "+f"(d[94]), "+f"(d[95]), "+f"(d[96]), "+f"(d[97]), "+f"(d[98]), "+f"(d[99]), "+f"(d[100]), "+f"(d[101]), "+f"(d[102]), "+f"(d[103]), "+f"(d[104]), "+f"(d[105]), "+f"(d[106]), "+f"(d[107]), "+f"(d[108]), "+f"(d[109]), "+f"(d[110]), "+f"(d[111])
    : "r"(a[0]), "r"(a[1]), "r"(a[2]), "r"(a[3]), "l"(descB), "r"(scaleD));
}

__host__ __device__ constexpr int step_kind(int i) { return (i < 3 || i == 6) ? 0 : (i == 7 ? 2 : 1); }
__host__ __device__ constexpr int step_k(int i) { return i < 3 ? i : (i < 6 ? i - 3 : 3); }
__device__ __forceinline__ int step_slice(int i, int j) {
  const int kind = step_kind(i), k = step_k(i);
  const int base = (kind == 0) ? (j ^ 1) : j;
  return (k == 3) ? base : ((base + 2 * (k + 1)) & 7);
}

__host__ __device__ constexpr int load_off(int i) {
  return i < 6 ? OFF_RING + i * SLOT_BYTES
       : i < 10 ? yslot_off(i - 6)
       : i < 16 ? OFF_RING + (i - 10) * SLOT_BYTES
       : i < 18 ? yslot_off(i - 14)
       : i < 24 ? OFF_RING + (i - 18) * SLOT_BYTES
       : i < 26 ? yslot_off(i - 22)
       : OFF_RING + (i - 26) * SLOT_BYTES;
}
__host__ __device__ constexpr int load_dep(int i) { return i < 6 ? -1 : (i < 10 ? -2 : (i < 16 ? i - 10 : i - 8)); }

__global__ void __cluster_dims__(2, 1, 1) __launch_bounds__(NTHREADS, 1)
fused_mlp_kernel(const __grid_constant__ CUtensorMap tm_x, const __grid_constant__ CUtensorMap tm_w1, const __grid_constant__ CUtensorMap tm_w2,
                 const __nv_bfloat16* __restrict__ w1, const __nv_bfloat16* __restrict__ w2,
                 const __nv_bfloat16* __restrict__ b1, const __nv_bfloat16* __restrict__ b2, __nv_bfloat16* __restrict__ out)
{
  extern __shared__ __align__(1024) unsigned char smem[];
  const uint32_t sbase = smem_u32(smem);
  const uint32_t bar_full = sbase + OFF_BAR;
  const uint32_t bar_cons = sbase + OFF_BAR + 256;
  const uint32_t bar_dfull = sbase + OFF_BAR + 528;
  const uint32_t bar_peer = sbase + OFF_BAR + 560;
  const uint32_t bar_x = sbase + OFF_BAR + 592;
  const uint32_t bar_ln = sbase + OFF_BAR + 568;
  const uint32_t bar_dack = sbase + OFF_BAR + 576;
  const int tid = threadIdx.x, warp = tid >> 5, lane = tid & 31;
  const int mb = blockIdx.x >> 3, j = blockIdx.x & 7;

  TS_DECL
  TSC(0);
  if (warp >= 8) {
    asm volatile("setmaxnreg.dec.sync.aligned.u32 40;");
  if (warp == 8) {
    mbar_init(bar_full + 8 * lane, 1); mbar_init(bar_cons + 8 * lane, 2);
    if (lane < 4) mbar_init(bar_dfull + 8 * lane, 1);
    if (lane == 4) mbar_init(bar_peer, 2);
    if (lane == 5) mbar_init(bar_ln, 2);
    if (lane >= 8 && lane < 12) mbar_init(bar_x + 8 * (lane - 8), 1);
    if (lane == 6 || lane == 7) mbar_init(bar_dack + 8 * (lane - 6), 1);
    asm volatile("fence.mbarrier_init.release.cluster;" ::: "memory");
    fence_async_smem();
    __syncwarp();
    if (lane >= 4 && lane < 8) mbar_expect_tx(bar_dfull + 8 * (lane - 4), DSLOT_BYTES);
    __syncwarp();
  }
    asm volatile("bar.sync 0, 384;" ::: "memory");
    if (warp == 8 && lane == 0) {
      for (int kq = 0; kq < 4; kq++) {
        mbar_expect_tx(bar_x + 8 * kq, 32768);
        tma_load_3d(sbase + kq * 16384, &tm_x, 0, mb * BM, 2 * kq, bar_x + 8 * kq);
        tma_load_3d(sbase + 65536 + kq * 16384, &tm_x, 0, mb * BM + 64, 2 * kq, bar_x + 8 * kq);
      }
      for (int i = 0; i < NRING; i++) {
        mbar_expect_tx(bar_full + 8 * i, W1_BYTES);
        tma_load_3d(sbase + OFF_RING + i * SLOT_BYTES, &tm_w1, 0, i * 32, j * 7, bar_full + 8 * i);
      }
      asm volatile("cp.async.bulk.prefetch.L2.global [%0], %1;" :: "l"(reinterpret_cast<const unsigned char*>(w1) + (size_t)blockIdx.x * 14336), "r"(14336) : "memory");
      asm volatile("cp.async.bulk.prefetch.L2.global [%0], %1;" :: "l"(reinterpret_cast<const unsigned char*>(w2) + (size_t)blockIdx.x * 14336), "r"(14336) : "memory");
      TS(2, 1);
    }
    __syncwarp();
    asm volatile("barrier.cluster.arrive.relaxed.aligned;" ::: "memory");
    if (warp == 8 && lane == 0) {
#pragma unroll
      for (int i = NRING; i < NLOAD; i++) {
        if (load_dep(i) >= 0) mbar_wait(bar_cons + 8 * load_dep(i), 0); else if (i == NRING) mbar_wait(bar_ln, 0);
        TS(2, i);
        const uint32_t dst = sbase + load_off(i);
        if (i < 16) {
          mbar_expect_tx(bar_full + 8 * i, W1_BYTES);
          tma_load_3d(dst, &tm_w1, 0, i * 32, j * 7, bar_full + 8 * i);
        } else {
          mbar_expect_tx(bar_full + 8 * i, W2_BYTES);
          tma_load_2d(dst, &tm_w2, step_slice((i - 16) >> 1, j) * BN2, j * BF + ((i - 16) & 1) * 112, bar_full + 8 * i);
        }
      }
    }
    __syncwarp();
    asm volatile("barrier.cluster.wait.aligned;" ::: "memory");
    if (warp == 9 && lane == 0) {
      for (int k = 0; k < 2; k++) {
        mbar_wait_cluster(bar_dfull + 8 * k, 0);
        mbar_arrive_remote(mapa(bar_dack + 8 * k, (j & 1) ^ 1));
      }
    }
    __syncwarp();
    asm volatile("barrier.cluster.arrive.relaxed.aligned;\nbarrier.cluster.wait.aligned;" ::: "memory");
  } else {
    asm volatile("setmaxnreg.inc.sync.aligned.u32 232;");
    asm volatile("bar.sync 0, 384;" ::: "memory");
    TSC(29);
    const int wg = warp >> 2, w4 = warp & 3, t128 = tid & 127;
    const int q = lane & 3, g = lane >> 2;
    uint32_t* b1s = reinterpret_cast<uint32_t*>(smem + OFF_B1 + wg * 512);
    uint32_t* b2s = reinterpret_cast<uint32_t*>(smem + OFF_B2 + wg * 128);
    uint32_t bias_a = 0, bias_b = 0;
    if (t128 < BF / 2) bias_a = reinterpret_cast<const uint32_t*>(b1 + j * BF)[t128];
    if (t128 < BN2 / 2) bias_b = reinterpret_cast<const uint32_t*>(b2 + j * BN2)[t128];
    const uint32_t epoch = g_box[blockIdx.x].epoch;

    float r0, r1;
    uint32_t xa[16][4];
    TSC(24);
    {
      uint32_t xb[16][4];
      float cs[2][4], c0[2][4], c1[2][4];
#pragma unroll
      for (int u = 0; u < 2; u++)
#pragma unroll
        for (int e = 0; e < 4; e++) { cs[u][e] = 0.f; c0[u][e] = 0.f; c1[u][e] = 0.f; }
      const int lrow = w4 * 16 + (lane & 7) + ((lane >> 3) & 1) * 8;
      const uint32_t lbase = sbase + wg * 65536 + lrow * 128;
      const uint32_t ones = 0x3F803F80u;
#pragma unroll
      for (int ks = 0; ks < 32; ks++) {
        if ((ks & 7) == 0) { mbar_wait(bar_x + 8 * (ks >> 3), 0); if (ks == 0) TSC(25); if (ks == 24) TSC(22); }
        uint32_t (&a)[4] = ks < 16 ? xa[ks] : xb[ks - 16];
        const uint32_t addr = lbase + (ks >> 2) * 8192 + (((2 * (ks & 3) + (lane >> 4)) ^ (lane & 7)) << 4);
        asm volatile("ldmatrix.sync.aligned.m8n8.x4.shared.b16 {%0,%1,%2,%3}, [%4];" : "=r"(a[0]), "=r"(a[1]), "=r"(a[2]), "=r"(a[3]) : "r"(addr));
        mma16816(cs[ks & 1], a[0], a[1], a[2], a[3], ones, ones);
        mma16816(c0[ks & 1], a[0], a[1], a[2], a[3], a[0], a[2]);
        mma16816(c1[ks & 1], a[0], a[1], a[2], a[3], a[1], a[3]);
      }
      TSC(27);
      const int dsrc = g * 4 + (g >> 1);
      const float q0 = __shfl_sync(0xffffffffu, (g & 1) ? c0[0][1] + c0[1][1] : c0[0][0] + c0[1][0], dsrc);
      const float q1 = __shfl_sync(0xffffffffu, (g & 1) ? c1[0][3] + c1[1][3] : c1[0][2] + c1[1][2], dsrc);
      const float m0 = (cs[0][0] + cs[1][0]) * (1.0f / D_MOD), m1 = (cs[0][2] + cs[1][2]) * (1.0f / D_MOD);
      const uint32_t mm0 = pack_bf16(m0, m0), mm1 = pack_bf16(m1, m1);
#pragma unroll
      for (int ks = 16; ks < 32; ks++) {
        const uint32_t addr = lbase + (ks >> 2) * 8192 + (((2 * (ks & 3) + (lane >> 4)) ^ (lane & 7)) << 4);
        asm volatile("stmatrix.sync.aligned.m8n8.x4.shared.b16 [%0], {%1,%2,%3,%4};" :: "r"(addr),
                     "r"(hsub2_bf(xb[ks - 16][0], mm0)), "r"(hsub2_bf(xb[ks - 16][1], mm1)),
                     "r"(hsub2_bf(xb[ks - 16][2], mm0)), "r"(hsub2_bf(xb[ks - 16][3], mm1)) : "memory");
      }
#pragma unroll
      for (int ks = 0; ks < 16; ks++) {
        xa[ks][0] = hsub2_bf(xa[ks][0], mm0); xa[ks][1] = hsub2_bf(xa[ks][1], mm1);
        xa[ks][2] = hsub2_bf(xa[ks][2], mm0); xa[ks][3] = hsub2_bf(xa[ks][3], mm1);
      }
      const float v0 = fmaxf(fmaf(-m0, m0, q0 * (1.0f / D_MOD)), 0.f), v1 = fmaxf(fmaf(-m1, m1, q1 * (1.0f / D_MOD)), 0.f);
      r0 = 1.0f / bf16r(sqrtf(bf16r(bf16r(v0) + 1e-5f)));
      r1 = 1.0f / bf16r(sqrtf(bf16r(bf16r(v1) + 1e-5f)));
    }
    TSC(1);
    fence_async_smem();
    wg_bar(wg);
    if (t128 == 0) mbar_arrive(bar_ln);
    asm volatile("barrier.cluster.arrive.relaxed.aligned;" ::: "memory");
    TSC(2);

    uint32_t h[14][4];
    {
      float acc[112];
#pragma unroll
      for (int kb = 0; kb < 16; kb++) {
        mbar_wait(bar_full + 8 * kb, 0);
        wg_fence();
        const uint32_t abase = sbase + wg * 65536 + (kb >> 1) * 8192 + (kb & 1) * 64;
        const uint32_t bbase = sbase + load_off(kb);
#pragma unroll
        for (int kk = 0; kk < 2; kk++) {
          if (kb < 8) wgmma_rs_n224(acc, xa[2 * kb + kk], make_desc(bbase + kk * 1024, 2048, 512, 2), (kb | kk) != 0);
          else wgmma_ss_n224(acc, make_desc(abase + kk * 32, 16, 1024, 1), make_desc(bbase + kk * 1024, 2048, 512, 2), 1);
        }
        wg_commit();
        if (kb > 0) { wg_wait<1>(); if (t128 == 0) mbar_arrive(bar_cons + 8 * (kb - 1)); }
      }
      if (t128 < BF / 2) b1s[t128] = bias_a;
      if (t128 < BN2 / 2) b2s[t128] = bias_b;
      wg_bar(wg);
      wg_wait<0>();
      reg_fence(acc);
      asm volatile("barrier.cluster.wait.aligned;" ::: "memory");
      if (t128 == 0) { mbar_arrive(bar_cons + 8 * 15); mbar_arrive_remote(mapa(bar_peer, (j & 1) ^ 1)); }
      TSC(11);

#pragma unroll
      for (int i = 0; i < 28; i++) {
        const uint32_t bb = b1s[i * 4 + q];
        uint32_t p0 = hadd2_bf(pack_bf16(acc[4 * i] * r0, acc[4 * i + 1] * r0), bb);
        uint32_t p1 = hadd2_bf(pack_bf16(acc[4 * i + 2] * r1, acc[4 * i + 3] * r1), bb);
        h[i >> 1][(i & 1) * 2 + 0] = pack_bf16(gelu_tanh(bf_lo(p0)), gelu_tanh(bf_hi(p0)));
        h[i >> 1][(i & 1) * 2 + 1] = pack_bf16(gelu_tanh(bf_lo(p1)), gelu_tanh(bf_hi(p1)));
      }
    }

    const uint32_t par = (epoch + 1) & 1;
    float acc2[2][32];
    float sum[32];
    uint4 pf[3][4];
    const uint32_t peer_base = mapa(sbase + wg * 8192, (j & 1) ^ 1);
    const uint32_t peer_dfull = mapa(bar_dfull, (j & 1) ^ 1);
    uint4* my_base = reinterpret_cast<uint4*>(smem) + wg * 512 + t128;
    const uint4* in_part = &g_box[blockIdx.x].part[wg * 512 + t128];
    auto ld_part = [&](const uint4* p) {
      uint4 v;
      asm volatile("ld.relaxed.gpu.global.v4.u32 {%0, %1, %2, %3}, [%4];" : "=r"(v.x), "=r"(v.y), "=r"(v.z), "=r"(v.w) : "l"(p) : "memory");
      return v;
    };
    auto prefetch = [&](int k) {
#pragma unroll
      for (int c = 0; c < 4; c++) pf[k][c] = ld_part(in_part + k * 1024 + c * 128);
    };
    auto consume = [&](int k) {
#pragma unroll
      for (int c = 0; c < 4; c++) {
        uint4 v = pf[k][c];
        uint32_t it = 0;
        while ((((v.x ^ par) | (v.y ^ par) | (v.z ^ par) | (v.w ^ par)) & 1u) != 0) {
          v = ld_part(in_part + k * 1024 + c * 128);
          if (++it > (1u << 20)) asm volatile("trap;");
        }
        sum[c * 8 + 0] += bf_lo(v.x & ~1u); sum[c * 8 + 1] += bf_hi(v.x);
        sum[c * 8 + 2] += bf_lo(v.y & ~1u); sum[c * 8 + 3] += bf_hi(v.y);
        sum[c * 8 + 4] += bf_lo(v.z & ~1u); sum[c * 8 + 5] += bf_hi(v.z);
        sum[c * 8 + 6] += bf_lo(v.w & ~1u); sum[c * 8 + 7] += bf_hi(v.w);
      }
    };
    auto post_pack = [&](int st, float (&a)[32], uint4 (&v)[4]) {
      const int kind = step_kind(st), k = step_k(st);
      if (kind == 0) {
#pragma unroll
        for (int c = 0; c < 4; c++) {
          v[c].x = pack_bf16(a[c * 8 + 0], a[c * 8 + 1]); v[c].y = pack_bf16(a[c * 8 + 2], a[c * 8 + 3]);
          v[c].z = pack_bf16(a[c * 8 + 4], a[c * 8 + 5]); v[c].w = pack_bf16(a[c * 8 + 6], a[c * 8 + 7]);
        }
      } else {
#pragma unroll
        for (int c = 0; c < 4; c++) {
          const uint4 d = v[c];
          v[c].x = (pack_bf16(a[c * 8 + 0] + bf_lo(d.x), a[c * 8 + 1] + bf_hi(d.x)) & ~1u) | par;
          v[c].y = (pack_bf16(a[c * 8 + 2] + bf_lo(d.y), a[c * 8 + 3] + bf_hi(d.y)) & ~1u) | par;
          v[c].z = (pack_bf16(a[c * 8 + 4] + bf_lo(d.z), a[c * 8 + 5] + bf_hi(d.z)) & ~1u) | par;
          v[c].w = (pack_bf16(a[c * 8 + 6] + bf_lo(d.w), a[c * 8 + 7] + bf_hi(d.w)) & ~1u) | par;
        }
      }
      (void)k;
    };
    auto post_send = [&](int st, uint4 (&v)[4]) {
      const int kind = step_kind(st), k = step_k(st);
      if (kind == 0) {
        if (st == 0) mbar_wait(bar_cons + 8 * 15, 0);
        if (k >= 2) mbar_wait_cluster(bar_dack + 8 * (k - 2), 0);
#pragma unroll
        for (int c = 0; c < 4; c++) my_base[yslot_off(k & 1) / 16 + c * 128] = v[c];
        fence_async_smem();
        wg_bar(wg);
        if (t128 == 0) {
          if (st == 0) mbar_wait_cluster(bar_peer, 0);
          asm volatile("cp.async.bulk.shared::cluster.shared::cta.mbarrier::complete_tx::bytes [%0], [%1], %2, [%3];"
                       :: "r"(peer_base + uslot_off(k)), "r"(sbase + yslot_off(k & 1) + wg * 8192), "r"(8192), "r"(peer_dfull + 8 * k) : "memory");
        }
      } else {
#pragma unroll
        for (int c = 0; c < 4; c++) my_base[uslot_off(k) / 16 + c * 128] = v[c];
        fence_async_smem();
        wg_bar(wg);
        if (t128 == 0) {
          const int dest = (j + 2 * (k + 1)) & 7;
          const uint4* p = &g_box[mb * NSPLIT + dest].part[k * 1024 + wg * 512];
          asm volatile("cp.async.bulk.global.shared::cta.bulk_group [%0], [%1], %2;"
                       :: "l"(p), "r"(sbase + uslot_off(k) + wg * 8192), "r"(8192) : "memory");
          asm volatile("cp.async.bulk.commit_group;" ::: "memory");
        }
      }
    };
    auto issue = [&](int i) {
      mbar_wait(bar_full + 8 * (16 + 2 * i), 0);
      wg_fence();
#pragma unroll
      for (int ks = 0; ks < 7; ks++) {
        wgmma_rs_n64(acc2[i & 1], h[ks], make_desc(sbase + load_off(16 + 2 * i) + ks * 2048, 16, 1024, 1), ks != 0);
      }
      mbar_wait(bar_full + 8 * (17 + 2 * i), 0);
      wg_fence();
#pragma unroll
      for (int ks = 0; ks < 7; ks++) {
        wgmma_rs_n64(acc2[i & 1], h[7 + ks], make_desc(sbase + load_off(17 + 2 * i) + ks * 2048, 16, 1024, 1), 1);
      }
      wg_commit();
    };
    TSC(12);
    issue(0);
    issue(1);
#pragma unroll
    for (int i = 0; i < 7; i++) {
      uint4 v[4];
      if (step_kind(i) == 1) {
        mbar_wait_cluster(bar_dfull + 8 * step_k(i), 0);
#pragma unroll
        for (int c = 0; c < 4; c++) v[c] = my_base[uslot_off(step_k(i)) / 16 + c * 128];
      }
      wg_wait<1>();
      reg_fence(acc2[i & 1]);
      post_pack(i, acc2[i & 1], v);
      if (i <= 3 && t128 == 0) { mbar_arrive(bar_cons + 8 * (16 + 2 * i)); mbar_arrive(bar_cons + 8 * (17 + 2 * i)); }
      if (i + 2 < 8) issue(i + 2);
      TSC(13 + i);
      post_send(i, v);
    }
    prefetch(0); prefetch(1); prefetch(2);
    mbar_wait_cluster(bar_dfull + 8 * 3, 0);
#pragma unroll
    for (int c = 0; c < 4; c++) {
      const uint4 d = my_base[uslot_off(3) / 16 + c * 128];
      sum[c * 8 + 0] = bf_lo(d.x); sum[c * 8 + 1] = bf_hi(d.x); sum[c * 8 + 2] = bf_lo(d.y); sum[c * 8 + 3] = bf_hi(d.y);
      sum[c * 8 + 4] = bf_lo(d.z); sum[c * 8 + 5] = bf_hi(d.z); sum[c * 8 + 6] = bf_lo(d.w); sum[c * 8 + 7] = bf_hi(d.w);
    }
    consume(0);
    consume(1);
    wg_wait<0>();
    reg_fence(acc2[1]);
    TSC(20);
    consume(2);
    TSC(21);
    if (tid == 0) g_box[blockIdx.x].epoch = epoch + 1;

    {
      const int row0 = mb * BM + wg * 64 + w4 * 16 + g;
      uint32_t* o0 = reinterpret_cast<uint32_t*>(out + (size_t)row0 * D_MOD + j * BN2) + q;
      uint32_t* o1 = o0 + 8 * D_MOD / 2;
#pragma unroll
      for (int i = 0; i < 8; i++) {
        const uint32_t bb = b2s[i * 4 + q];
        o0[i * 4] = hadd2_bf(pack_bf16(acc2[1][4 * i] + sum[4 * i], acc2[1][4 * i + 1] + sum[4 * i + 1]), bb);
        o1[i * 4] = hadd2_bf(pack_bf16(acc2[1][4 * i + 2] + sum[4 * i + 2], acc2[1][4 * i + 3] + sum[4 * i + 3]), bb);
      }
    }
    if (t128 == 0) asm volatile("cp.async.bulk.wait_group 0;" ::: "memory");
    TSC(26);
    TS_FLUSH;
    asm volatile("barrier.cluster.arrive.relaxed.aligned;\nbarrier.cluster.wait.aligned;" ::: "memory");
  }
}

typedef CUresult (*EncodeFn)(CUtensorMap*, CUtensorMapDataType, cuuint32_t, void*, const cuuint64_t*, const cuuint64_t*,
                             const cuuint32_t*, const cuuint32_t*, CUtensorMapInterleave, CUtensorMapSwizzle,
                             CUtensorMapL2promotion, CUtensorMapFloatOOBfill);

}

extern "C" void kernel_launch(void* const* d_in, const int* in_sizes, int n_in, void* d_out, int out_size) {
  (void)in_sizes; (void)n_in; (void)out_size;
  static CUtensorMap tm_x, tm_w1, tm_w2;
  static const void* cached_w1 = nullptr; static const void* cached_w2 = nullptr; static const void* cached_x = nullptr;
  const void* w1 = d_in[1]; const void* w2 = d_in[3]; const void* xp = d_in[0];
  if (cached_w1 != w1 || cached_w2 != w2 || cached_x != xp) {
    void* fn = nullptr; cudaDriverEntryPointQueryResult st;
    cudaGetDriverEntryPoint("cuTensorMapEncodeTiled", &fn, cudaEnableDefault, &st);
    EncodeFn enc = (EncodeFn)fn;
    {
      cuuint64_t dims[3] = {64, (cuuint64_t)S_TOK, (cuuint64_t)(D_MOD / 64)};
      cuuint64_t strides[2] = {(cuuint64_t)D_MOD * 2, 128};
      cuuint32_t box[3] = {64, 64, 2};
      cuuint32_t es[3] = {1, 1, 1};
      enc(&tm_x, CU_TENSOR_MAP_DATA_TYPE_BFLOAT16, 3, const_cast<void*>(xp), dims, strides, box, es,
          CU_TENSOR_MAP_INTERLEAVE_NONE, CU_TENSOR_MAP_SWIZZLE_128B, CU_TENSOR_MAP_L2_PROMOTION_L2_128B, CU_TENSOR_MAP_FLOAT_OOB_FILL_NONE);
    }
    {
      cuuint64_t dims[3] = {32, (cuuint64_t)D_MOD, (cuuint64_t)(F_HID / 32)};
      cuuint64_t strides[2] = {(cuuint64_t)F_HID * 2, 64};
      cuuint32_t box[3] = {32, 32, 7};
      cuuint32_t es[3] = {1, 1, 1};
      enc(&tm_w1, CU_TENSOR_MAP_DATA_TYPE_BFLOAT16, 3, const_cast<void*>(w1), dims, strides, box, es,
          CU_TENSOR_MAP_INTERLEAVE_NONE, CU_TENSOR_MAP_SWIZZLE_64B, CU_TENSOR_MAP_L2_PROMOTION_L2_128B, CU_TENSOR_MAP_FLOAT_OOB_FILL_NONE);
    }
    {
      cuuint64_t dims[2] = {(cuuint64_t)D_MOD, (cuuint64_t)F_HID};
      cuuint64_t strides[1] = {(cuuint64_t)D_MOD * 2};
      cuuint32_t box[2] = {64, 112};
      cuuint32_t es[2] = {1, 1};
      enc(&tm_w2, CU_TENSOR_MAP_DATA_TYPE_BFLOAT16, 2, const_cast<void*>(w2), dims, strides, box, es,
          CU_TENSOR_MAP_INTERLEAVE_NONE, CU_TENSOR_MAP_SWIZZLE_128B, CU_TENSOR_MAP_L2_PROMOTION_L2_128B, CU_TENSOR_MAP_FLOAT_OOB_FILL_NONE);
    }
    cudaFuncSetAttribute(fused_mlp_kernel, cudaFuncAttributeMaxDynamicSharedMemorySize, SMEM_TOTAL);
    cached_w1 = w1; cached_w2 = w2; cached_x = xp;
  }
  fused_mlp_kernel<<<NMB * NSPLIT, NTHREADS, SMEM_TOTAL>>>(tm_x, tm_w1, tm_w2,
      (const __nv_bfloat16*)d_in[1], (const __nv_bfloat16*)d_in[3], (const __nv_bfloat16*)d_in[2], (const __nv_bfloat16*)d_in[4], (__nv_bfloat16*)d_out);
}
```

```cpp
#include <cuda_runtime.h>
#include <cuda_bf16.h>
#include <cuda.h>
#include <stdint.h>

namespace {

constexpr int S_TOK = 2048, D_MOD = 512, F_HID = 1792;
constexpr int BM = 128, NSPLIT = 8, BF = F_HID / NSPLIT;
constexpr int BN2 = D_MOD / NSPLIT;
constexpr int NMB = S_TOK / BM;
constexpr int SLOT_BYTES = 16384;
constexpr int W1_BYTES = 14336;
constexpr int W2_BYTES = 14336;
constexpr int Y_BYTES = BM * D_MOD * 2;
constexpr int NRING = 6;
constexpr int NLOAD = 32;
constexpr int OFF_RING = Y_BYTES;
__host__ __device__ constexpr int yslot_off(int s) { return (s >> 1) * 65536 + (s & 1) * 16384; }
__host__ __device__ constexpr int uslot_off(int s) { return (s >> 1) * 65536 + 32768 + (s & 1) * 16384; }
constexpr int DSLOT_BYTES = 16384;
constexpr int OFF_BAR = OFF_RING + NRING * SLOT_BYTES;
constexpr int OFF_MEAN = OFF_BAR + 640;
constexpr int OFF_B1 = OFF_MEAN + 512;
constexpr int OFF_B2 = OFF_B1 + 1024;
constexpr int SMEM_TOTAL = OFF_B2 + 256;
constexpr int NTHREADS = 384;
static_assert(SMEM_TOTAL <= 232448, "smem");

struct __align__(128) Mailbox { uint4 part[3 * 1024]; unsigned int epoch; unsigned int pad[31]; };
__device__ Mailbox g_box[NMB * NSPLIT];

#define TS_DECL
#define TS_FLUSH do {} while (0)
#define TS(role, idx) do {} while (0)
#define TSC(idx) do {} while (0)

__device__ __forceinline__ uint32_t smem_u32(const void* p) { return (uint32_t)__cvta_generic_to_shared(p); }
__device__ __forceinline__ uint32_t mapa(uint32_t a, uint32_t r) {
  uint32_t d; asm volatile("mapa.shared::cluster.u32 %0, %1, %2;" : "=r"(d) : "r"(a), "r"(r)); return d;
}
__device__ __forceinline__ void mbar_init(uint32_t bar, uint32_t cnt) {
  asm volatile("mbarrier.init.shared::cta.b64 [%0], %1;" :: "r"(bar), "r"(cnt) : "memory");
}
__device__ __forceinline__ void mbar_expect_tx(uint32_t bar, uint32_t bytes) {
  asm volatile("mbarrier.arrive.expect_tx.shared::cta.b64 _, [%0], %1;" :: "r"(bar), "r"(bytes) : "memory");
}
__device__ __forceinline__ void mbar_arrive(uint32_t bar) {
  asm volatile("mbarrier.arrive.shared::cta.b64 _, [%0];" :: "r"(bar) : "memory");
}
__device__ __forceinline__ void mbar_arrive_remote(uint32_t rbar) {
  asm volatile("mbarrier.arrive.release.cluster.shared::cluster.b64 _, [%0];" :: "r"(rbar) : "memory");
}
__device__ __forceinline__ void mbar_wait(uint32_t bar, uint32_t parity) {
  uint32_t done = 0; uint32_t it = 0;
  while (true) {
    asm volatile("{\n.reg .pred p;\nmbarrier.try_wait.parity.shared::cta.b64 p, [%1], %2;\nselp.u32 %0, 1, 0, p;\n}"
                 : "=r"(done) : "r"(bar), "r"(parity) : "memory");
    if (done) break;
    if (++it > (1u << 22)) asm volatile("trap;");
  }
}
__device__ __forceinline__ void mbar_wait_cluster(uint32_t bar, uint32_t parity) {
  uint32_t done = 0; uint32_t it = 0;
  while (true) {
    asm volatile("{\n.reg .pred p;\nmbarrier.try_wait.parity.acquire.cluster.shared::cta.b64 p, [%1], %2;\nselp.u32 %0, 1, 0, p;\n}"
                 : "=r"(done) : "r"(bar), "r"(parity) : "memory");
    if (done) break;
    if (++it > (1u << 22)) asm volatile("trap;");
  }
}
__device__ __forceinline__ void tma_load_3d(uint32_t dst, const CUtensorMap* tm, int c0, int c1, int c2, uint32_t bar) {
  asm volatile("cp.async.bulk.tensor.3d.shared::cluster.global.mbarrier::complete_tx::bytes [%0], [%1, {%3, %4, %5}], [%2];"
               :: "r"(dst), "l"(tm), "r"(bar), "r"(c0), "r"(c1), "r"(c2) : "memory");
}
__device__ __forceinline__ void tma_load_2d(uint32_t dst, const CUtensorMap* tm, int c0, int c1, uint32_t bar) {
  asm volatile("cp.async.bulk.tensor.2d.shared::cluster.global.mbarrier::complete_tx::bytes [%0], [%1, {%3, %4}], [%2];"
               :: "r"(dst), "l"(tm), "r"(bar), "r"(c0), "r"(c1) : "memory");
}
__device__ __forceinline__ void tma_prefetch_2d(const CUtensorMap* tm, int c0, int c1) {
  asm volatile("cp.async.bulk.prefetch.tensor.2d.L2.global.tile [%0, {%1, %2}];" :: "l"(tm), "r"(c0), "r"(c1) : "memory");
}
__device__ __forceinline__ void fence_async_smem() { asm volatile("fence.proxy.async.shared::cta;" ::: "memory"); }
__device__ __forceinline__ void wg_bar(int wg) {
  if (wg == 0) asm volatile("bar.sync 1, 128;" ::: "memory"); else asm volatile("bar.sync 2, 128;" ::: "memory");
}
__device__ __forceinline__ void wg_fence() { asm volatile("wgmma.fence.sync.aligned;" ::: "memory"); }
__device__ __forceinline__ void wg_commit() { asm volatile("wgmma.commit_group.sync.aligned;" ::: "memory"); }
template <int N> __device__ __forceinline__ void wg_wait() { asm volatile("wgmma.wait_group.sync.aligned %0;" :: "n"(N) : "memory"); }
template <int N> __device__ __forceinline__ void reg_fence(float (&d)[N]) {
#pragma unroll
  for (int i = 0; i < N; i++) asm volatile("" : "+f"(d[i]) :: "memory");
}
__device__ __forceinline__ uint64_t make_desc(uint32_t addr, uint32_t lbo, uint32_t sbo, uint32_t lt) {
  return (uint64_t)((addr & 0x3FFFF) >> 4) | ((uint64_t)(lbo >> 4) << 16) | ((uint64_t)(sbo >> 4) << 32) | ((uint64_t)lt << 62);
}
__device__ __forceinline__ uint32_t pack_bf16(float lo, float hi) {
  uint32_t r; asm("cvt.rn.bf16x2.f32 %0, %1, %2;" : "=r"(r) : "f"(hi), "f"(lo)); return r;
}
__device__ __forceinline__ float bf_lo(uint32_t v) { return __uint_as_float(v << 16); }
__device__ __forceinline__ float bf_hi(uint32_t v) { return __uint_as_float(v & 0xffff0000u); }
__device__ __forceinline__ float bf16r(float v) { return __bfloat162float(__float2bfloat16_rn(v)); }
__device__ __forceinline__ uint32_t hadd2_bf(uint32_t a, uint32_t b) {
  uint32_t r; asm("add.rn.bf16x2 %0, %1, %2;" : "=r"(r) : "r"(a), "r"(b)); return r;
}
__device__ __forceinline__ uint32_t hsub2_bf(uint32_t a, uint32_t b) {
  uint32_t r; asm("sub.rn.bf16x2 %0, %1, %2;" : "=r"(r) : "r"(a), "r"(b)); return r;
}
__device__ __forceinline__ float gelu_tanh(float u) {
  float inner = u * fmaf(0.035677408136300125f, u * u, 0.7978845608028654f);
  float th; asm("tanh.approx.f32 %0, %1;" : "=f"(th) : "f"(inner));
  float hu = 0.5f * u;
  return fmaf(hu, th, hu);
}
__device__ __forceinline__ void mma16816(float (&c)[4], uint32_t a0, uint32_t a1, uint32_t a2, uint32_t a3, uint32_t b0, uint32_t b1) {
  asm volatile("mma.sync.aligned.m16n8k16.row.col.f32.bf16.bf16.f32 {%0,%1,%2,%3}, {%4,%5,%6,%7}, {%8,%9}, {%0,%1,%2,%3};"
               : "+f"(c[0]), "+f"(c[1]), "+f"(c[2]), "+f"(c[3]) : "r"(a0), "r"(a1), "r"(a2), "r"(a3), "r"(b0), "r"(b1));
}

__device__ __forceinline__ void wgmma_ss_n224(float (&d)[112], uint64_t descA, uint64_t descB, int scaleD) {
  asm volatile("{\n.reg .pred p;\nsetp.ne.b32 p, %114, 0;\n"
    "wgmma.mma_async.sync.aligned.m64n224k16.f32.bf16.bf16 {%0, %1, %2, %3, %4, %5, %6, %7, %8, %9, %10, %11, %12, %13, %14, %15, %16, %17, %18, %19, %20, %21, %22, %23, %24, %25, %26, %27, %28, %29, %30, %31, %32, %33, %34, %35, %36, %37, %38, %39, %40, %41, %42, %43, %44, %45, %46, %47, %48, %49, %50, %51, %52, %53, %54, %55, %56, %57, %58, %59, %60, %61, %62, %63, %64, %65, %66, %67, %68, %69, %70, %71, %72, %73, %74, %75, %76, %77, %78, %79, %80, %81, %82, %83, %84, %85, %86, %87, %88, %89, %90, %91, %92, %93, %94, %95, %96, %97, %98, %99, %100, %101, %102, %103, %104, %105, %106, %107, %108, %109, %110, %111}, %112, %113, p, 1, 1, 0, 1;\n}\n"
    : "+f"(d[0]), "+f"(d[1]), "+f"(d[2]), "+f"(d[3]), "+f"(d[4]), "+f"(d[5]), "+f"(d[6]), "+f"(d[7]), "+f"(d[8]), "+f"(d[9]), "+f"(d[10]), "+f"(d[11]), "+f"(d[12]), "+f"(d[13]), "+f"(d[14]), "+f"(d[15]), "+f"(d[16]), "+f"(d[17]), "+f"(d[18]), "+f"(d[19]), "+f"(d[20]), "+f"(d[21]), "+f"(d[22]), "+f"(d[23]), "+f"(d[24]), "+f"(d[25]), "+f"(d[26]), "+f"(d[27]), "+f"(d[28]), "+f"(d[29]), "+f"(d[30]), "+f"(d[31]), "+f"(d[32]), "+f"(d[33]), "+f"(d[34]), "+f"(d[35]), "+f"(d[36]), "+f"(d[37]), "+f"(d[38]), "+f"(d[39]), "+f"(d[40]), "+f"(d[41]), "+f"(d[42]), "+f"(d[43]), "+f"(d[44]), "+f"(d[45]), "+f"(d[46]), "+f"(d[47]), "+f"(d[48]), "+f"(d[49]), "+f"(d[50]), "+f"(d[51]), "+f"(d[52]), "+f"(d[53]), "+f"(d[54]), "+f"(d[55]), "+f"(d[56]), "+f"(d[57]), "+f"(d[58]), "+f"(d[59]), "+f"(d[60]), "+f"(d[61]), "+f"(d[62]), "+f"(d[63]), "+f"(d[64]), "+f"(d[65]), "+f"(d[66]), "+f"(d[67]), "+f"(d[68]), "+f"(d[69]), "+f"(d[70]), "+f"(d[71]), "+f"(d[72]), "+f"(d[73]), "+f"(d[74]), "+f"(d[75]), "+f"(d[76]), "+f"(d[77]), "+f"(d[78]), "+f"(d[79]), "+f"(d[80]), "+f"(d[81]), "+f"(d[82]), "+f"(d[83]), "+f"(d[84]), "+f"(d[85]), "+f"(d[86]), "+f"(d[87]), "+f"(d[88]), "+f"(d[89]), "+f"(d[90]), "+f"(d[91]), "+f"(d[92]), "+f"(d[93]), "+f"(d[94]), "+f"(d[95]), "+f"(d[96]), "+f"(d[97]), "+f"(d[98]), "+f"(d[99]), "+f"(d[100]), "+f"(d[101]), "+f"(d[102]), "+f"(d[103]), "+f"(d[104]), "+f"(d[105]), "+f"(d[106]), "+f"(d[107]), "+f"(d[108]), "+f"(d[109]), "+f"(d[110]), "+f"(d[111])
    : "l"(descA), "l"(descB), "r"(scaleD));
}

__device__ __forceinline__ void wgmma_rs_n64(float (&d)[32], const uint32_t (&a)[4], uint64_t descB, int scaleD) {
  asm volatile("{\n.reg .pred p;\nsetp.ne.b32 p, %37, 0;\n"
    "wgmma.mma_async.sync.aligned.m64n64k16.f32.bf16.bf16 {%0, %1, %2, %3, %4, %5, %6, %7, %8, %9, %10, %11, %12, %13, %14, %15, %16, %17, %18, %19, %20, %21, %22, %23, %24, %25, %26, %27, %28, %29, %30, %31}, {%32, %33, %34, %35}, %36, p, 1, 1, 1;\n}\n"
    : "+f"(d[0]), "+f"(d[1]), "+f"(d[2]), "+f"(d[3]), "+f"(d[4]), "+f"(d[5]), "+f"(d[6]), "+f"(d[7]), "+f"(d[8]), "+f"(d[9]), "+f"(d[10]), "+f"(d[11]), "+f"(d[12]), "+f"(d[13]), "+f"(d[14]), "+f"(d[15]), "+f"(d[16]), "+f"(d[17]), "+f"(d[18]), "+f"(d[19]), "+f"(d[20]), "+f"(d[21]), "+f"(d[22]), "+f"(d[23]), "+f"(d[24]), "+f"(d[25]), "+f"(d[26]), "+f"(d[27]), "+f"(d[28]), "+f"(d[29]), "+f"(d[30]), "+f"(d[31])
    : "r"(a[0]), "r"(a[1]), "r"(a[2]), "r"(a[3]), "l"(descB), "r"(scaleD));
}

__device__ __forceinline__ void wgmma_rs_n224(float (&d)[112], const uint32_t (&a)[4], uint64_t descB, int scaleD) {
  asm volatile("{\n.reg .pred p;\nsetp.ne.b32 p, %117, 0;\n"
    "wgmma.mma_async.sync.aligned.m64n224k16.f32.bf16.bf16 {%0, %1, %2, %3, %4, %5, %6, %7, %8, %9, %10, %11, %12, %13, %14, %15, %16, %17, %18, %19, %20, %21, %22, %23, %24, %25, %26, %27, %28, %29, %30, %31, %32, %33, %34, %35, %36, %37, %38, %39, %40, %41, %42, %43, %44, %45, %46, %47, %48, %49, %50, %51, %52, %53, %54, %55, %56, %57, %58, %59, %60, %61, %62, %63, %64, %65, %66, %67, %68, %69, %70, %71, %72, %73, %74, %75, %76, %77, %78, %79, %80, %81, %82, %83, %84, %85, %86, %87, %88, %89, %90, %91, %92, %93, %94, %95, %96, %97, %98, %99, %100, %101, %102, %103, %104, %105, %106, %107, %108, %109, %110, %111}, {%112, %113, %114, %115}, %116, p, 1, 1, 1;\n}\n"
    : "+f"(d[0]), "+f"(d[1]), "+f"(d[2]), "+f"(d[3]), "+f"(d[4]), "+f"(d[5]), "+f"(d[6]), "+f"(d[7]), "+f"(d[8]), "+f"(d[9]), "+f"(d[10]), "+f"(d[11]), "+f"(d[12]), "+f"(d[13]), "+f"(d[14]), "+f"(d[15]), "+f"(d[16]), "+f"(d[17]), "+f"(d[18]), "+f"(d[19]), "+f"(d[20]), "+f"(d[21]), "+f"(d[22]), "+f"(d[23]), "+f"(d[24]), "+f"(d[25]), "+f"(d[26]), "+f"(d[27]), "+f"(d[28]), "+f"(d[29]), "+f"(d[30]), "+f"(d[31]), "+f"(d[32]), "+f"(d[33]), "+f"(d[34]), "+f"(d[35]), "+f"(d[36]), "+f"(d[37]), "+f"(d[38]), "+f"(d[39]), "+f"(d[40]), "+f"(d[41]), "+f"(d[42]), "+f"(d[43]), "+f"(d[44]), "+f"(d[45]), "+f"(d[46]), "+f"(d[47]), "+f"(d[48]), "+f"(d[49]), "+f"(d[50]), "+f"(d[51]), "+f"(d[52]), "+f"(d[53]), "+f"(d[54]), "+f"(d[55]), "+f"(d[56]), "+f"(d[57]), "+f"(d[58]), "+f"(d[59]), "+f"(d[60]), "+f"(d[61]), "+f"(d[62]), "+f"(d[63]), "+f"(d[64]), "+f"(d[65]), "+f"(d[66]), "+f"(d[67]), "+f"(d[68]), "+f"(d[69]), "+f"(d[70]), "+f"(d[71]), "+f"(d[72]), "+f"(d[73]), "+f"(d[74]), "+f"(d[75]), "+f"(d[76]), "+f"(d[77]), "+f"(d[78]), "+f"(d[79]), "+f"(d[80]), "+f"(d[81]), "+f"(d[82]), "+f"(d[83]), "+f"(d[84]), "+f"(d[85]), "+f"(d[86]), "+f"(d[87]), "+f"(d[88]), "+f"(d[89]), "+f"(d[90]), "+f"(d[91]), "+f"(d[92]), "+f"(d[93]), "+f"(d[94]), "+f"(d[95]), "+f"(d[96]), "+f"(d[97]), "+f"(d[98]), "+f"(d[99]), "+f"(d[100]), "+f"(d[101]), "+f"(d[102]), "+f"(d[103]), "+f"(d[104]), "+f"(d[105]), "+f"(d[106]), "+f"(d[107]), "+f"(d[108]), "+f"(d[109]), "+f"(d[110]), "+f"(d[111])
    : "r"(a[0]), "r"(a[1]), "r"(a[2]), "r"(a[3]), "l"(descB), "r"(scaleD));
}

__host__ __device__ constexpr int step_kind(int i) { return (i < 3 || i == 6) ? 0 : (i == 7 ? 2 : 1); }
__host__ __device__ constexpr int step_k(int i) { return i < 3 ? i : (i < 6 ? i - 3 : 3); }
__device__ __forceinline__ int step_slice(int i, int j) {
  const int kind = step_kind(i), k = step_k(i);
  const int base = (kind == 0) ? (j ^ 1) : j;
  return (k == 3) ? base : ((base + 2 * (k + 1)) & 7);
}

__host__ __device__ constexpr int load_off(int i) {
  return i < 6 ? OFF_RING + i * SLOT_BYTES
       : i < 10 ? yslot_off(i - 6)
       : i < 16 ? OFF_RING + (i - 10) * SLOT_BYTES
       : i < 18 ? yslot_off(i - 14)
       : i < 24 ? OFF_RING + (i - 18) * SLOT_BYTES
       : i < 26 ? yslot_off(i - 22)
       : OFF_RING + (i - 26) * SLOT_BYTES;
}
__host__ __device__ constexpr int load_dep(int i) { return i < 6 ? -1 : (i < 10 ? -2 : (i < 16 ? i - 10 : i - 8)); }

__global__ void __cluster_dims__(2, 1, 1) __launch_bounds__(NTHREADS, 1)
fused_mlp_kernel(const __nv_bfloat16* __restrict__ x, const __grid_constant__ CUtensorMap tm_w1, const __grid_constant__ CUtensorMap tm_w2,
                 const __nv_bfloat16* __restrict__ w1, const __nv_bfloat16* __restrict__ w2,
                 const __nv_bfloat16* __restrict__ b1, const __nv_bfloat16* __restrict__ b2, __nv_bfloat16* __restrict__ out)
{
  extern __shared__ __align__(1024) unsigned char smem[];
  const uint32_t sbase = smem_u32(smem);
  const uint32_t bar_full = sbase + OFF_BAR;
  const uint32_t bar_cons = sbase + OFF_BAR + 256;
  const uint32_t bar_dfull = sbase + OFF_BAR + 528;
  const uint32_t bar_peer = sbase + OFF_BAR + 560;
  const uint32_t bar_ln = sbase + OFF_BAR + 568;
  const uint32_t bar_dack = sbase + OFF_BAR + 576;
  const int tid = threadIdx.x, warp = tid >> 5, lane = tid & 31;
  const int mb = blockIdx.x >> 3, j = blockIdx.x & 7;

  TS_DECL
  TSC(0);
  if (warp >= 8) {
    asm volatile("setmaxnreg.dec.sync.aligned.u32 40;");
  if (warp == 8) {
    mbar_init(bar_full + 8 * lane, 1); mbar_init(bar_cons + 8 * lane, 2);
    if (lane < 4) mbar_init(bar_dfull + 8 * lane, 1);
    if (lane == 4) mbar_init(bar_peer, 2);
    if (lane == 5) mbar_init(bar_ln, 2);
    if (lane == 6 || lane == 7) mbar_init(bar_dack + 8 * (lane - 6), 1);
    asm volatile("fence.mbarrier_init.release.cluster;" ::: "memory");
    fence_async_smem();
    __syncwarp();
    if (lane >= 4 && lane < 8) mbar_expect_tx(bar_dfull + 8 * (lane - 4), DSLOT_BYTES);
    __syncwarp();
  }
    asm volatile("bar.sync 0, 384;" ::: "memory");
    if (warp == 9 && lane == 0) asm volatile("prefetch.tensormap [%0];" :: "l"(&tm_w1) : "memory");
    if (warp == 10 && lane == 0) asm volatile("prefetch.tensormap [%0];" :: "l"(&tm_w2) : "memory");
    if (warp == 11 && lane == 0) {
      asm volatile("cp.async.bulk.prefetch.L2.global [%0], %1;" :: "l"(reinterpret_cast<const unsigned char*>(w1) + (size_t)blockIdx.x * 14336), "r"(14336) : "memory");
      asm volatile("cp.async.bulk.prefetch.L2.global [%0], %1;" :: "l"(reinterpret_cast<const unsigned char*>(w2) + (size_t)blockIdx.x * 14336), "r"(14336) : "memory");
    }
    if (warp == 8 && lane == 0) {
      for (int i = 0; i < NRING; i++) {
        mbar_expect_tx(bar_full + 8 * i, W1_BYTES);
        tma_load_3d(sbase + OFF_RING + i * SLOT_BYTES, &tm_w1, 0, i * 32, j * 7, bar_full + 8 * i);
      }
      TS(2, 1);
    }
    __syncwarp();
    asm volatile("barrier.cluster.arrive.relaxed.aligned;" ::: "memory");
    if (warp == 8 && lane == 0) {
#pragma unroll
      for (int i = NRING; i < NLOAD; i++) {
        if (load_dep(i) >= 0) mbar_wait(bar_cons + 8 * load_dep(i), 0); else if (i == NRING) mbar_wait(bar_ln, 0);
        TS(2, i);
        const uint32_t dst = sbase + load_off(i);
        if (i < 16) {
          mbar_expect_tx(bar_full + 8 * i, W1_BYTES);
          tma_load_3d(dst, &tm_w1, 0, i * 32, j * 7, bar_full + 8 * i);
        } else {
          mbar_expect_tx(bar_full + 8 * i, W2_BYTES);
          tma_load_2d(dst, &tm_w2, step_slice((i - 16) >> 1, j) * BN2, j * BF + ((i - 16) & 1) * 112, bar_full + 8 * i);
        }
      }
    }
    __syncwarp();
    asm volatile("barrier.cluster.wait.aligned;" ::: "memory");
    if (warp == 9 && lane == 0) {
      for (int k = 0; k < 2; k++) {
        mbar_wait_cluster(bar_dfull + 8 * k, 0);
        mbar_arrive_remote(mapa(bar_dack + 8 * k, (j & 1) ^ 1));
      }
    }
    __syncwarp();
    asm volatile("barrier.cluster.arrive.relaxed.aligned;\nbarrier.cluster.wait.aligned;" ::: "memory");
  } else {
    asm volatile("setmaxnreg.inc.sync.aligned.u32 232;");
    asm volatile("bar.sync 0, 384;" ::: "memory");
    {
      const int wg_ = warp >> 2, w4_ = warp & 3;
      const unsigned char* xg = reinterpret_cast<const unsigned char*>(x + (size_t)(mb * BM + wg_ * 64 + w4_ * 16) * D_MOD) + (lane >> 4) * 1024 + (lane & 15) * 16;
      const uint32_t xs = sbase + wg_ * 65536 + ((lane & 15) >> 3) * 8192 + (w4_ * 16 + (lane >> 4)) * 128;
#pragma unroll
      for (int kq = 0; kq < 4; kq++) {
#pragma unroll
        for (int i = 0; i < 8; i++) {
          const uint32_t dst = xs + kq * 16384 + i * 256 + (((lane & 7) ^ ((2 * i + (lane >> 4)) & 7)) << 4);
          asm volatile("cp.async.cg.shared.global [%0], [%1], 16;" :: "r"(dst), "l"(xg + i * 2048 + kq * 256) : "memory");
        }
        asm volatile("cp.async.commit_group;" ::: "memory");
      }
    }
    TSC(29);
    const int wg = warp >> 2, w4 = warp & 3, t128 = tid & 127;
    const int q = lane & 3, g = lane >> 2;
    uint32_t* b1s = reinterpret_cast<uint32_t*>(smem + OFF_B1 + wg * 512);
    uint32_t* b2s = reinterpret_cast<uint32_t*>(smem + OFF_B2 + wg * 128);
    uint32_t bias_a = 0, bias_b = 0;
    if (t128 < BF / 2) bias_a = reinterpret_cast<const uint32_t*>(b1 + j * BF)[t128];
    if (t128 < BN2 / 2) bias_b = reinterpret_cast<const uint32_t*>(b2 + j * BN2)[t128];
    const uint32_t epoch = g_box[blockIdx.x].epoch;

    float r0, r1;
    uint32_t xa[16][4];
    TSC(24);
    {
      uint32_t xb[16][4];
      float cs[2][4], c0[2][4], c1[2][4];
#pragma unroll
      for (int u = 0; u < 2; u++)
#pragma unroll
        for (int e = 0; e < 4; e++) { cs[u][e] = 0.f; c0[u][e] = 0.f; c1[u][e] = 0.f; }
      const int lrow = w4 * 16 + (lane & 7) + ((lane >> 3) & 1) * 8;
      const uint32_t lbase = sbase + wg * 65536 + lrow * 128;
      const uint32_t ones = 0x3F803F80u;
#pragma unroll
      for (int ks = 0; ks < 32; ks++) {
        if (ks == 0) { asm volatile("cp.async.wait_group 3;" ::: "memory"); __syncwarp(); TSC(25); }
        if (ks == 8) { asm volatile("cp.async.wait_group 2;" ::: "memory"); __syncwarp(); }
        if (ks == 16) { asm volatile("cp.async.wait_group 1;" ::: "memory"); __syncwarp(); }
        if (ks == 24) { asm volatile("cp.async.wait_group 0;" ::: "memory"); __syncwarp(); TSC(22); }
        uint32_t (&a)[4] = ks < 16 ? xa[ks] : xb[ks - 16];
        const uint32_t addr = lbase + (ks >> 2) * 8192 + (((2 * (ks & 3) + (lane >> 4)) ^ (lane & 7)) << 4);
        asm volatile("ldmatrix.sync.aligned.m8n8.x4.shared.b16 {%0,%1,%2,%3}, [%4];" : "=r"(a[0]), "=r"(a[1]), "=r"(a[2]), "=r"(a[3]) : "r"(addr));
        mma16816(cs[ks & 1], a[0], a[1], a[2], a[3], ones, ones);
        mma16816(c0[ks & 1], a[0], a[1], a[2], a[3], a[0], a[2]);
        mma16816(c1[ks & 1], a[0], a[1], a[2], a[3], a[1], a[3]);
      }
      TSC(27);
      const int dsrc = g * 4 + (g >> 1);
      const float q0 = __shfl_sync(0xffffffffu, (g & 1) ? c0[0][1] + c0[1][1] : c0[0][0] + c0[1][0], dsrc);
      const float q1 = __shfl_sync(0xffffffffu, (g & 1) ? c1[0][3] + c1[1][3] : c1[0][2] + c1[1][2], dsrc);
      const float m0 = (cs[0][0] + cs[1][0]) * (1.0f / D_MOD), m1 = (cs[0][2] + cs[1][2]) * (1.0f / D_MOD);
      const uint32_t mm0 = pack_bf16(m0, m0), mm1 = pack_bf16(m1, m1);
#pragma unroll
      for (int ks = 16; ks < 32; ks++) {
        const uint32_t addr = lbase + (ks >> 2) * 8192 + (((2 * (ks & 3) + (lane >> 4)) ^ (lane & 7)) << 4);
        asm volatile("stmatrix.sync.aligned.m8n8.x4.shared.b16 [%0], {%1,%2,%3,%4};" :: "r"(addr),
                     "r"(hsub2_bf(xb[ks - 16][0], mm0)), "r"(hsub2_bf(xb[ks - 16][1], mm1)),
                     "r"(hsub2_bf(xb[ks - 16][2], mm0)), "r"(hsub2_bf(xb[ks - 16][3], mm1)) : "memory");
      }
#pragma unroll
      for (int ks = 0; ks < 16; ks++) {
        xa[ks][0] = hsub2_bf(xa[ks][0], mm0); xa[ks][1] = hsub2_bf(xa[ks][1], mm1);
        xa[ks][2] = hsub2_bf(xa[ks][2], mm0); xa[ks][3] = hsub2_bf(xa[ks][3], mm1);
      }
      const float v0 = fmaxf(fmaf(-m0, m0, q0 * (1.0f / D_MOD)), 0.f), v1 = fmaxf(fmaf(-m1, m1, q1 * (1.0f / D_MOD)), 0.f);
      r0 = 1.0f / bf16r(sqrtf(bf16r(bf16r(v0) + 1e-5f)));
      r1 = 1.0f / bf16r(sqrtf(bf16r(bf16r(v1) + 1e-5f)));
    }
    TSC(1);
    fence_async_smem();
    wg_bar(wg);
    if (t128 == 0) mbar_arrive(bar_ln);
    asm volatile("barrier.cluster.arrive.relaxed.aligned;" ::: "memory");
    TSC(2);

    uint32_t h[14][4];
    {
      float acc[112];
#pragma unroll
      for (int kb = 0; kb < 16; kb++) {
        mbar_wait(bar_full + 8 * kb, 0);
        wg_fence();
        const uint32_t abase = sbase + wg * 65536 + (kb >> 1) * 8192 + (kb & 1) * 64;
        const uint32_t bbase = sbase + load_off(kb);
#pragma unroll
        for (int kk = 0; kk < 2; kk++) {
          if (kb < 8) wgmma_rs_n224(acc, xa[2 * kb + kk], make_desc(bbase + kk * 1024, 2048, 512, 2), (kb | kk) != 0);
          else wgmma_ss_n224(acc, make_desc(abase + kk * 32, 16, 1024, 1), make_desc(bbase + kk * 1024, 2048, 512, 2), 1);
        }
        wg_commit();
        if (kb > 0) { wg_wait<1>(); if (t128 == 0) mbar_arrive(bar_cons + 8 * (kb - 1)); }
      }
      if (t128 < BF / 2) b1s[t128] = bias_a;
      if (t128 < BN2 / 2) b2s[t128] = bias_b;
      wg_bar(wg);
      wg_wait<0>();
      reg_fence(acc);
      asm volatile("barrier.cluster.wait.aligned;" ::: "memory");
      if (t128 == 0) { mbar_arrive(bar_cons + 8 * 15); mbar_arrive_remote(mapa(bar_peer, (j & 1) ^ 1)); }
      TSC(11);

#pragma unroll
      for (int i = 0; i < 28; i++) {
        const uint32_t bb = b1s[i * 4 + q];
        uint32_t p0 = hadd2_bf(pack_bf16(acc[4 * i] * r0, acc[4 * i + 1] * r0), bb);
        uint32_t p1 = hadd2_bf(pack_bf16(acc[4 * i + 2] * r1, acc[4 * i + 3] * r1), bb);
        h[i >> 1][(i & 1) * 2 + 0] = pack_bf16(gelu_tanh(bf_lo(p0)), gelu_tanh(bf_hi(p0)));
        h[i >> 1][(i & 1) * 2 + 1] = pack_bf16(gelu_tanh(bf_lo(p1)), gelu_tanh(bf_hi(p1)));
      }
    }

    const uint32_t par = (epoch + 1) & 1;
    float acc2[2][32];
    float sum[32];
    uint4 pf[3][4];
    const uint32_t peer_base = mapa(sbase + wg * 8192, (j & 1) ^ 1);
    const uint32_t peer_dfull = mapa(bar_dfull, (j & 1) ^ 1);
    uint4* my_base = reinterpret_cast<uint4*>(smem) + wg * 512 + t128;
    const uint4* in_part = &g_box[blockIdx.x].part[wg * 512 + t128];
    auto ld_part = [&](const uint4* p) {
      uint4 v;
      asm volatile("ld.relaxed.gpu.global.v4.u32 {%0, %1, %2, %3}, [%4];" : "=r"(v.x), "=r"(v.y), "=r"(v.z), "=r"(v.w) : "l"(p) : "memory");
      return v;
    };
    auto prefetch = [&](int k) {
#pragma unroll
      for (int c = 0; c < 4; c++) pf[k][c] = ld_part(in_part + k * 1024 + c * 128);
    };
    auto consume = [&](int k) {
#pragma unroll
      for (int c = 0; c < 4; c++) {
        uint4 v = pf[k][c];
        uint32_t it = 0;
        while ((((v.x ^ par) | (v.y ^ par) | (v.z ^ par) | (v.w ^ par)) & 1u) != 0) {
          v = ld_part(in_part + k * 1024 + c * 128);
          if (++it > (1u << 20)) asm volatile("trap;");
        }
        sum[c * 8 + 0] += bf_lo(v.x & ~1u); sum[c * 8 + 1] += bf_hi(v.x);
        sum[c * 8 + 2] += bf_lo(v.y & ~1u); sum[c * 8 + 3] += bf_hi(v.y);
        sum[c * 8 + 4] += bf_lo(v.z & ~1u); sum[c * 8 + 5] += bf_hi(v.z);
        sum[c * 8 + 6] += bf_lo(v.w & ~1u); sum[c * 8 + 7] += bf_hi(v.w);
      }
    };
    auto post_pack = [&](int st, float (&a)[32], uint4 (&v)[4]) {
      const int kind = step_kind(st), k = step_k(st);
      if (kind == 0) {
#pragma unroll
        for (int c = 0; c < 4; c++) {
          v[c].x = pack_bf16(a[c * 8 + 0], a[c * 8 + 1]); v[c].y = pack_bf16(a[c * 8 + 2], a[c * 8 + 3]);
          v[c].z = pack_bf16(a[c * 8 + 4], a[c * 8 + 5]); v[c].w = pack_bf16(a[c * 8 + 6], a[c * 8 + 7]);
        }
      } else {
#pragma unroll
        for (int c = 0; c < 4; c++) {
          const uint4 d = v[c];
          v[c].x = (pack_bf16(a[c * 8 + 0] + bf_lo(d.x), a[c * 8 + 1] + bf_hi(d.x)) & ~1u) | par;
          v[c].y = (pack_bf16(a[c * 8 + 2] + bf_lo(d.y), a[c * 8 + 3] + bf_hi(d.y)) & ~1u) | par;
          v[c].z = (pack_bf16(a[c * 8 + 4] + bf_lo(d.z), a[c * 8 + 5] + bf_hi(d.z)) & ~1u) | par;
          v[c].w = (pack_bf16(a[c * 8 + 6] + bf_lo(d.w), a[c * 8 + 7] + bf_hi(d.w)) & ~1u) | par;
        }
      }
      (void)k;
    };
    auto post_send = [&](int st, uint4 (&v)[4]) {
      const int kind = step_kind(st), k = step_k(st);
      if (kind == 0) {
        if (st == 0) mbar_wait(bar_cons + 8 * 15, 0);
        if (k >= 2) mbar_wait_cluster(bar_dack + 8 * (k - 2), 0);
#pragma unroll
        for (int c = 0; c < 4; c++) my_base[yslot_off(k & 1) / 16 + c * 128] = v[c];
        fence_async_smem();
        wg_bar(wg);
        if (t128 == 0) {
          if (st == 0) mbar_wait_cluster(bar_peer, 0);
          asm volatile("cp.async.bulk.shared::cluster.shared::cta.mbarrier::complete_tx::bytes [%0], [%1], %2, [%3];"
                       :: "r"(peer_base + uslot_off(k)), "r"(sbase + yslot_off(k & 1) + wg * 8192), "r"(8192), "r"(peer_dfull + 8 * k) : "memory");
        }
      } else {
#pragma unroll
        for (int c = 0; c < 4; c++) my_base[uslot_off(k) / 16 + c * 128] = v[c];
        fence_async_smem();
        wg_bar(wg);
        if (t128 == 0) {
          const int dest = (j + 2 * (k + 1)) & 7;
          const uint4* p = &g_box[mb * NSPLIT + dest].part[k * 1024 + wg * 512];
          asm volatile("cp.async.bulk.global.shared::cta.bulk_group [%0], [%1], %2;"
                       :: "l"(p), "r"(sbase + uslot_off(k) + wg * 8192), "r"(8192) : "memory");
          asm volatile("cp.async.bulk.commit_group;" ::: "memory");
        }
      }
    };
    auto issue = [&](int i) {
      mbar_wait(bar_full + 8 * (16 + 2 * i), 0);
      wg_fence();
#pragma unroll
      for (int ks = 0; ks < 7; ks++) {
        wgmma_rs_n64(acc2[i & 1], h[ks], make_desc(sbase + load_off(16 + 2 * i) + ks * 2048, 16, 1024, 1), ks != 0);
      }
      mbar_wait(bar_full + 8 * (17 + 2 * i), 0);
      wg_fence();
#pragma unroll
      for (int ks = 0; ks < 7; ks++) {
        wgmma_rs_n64(acc2[i & 1], h[7 + ks], make_desc(sbase + load_off(17 + 2 * i) + ks * 2048, 16, 1024, 1), 1);
      }
      wg_commit();
    };
    TSC(12);
    issue(0);
    issue(1);
#pragma unroll
    for (int i = 0; i < 7; i++) {
      uint4 v[4];
      if (step_kind(i) == 1) {
        mbar_wait_cluster(bar_dfull + 8 * step_k(i), 0);
#pragma unroll
        for (int c = 0; c < 4; c++) v[c] = my_base[uslot_off(step_k(i)) / 16 + c * 128];
      }
      wg_wait<1>();
      reg_fence(acc2[i & 1]);
      post_pack(i, acc2[i & 1], v);
      if (i <= 3 && t128 == 0) { mbar_arrive(bar_cons + 8 * (16 + 2 * i)); mbar_arrive(bar_cons + 8 * (17 + 2 * i)); }
      if (i + 2 < 8) issue(i + 2);
      TSC(13 + i);
      post_send(i, v);
    }
    prefetch(0); prefetch(1); prefetch(2);
    mbar_wait_cluster(bar_dfull + 8 * 3, 0);
#pragma unroll
    for (int c = 0; c < 4; c++) {
      const uint4 d = my_base[uslot_off(3) / 16 + c * 128];
      sum[c * 8 + 0] = bf_lo(d.x); sum[c * 8 + 1] = bf_hi(d.x); sum[c * 8 + 2] = bf_lo(d.y); sum[c * 8 + 3] = bf_hi(d.y);
      sum[c * 8 + 4] = bf_lo(d.z); sum[c * 8 + 5] = bf_hi(d.z); sum[c * 8 + 6] = bf_lo(d.w); sum[c * 8 + 7] = bf_hi(d.w);
    }
    consume(0);
    consume(1);
    wg_wait<0>();
    reg_fence(acc2[1]);
    TSC(20);
    consume(2);
    TSC(21);
    if (tid == 0) g_box[blockIdx.x].epoch = epoch + 1;

    {
      const int row0 = mb * BM + wg * 64 + w4 * 16 + g;
      uint32_t* o0 = reinterpret_cast<uint32_t*>(out + (size_t)row0 * D_MOD + j * BN2) + q;
      uint32_t* o1 = o0 + 8 * D_MOD / 2;
#pragma unroll
      for (int i = 0; i < 8; i++) {
        const uint32_t bb = b2s[i * 4 + q];
        o0[i * 4] = hadd2_bf(pack_bf16(acc2[1][4 * i] + sum[4 * i], acc2[1][4 * i + 1] + sum[4 * i + 1]), bb);
        o1[i * 4] = hadd2_bf(pack_bf16(acc2[1][4 * i + 2] + sum[4 * i + 2], acc2[1][4 * i + 3] + sum[4 * i + 3]), bb);
      }
    }
    if (t128 == 0) asm volatile("cp.async.bulk.wait_group 0;" ::: "memory");
    TSC(26);
    TS_FLUSH;
    asm volatile("barrier.cluster.arrive.relaxed.aligned;\nbarrier.cluster.wait.aligned;" ::: "memory");
  }
}

typedef CUresult (*EncodeFn)(CUtensorMap*, CUtensorMapDataType, cuuint32_t, void*, const cuuint64_t*, const cuuint64_t*,
                             const cuuint32_t*, const cuuint32_t*, CUtensorMapInterleave, CUtensorMapSwizzle,
                             CUtensorMapL2promotion, CUtensorMapFloatOOBfill);

}

extern "C" void kernel_launch(void* const* d_in, const int* in_sizes, int n_in, void* d_out, int out_size) {
  (void)in_sizes; (void)n_in; (void)out_size;
  static CUtensorMap tm_w1, tm_w2;
  static const void* cached_w1 = nullptr; static const void* cached_w2 = nullptr; static const void* cached_x = nullptr;
  const void* w1 = d_in[1]; const void* w2 = d_in[3]; const void* xp = d_in[0];
  if (cached_w1 != w1 || cached_w2 != w2 || cached_x != xp) {
    void* fn = nullptr; cudaDriverEntryPointQueryResult st;
    cudaGetDriverEntryPoint("cuTensorMapEncodeTiled", &fn, cudaEnableDefault, &st);
    EncodeFn enc = (EncodeFn)fn;
    {
      cuuint64_t dims[3] = {32, (cuuint64_t)D_MOD, (cuuint64_t)(F_HID / 32)};
      cuuint64_t strides[2] = {(cuuint64_t)F_HID * 2, 64};
      cuuint32_t box[3] = {32, 32, 7};
      cuuint32_t es[3] = {1, 1, 1};
      enc(&tm_w1, CU_TENSOR_MAP_DATA_TYPE_BFLOAT16, 3, const_cast<void*>(w1), dims, strides, box, es,
          CU_TENSOR_MAP_INTERLEAVE_NONE, CU_TENSOR_MAP_SWIZZLE_64B, CU_TENSOR_MAP_L2_PROMOTION_L2_128B, CU_TENSOR_MAP_FLOAT_OOB_FILL_NONE);
    }
    {
      cuuint64_t dims[2] = {(cuuint64_t)D_MOD, (cuuint64_t)F_HID};
      cuuint64_t strides[1] = {(cuuint64_t)D_MOD * 2};
      cuuint32_t box[2] = {64, 112};
      cuuint32_t es[2] = {1, 1};
      enc(&tm_w2, CU_TENSOR_MAP_DATA_TYPE_BFLOAT16, 2, const_cast<void*>(w2), dims, strides, box, es,
          CU_TENSOR_MAP_INTERLEAVE_NONE, CU_TENSOR_MAP_SWIZZLE_128B, CU_TENSOR_MAP_L2_PROMOTION_L2_128B, CU_TENSOR_MAP_FLOAT_OOB_FILL_NONE);
    }
    cudaFuncSetAttribute(fused_mlp_kernel, cudaFuncAttributeMaxDynamicSharedMemorySize, SMEM_TOTAL);
    cached_w1 = w1; cached_w2 = w2; cached_x = xp;
  }
  fused_mlp_kernel<<<NMB * NSPLIT, NTHREADS, SMEM_TOTAL>>>((const __nv_bfloat16*)d_in[0], tm_w1, tm_w2,
      (const __nv_bfloat16*)d_in[1], (const __nv_bfloat16*)d_in[3], (const __nv_bfloat16*)d_in[2], (const __nv_bfloat16*)d_in[4], (__nv_bfloat16*)d_out);
}
```

```cpp
#include <cuda_runtime.h>
#include <cuda_bf16.h>
#include <cuda.h>
#include <stdint.h>

namespace {

constexpr int S_TOK = 2048, D_MOD = 512, F_HID = 1792;
constexpr int BM = 128, NSPLIT = 8, BF = F_HID / NSPLIT;
constexpr int BN2 = D_MOD / NSPLIT;
constexpr int NMB = S_TOK / BM;
constexpr int SLOT_BYTES = 16384;
constexpr int W1_BYTES = 14336;
constexpr int W2_BYTES = 14336;
constexpr int Y_BYTES = BM * D_MOD * 2;
constexpr int NRING = 6;
constexpr int NLOAD = 32;
constexpr int OFF_RING = Y_BYTES;
__host__ __device__ constexpr int yslot_off(int s) { return (s >> 1) * 65536 + (s & 1) * 16384; }
__host__ __device__ constexpr int uslot_off(int s) { return (s >> 1) * 65536 + 32768 + (s & 1) * 16384; }
constexpr int DSLOT_BYTES = 16384;
constexpr int OFF_BAR = OFF_RING + NRING * SLOT_BYTES;
constexpr int OFF_MEAN = OFF_BAR + 768;
constexpr int OFF_B1 = OFF_MEAN + 512;
constexpr int OFF_B2 = OFF_B1 + 1024;
constexpr int SMEM_TOTAL = OFF_B2 + 256;
constexpr int NTHREADS = 384;
static_assert(SMEM_TOTAL <= 232448, "smem");

struct __align__(128) Mailbox { uint4 part[3 * 1024]; unsigned int epoch; unsigned int pad[31]; };
__device__ Mailbox g_box[NMB * NSPLIT];

#define TS_DECL
#define TS_FLUSH do {} while (0)
#define TS(role, idx) do {} while (0)
#define TSC(idx) do {} while (0)

__device__ __forceinline__ uint32_t smem_u32(const void* p) { return (uint32_t)__cvta_generic_to_shared(p); }
__device__ __forceinline__ uint32_t mapa(uint32_t a, uint32_t r) {
  uint32_t d; asm volatile("mapa.shared::cluster.u32 %0, %1, %2;" : "=r"(d) : "r"(a), "r"(r)); return d;
}
__device__ __forceinline__ void mbar_init(uint32_t bar, uint32_t cnt) {
  asm volatile("mbarrier.init.shared::cta.b64 [%0], %1;" :: "r"(bar), "r"(cnt) : "memory");
}
__device__ __forceinline__ void mbar_expect_tx(uint32_t bar, uint32_t bytes) {
  asm volatile("mbarrier.arrive.expect_tx.shared::cta.b64 _, [%0], %1;" :: "r"(bar), "r"(bytes) : "memory");
}
__device__ __forceinline__ void mbar_arrive(uint32_t bar) {
  asm volatile("mbarrier.arrive.shared::cta.b64 _, [%0];" :: "r"(bar) : "memory");
}
__device__ __forceinline__ void mbar_arrive_remote(uint32_t rbar) {
  asm volatile("mbarrier.arrive.release.cluster.shared::cluster.b64 _, [%0];" :: "r"(rbar) : "memory");
}
__device__ __forceinline__ void mbar_wait(uint32_t bar, uint32_t parity) {
  uint32_t done = 0; uint32_t it = 0;
  while (true) {
    asm volatile("{\n.reg .pred p;\nmbarrier.try_wait.parity.shared::cta.b64 p, [%1], %2;\nselp.u32 %0, 1, 0, p;\n}"
                 : "=r"(done) : "r"(bar), "r"(parity) : "memory");
    if (done) break;
    if (++it > (1u << 22)) asm volatile("trap;");
  }
}
__device__ __forceinline__ void mbar_wait_cluster(uint32_t bar, uint32_t parity) {
  uint32_t done = 0; uint32_t it = 0;
  while (true) {
    asm volatile("{\n.reg .pred p;\nmbarrier.try_wait.parity.acquire.cluster.shared::cta.b64 p, [%1], %2;\nselp.u32 %0, 1, 0, p;\n}"
                 : "=r"(done) : "r"(bar), "r"(parity) : "memory");
    if (done) break;
    if (++it > (1u << 22)) asm volatile("trap;");
  }
}
__device__ __forceinline__ void tma_load_3d(uint32_t dst, const CUtensorMap* tm, int c0, int c1, int c2, uint32_t bar) {
  asm volatile("cp.async.bulk.tensor.3d.shared::cluster.global.mbarrier::complete_tx::bytes [%0], [%1, {%3, %4, %5}], [%2];"
               :: "r"(dst), "l"(tm), "r"(bar), "r"(c0), "r"(c1), "r"(c2) : "memory");
}
__device__ __forceinline__ void tma_load_2d(uint32_t dst, const CUtensorMap* tm, int c0, int c1, uint32_t bar) {
  asm volatile("cp.async.bulk.tensor.2d.shared::cluster.global.mbarrier::complete_tx::bytes [%0], [%1, {%3, %4}], [%2];"
               :: "r"(dst), "l"(tm), "r"(bar), "r"(c0), "r"(c1) : "memory");
}
__device__ __forceinline__ void tma_prefetch_2d(const CUtensorMap* tm, int c0, int c1) {
  asm volatile("cp.async.bulk.prefetch.tensor.2d.L2.global.tile [%0, {%1, %2}];" :: "l"(tm), "r"(c0), "r"(c1) : "memory");
}
__device__ __forceinline__ void fence_async_smem() { asm volatile("fence.proxy.async.shared::cta;" ::: "memory"); }
__device__ __forceinline__ void wg_bar(int wg) {
  if (wg == 0) asm volatile("bar.sync 1, 128;" ::: "memory"); else asm volatile("bar.sync 2, 128;" ::: "memory");
}
__device__ __forceinline__ void wg_fence() { asm volatile("wgmma.fence.sync.aligned;" ::: "memory"); }
__device__ __forceinline__ void wg_commit() { asm volatile("wgmma.commit_group.sync.aligned;" ::: "memory"); }
template <int N> __device__ __forceinline__ void wg_wait() { asm volatile("wgmma.wait_group.sync.aligned %0;" :: "n"(N) : "memory"); }
template <int N> __device__ __forceinline__ void reg_fence(float (&d)[N]) {
#pragma unroll
  for (int i = 0; i < N; i++) asm volatile("" : "+f"(d[i]) :: "memory");
}
__device__ __forceinline__ uint64_t make_desc(uint32_t addr, uint32_t lbo, uint32_t sbo, uint32_t lt) {
  return (uint64_t)((addr & 0x3FFFF) >> 4) | ((uint64_t)(lbo >> 4) << 16) | ((uint64_t)(sbo >> 4) << 32) | ((uint64_t)lt << 62);
}
__device__ __forceinline__ uint32_t pack_bf16(float lo, float hi) {
  uint32_t r; asm("cvt.rn.bf16x2.f32 %0, %1, %2;" : "=r"(r) : "f"(hi), "f"(lo)); return r;
}
__device__ __forceinline__ float bf_lo(uint32_t v) { return __uint_as_float(v << 16); }
__device__ __forceinline__ float bf_hi(uint32_t v) { return __uint_as_float(v & 0xffff0000u); }
__device__ __forceinline__ float bf16r(float v) { return __bfloat162float(__float2bfloat16_rn(v)); }
__device__ __forceinline__ uint32_t hadd2_bf(uint32_t a, uint32_t b) {
  uint32_t r; asm("add.rn.bf16x2 %0, %1, %2;" : "=r"(r) : "r"(a), "r"(b)); return r;
}
__device__ __forceinline__ uint32_t hsub2_bf(uint32_t a, uint32_t b) {
  uint32_t r; asm("sub.rn.bf16x2 %0, %1, %2;" : "=r"(r) : "r"(a), "r"(b)); return r;
}
__device__ __forceinline__ float gelu_tanh(float u) {
  float inner = u * fmaf(0.035677408136300125f, u * u, 0.7978845608028654f);
  float th; asm("tanh.approx.f32 %0, %1;" : "=f"(th) : "f"(inner));
  float hu = 0.5f * u;
  return fmaf(hu, th, hu);
}
__device__ __forceinline__ void mma16816(float (&c)[4], uint32_t a0, uint32_t a1, uint32_t a2, uint32_t a3, uint32_t b0, uint32_t b1) {
  asm volatile("mma.sync.aligned.m16n8k16.row.col.f32.bf16.bf16.f32 {%0,%1,%2,%3}, {%4,%5,%6,%7}, {%8,%9}, {%0,%1,%2,%3};"
               : "+f"(c[0]), "+f"(c[1]), "+f"(c[2]), "+f"(c[3]) : "r"(a0), "r"(a1), "r"(a2), "r"(a3), "r"(b0), "r"(b1));
}

__device__ __forceinline__ void wgmma_ss_n224(float (&d)[112], uint64_t descA, uint64_t descB, int scaleD) {
  asm volatile("{\n.reg .pred p;\nsetp.ne.b32 p, %114, 0;\n"
    "wgmma.mma_async.sync.aligned.m64n224k16.f32.bf16.bf16 {%0, %1, %2, %3, %4, %5, %6, %7, %8, %9, %10, %11, %12, %13, %14, %15, %16, %17, %18, %19, %20, %21, %22, %23, %24, %25, %26, %27, %28, %29, %30, %31, %32, %33, %34, %35, %36, %37, %38, %39, %40, %41, %42, %43, %44, %45, %46, %47, %48, %49, %50, %51, %52, %53, %54, %55, %56, %57, %58, %59, %60, %61, %62, %63, %64, %65, %66, %67, %68, %69, %70, %71, %72, %73, %74, %75, %76, %77, %78, %79, %80, %81, %82, %83, %84, %85, %86, %87, %88, %89, %90, %91, %92, %93, %94, %95, %96, %97, %98, %99, %100, %101, %102, %103, %104, %105, %106, %107, %108, %109, %110, %111}, %112, %113, p, 1, 1, 0, 1;\n}\n"
    : "+f"(d[0]), "+f"(d[1]), "+f"(d[2]), "+f"(d[3]), "+f"(d[4]), "+f"(d[5]), "+f"(d[6]), "+f"(d[7]), "+f"(d[8]), "+f"(d[9]), "+f"(d[10]), "+f"(d[11]), "+f"(d[12]), "+f"(d[13]), "+f"(d[14]), "+f"(d[15]), "+f"(d[16]), "+f"(d[17]), "+f"(d[18]), "+f"(d[19]), "+f"(d[20]), "+f"(d[21]), "+f"(d[22]), "+f"(d[23]), "+f"(d[24]), "+f"(d[25]), "+f"(d[26]), "+f"(d[27]), "+f"(d[28]), "+f"(d[29]), "+f"(d[30]), "+f"(d[31]), "+f"(d[32]), "+f"(d[33]), "+f"(d[34]), "+f"(d[35]), "+f"(d[36]), "+f"(d[37]), "+f"(d[38]), "+f"(d[39]), "+f"(d[40]), "+f"(d[41]), "+f"(d[42]), "+f"(d[43]), "+f"(d[44]), "+f"(d[45]), "+f"(d[46]), "+f"(d[47]), "+f"(d[48]), "+f"(d[49]), "+f"(d[50]), "+f"(d[51]), "+f"(d[52]), "+f"(d[53]), "+f"(d[54]), "+f"(d[55]), "+f"(d[56]), "+f"(d[57]), "+f"(d[58]), "+f"(d[59]), "+f"(d[60]), "+f"(d[61]), "+f"(d[62]), "+f"(d[63]), "+f"(d[64]), "+f"(d[65]), "+f"(d[66]), "+f"(d[67]), "+f"(d[68]), "+f"(d[69]), "+f"(d[70]), "+f"(d[71]), "+f"(d[72]), "+f"(d[73]), "+f"(d[74]), "+f"(d[75]), "+f"(d[76]), "+f"(d[77]), "+f"(d[78]), "+f"(d[79]), "+f"(d[80]), "+f"(d[81]), "+f"(d[82]), "+f"(d[83]), "+f"(d[84]), "+f"(d[85]), "+f"(d[86]), "+f"(d[87]), "+f"(d[88]), "+f"(d[89]), "+f"(d[90]), "+f"(d[91]), "+f"(d[92]), "+f"(d[93]), "+f"(d[94]), "+f"(d[95]), "+f"(d[96]), "+f"(d[97]), "+f"(d[98]), "+f"(d[99]), "+f"(d[100]), "+f"(d[101]), "+f"(d[102]), "+f"(d[103]), "+f"(d[104]), "+f"(d[105]), "+f"(d[106]), "+f"(d[107]), "+f"(d[108]), "+f"(d[109]), "+f"(d[110]), "+f"(d[111])
    : "l"(descA), "l"(descB), "r"(scaleD));
}

__device__ __forceinline__ void wgmma_rs_n64(float (&d)[32], const uint32_t (&a)[4], uint64_t descB, int scaleD) {
  asm volatile("{\n.reg .pred p;\nsetp.ne.b32 p, %37, 0;\n"
    "wgmma.mma_async.sync.aligned.m64n64k16.f32.bf16.bf16 {%0, %1, %2, %3, %4, %5, %6, %7, %8, %9, %10, %11, %12, %13, %14, %15, %16, %17, %18, %19, %20, %21, %22, %23, %24, %25, %26, %27, %28, %29, %30, %31}, {%32, %33, %34, %35}, %36, p, 1, 1, 1;\n}\n"
    : "+f"(d[0]), "+f"(d[1]), "+f"(d[2]), "+f"(d[3]), "+f"(d[4]), "+f"(d[5]), "+f"(d[6]), "+f"(d[7]), "+f"(d[8]), "+f"(d[9]), "+f"(d[10]), "+f"(d[11]), "+f"(d[12]), "+f"(d[13]), "+f"(d[14]), "+f"(d[15]), "+f"(d[16]), "+f"(d[17]), "+f"(d[18]), "+f"(d[19]), "+f"(d[20]), "+f"(d[21]), "+f"(d[22]), "+f"(d[23]), "+f"(d[24]), "+f"(d[25]), "+f"(d[26]), "+f"(d[27]), "+f"(d[28]), "+f"(d[29]), "+f"(d[30]), "+f"(d[31])
    : "r"(a[0]), "r"(a[1]), "r"(a[2]), "r"(a[3]), "l"(descB), "r"(scaleD));
}

__device__ __forceinline__ void wgmma_rs_n224(float (&d)[112], const uint32_t (&a)[4], uint64_t descB, int scaleD) {
  asm volatile("{\n.reg .pred p;\nsetp.ne.b32 p, %117, 0;\n"
    "wgmma.mma_async.sync.aligned.m64n224k16.f32.bf16.bf16 {%0, %1, %2, %3, %4, %5, %6, %7, %8, %9, %10, %11, %12, %13, %14, %15, %16, %17, %18, %19, %20, %21, %22, %23, %24, %25, %26, %27, %28, %29, %30, %31, %32, %33, %34, %35, %36, %37, %38, %39, %40, %41, %42, %43, %44, %45, %46, %47, %48, %49, %50, %51, %52, %53, %54, %55, %56, %57, %58, %59, %60, %61, %62, %63, %64, %65, %66, %67, %68, %69, %70, %71, %72, %73, %74, %75, %76, %77, %78, %79, %80, %81, %82, %83, %84, %85, %86, %87, %88, %89, %90, %91, %92, %93, %94, %95, %96, %97, %98, %99, %100, %101, %102, %103, %104, %105, %106, %107, %108, %109, %110, %111}, {%112, %113, %114, %115}, %116, p, 1, 1, 1;\n}\n"
    : "+f"(d[0]), "+f"(d[1]), "+f"(d[2]), "+f"(d[3]), "+f"(d[4]), "+f"(d[5]), "+f"(d[6]), "+f"(d[7]), "+f"(d[8]), "+f"(d[9]), "+f"(d[10]), "+f"(d[11]), "+f"(d[12]), "+f"(d[13]), "+f"(d[14]), "+f"(d[15]), "+f"(d[16]), "+f"(d[17]), "+f"(d[18]), "+f"(d[19]), "+f"(d[20]), "+f"(d[21]), "+f"(d[22]), "+f"(d[23]), "+f"(d[24]), "+f"(d[25]), "+f"(d[26]), "+f"(d[27]), "+f"(d[28]), "+f"(d[29]), "+f"(d[30]), "+f"(d[31]), "+f"(d[32]), "+f"(d[33]), "+f"(d[34]), "+f"(d[35]), "+f"(d[36]), "+f"(d[37]), "+f"(d[38]), "+f"(d[39]), "+f"(d[40]), "+f"(d[41]), "+f"(d[42]), "+f"(d[43]), "+f"(d[44]), "+f"(d[45]), "+f"(d[46]), "+f"(d[47]), "+f"(d[48]), "+f"(d[49]), "+f"(d[50]), "+f"(d[51]), "+f"(d[52]), "+f"(d[53]), "+f"(d[54]), "+f"(d[55]), "+f"(d[56]), "+f"(d[57]), "+f"(d[58]), "+f"(d[59]), "+f"(d[60]), "+f"(d[61]), "+f"(d[62]), "+f"(d[63]), "+f"(d[64]), "+f"(d[65]), "+f"(d[66]), "+f"(d[67]), "+f"(d[68]), "+f"(d[69]), "+f"(d[70]), "+f"(d[71]), "+f"(d[72]), "+f"(d[73]), "+f"(d[74]), "+f"(d[75]), "+f"(d[76]), "+f"(d[77]), "+f"(d[78]), "+f"(d[79]), "+f"(d[80]), "+f"(d[81]), "+f"(d[82]), "+f"(d[83]), "+f"(d[84]), "+f"(d[85]), "+f"(d[86]), "+f"(d[87]), "+f"(d[88]), "+f"(d[89]), "+f"(d[90]), "+f"(d[91]), "+f"(d[92]), "+f"(d[93]), "+f"(d[94]), "+f"(d[95]), "+f"(d[96]), "+f"(d[97]), "+f"(d[98]), "+f"(d[99]), "+f"(d[100]), "+f"(d[101]), "+f"(d[102]), "+f"(d[103]), "+f"(d[104]), "+f"(d[105]), "+f"(d[106]), "+f"(d[107]), "+f"(d[108]), "+f"(d[109]), "+f"(d[110]), "+f"(d[111])
    : "r"(a[0]), "r"(a[1]), "r"(a[2]), "r"(a[3]), "l"(descB), "r"(scaleD));
}

__host__ __device__ constexpr int step_kind(int i) { return (i < 3 || i == 6) ? 0 : (i == 7 ? 2 : 1); }
__host__ __device__ constexpr int step_k(int i) { return i < 3 ? i : (i < 6 ? i - 3 : 3); }
__device__ __forceinline__ int step_slice(int i, int j) {
  const int kind = step_kind(i), k = step_k(i);
  const int base = (kind == 0) ? (j ^ 1) : j;
  return (k == 3) ? base : ((base + 2 * (k + 1)) & 7);
}

__host__ __device__ constexpr int load_off(int i) {
  return i < 6 ? OFF_RING + i * SLOT_BYTES
       : i < 10 ? yslot_off(i - 6)
       : i < 16 ? OFF_RING + (i - 10) * SLOT_BYTES
       : i < 18 ? yslot_off(i - 14)
       : i < 24 ? OFF_RING + (i - 18) * SLOT_BYTES
       : i < 26 ? yslot_off(i - 22)
       : OFF_RING + (i - 26) * SLOT_BYTES;
}
__host__ __device__ constexpr int load_dep(int i) { return i < 6 ? -1 : (i < 10 ? -2 : (i < 16 ? i - 10 : i - 8)); }

__global__ void __cluster_dims__(2, 1, 1) __launch_bounds__(NTHREADS, 1)
fused_mlp_kernel(const __nv_bfloat16* __restrict__ x, const __grid_constant__ CUtensorMap tm_w1, const __grid_constant__ CUtensorMap tm_w2,
                 const __nv_bfloat16* __restrict__ w1, const __nv_bfloat16* __restrict__ w2,
                 const __nv_bfloat16* __restrict__ b1, const __nv_bfloat16* __restrict__ b2, __nv_bfloat16* __restrict__ out)
{
  extern __shared__ __align__(1024) unsigned char smem[];
  const uint32_t sbase = smem_u32(smem);
  const uint32_t bar_full = sbase + OFF_BAR;
  const uint32_t bar_cons = sbase + OFF_BAR + 256;
  const uint32_t bar_dfull = sbase + OFF_BAR + 528;
  const uint32_t bar_peer = sbase + OFF_BAR + 560;
  const uint32_t bar_ln = sbase + OFF_BAR + 568;
  const uint32_t bar_staged = sbase + OFF_BAR + 640;
  const uint32_t bar_dack = sbase + OFF_BAR + 576;
  const int tid = threadIdx.x, warp = tid >> 5, lane = tid & 31;
  const int mb = blockIdx.x >> 3, j = blockIdx.x & 7;

  TS_DECL
  TSC(0);
  if (warp >= 8) {
    asm volatile("setmaxnreg.dec.sync.aligned.u32 40;");
  if (warp == 8) {
    mbar_init(bar_full + 8 * lane, 1); mbar_init(bar_cons + 8 * lane, 2);
    if (lane < 4) mbar_init(bar_dfull + 8 * lane, 1);
    if (lane >= 16) mbar_init(bar_staged + 8 * (lane - 16), 128);
    if (lane == 4) mbar_init(bar_peer, 2);
    if (lane == 5) mbar_init(bar_ln, 2);
    if (lane == 6 || lane == 7) mbar_init(bar_dack + 8 * (lane - 6), 1);
    asm volatile("fence.mbarrier_init.release.cluster;" ::: "memory");
    fence_async_smem();
    __syncwarp();
    if (lane >= 4 && lane < 8) mbar_expect_tx(bar_dfull + 8 * (lane - 4), DSLOT_BYTES);
    __syncwarp();
  }
    asm volatile("bar.arrive 0, 384;" ::: "memory");
    if (warp == 8 && lane == 0) {
      for (int i = 0; i < NRING; i++) {
        mbar_expect_tx(bar_full + 8 * i, W1_BYTES);
        tma_load_3d(sbase + OFF_RING + i * SLOT_BYTES, &tm_w1, 0, i * 32, j * 7, bar_full + 8 * i);
      }
      asm volatile("prefetch.tensormap [%0];" :: "l"(&tm_w2) : "memory");
      asm volatile("cp.async.bulk.prefetch.L2.global [%0], %1;" :: "l"(reinterpret_cast<const unsigned char*>(w1) + (size_t)blockIdx.x * 14336), "r"(14336) : "memory");
      asm volatile("cp.async.bulk.prefetch.L2.global [%0], %1;" :: "l"(reinterpret_cast<const unsigned char*>(w2) + (size_t)blockIdx.x * 14336), "r"(14336) : "memory");
      TS(2, 1);
    }
    __syncwarp();
    asm volatile("barrier.cluster.arrive.relaxed.aligned;" ::: "memory");
    if (warp == 8 && lane == 0) {
#pragma unroll
      for (int i = NRING; i < NLOAD; i++) {
        if (load_dep(i) >= 0) mbar_wait(bar_cons + 8 * load_dep(i), 0); else if (i == NRING) mbar_wait(bar_ln, 0);
        TS(2, i);
        const uint32_t dst = sbase + load_off(i);
        if (i < 16) {
          mbar_expect_tx(bar_full + 8 * i, W1_BYTES);
          tma_load_3d(dst, &tm_w1, 0, i * 32, j * 7, bar_full + 8 * i);
        } else {
          mbar_expect_tx(bar_full + 8 * i, W2_BYTES);
          tma_load_2d(dst, &tm_w2, step_slice((i - 16) >> 1, j) * BN2, j * BF + ((i - 16) & 1) * 112, bar_full + 8 * i);
        }
      }
    }
    __syncwarp();
    asm volatile("barrier.cluster.wait.aligned;" ::: "memory");
    if (warp == 11 && lane == 0) {
      for (int k = 0; k < 2; k++) {
        mbar_wait_cluster(bar_dfull + 8 * k, 0);
        mbar_arrive_remote(mapa(bar_dack + 8 * k, (j & 1) ^ 1));
      }
    }
    if ((warp == 9 || warp == 10) && lane == 0) {
      const int wg = warp - 9;
      const uint32_t peer_base = mapa(sbase + wg * 8192, (j & 1) ^ 1);
      const uint32_t peer_dfull = mapa(bar_dfull, (j & 1) ^ 1);
#pragma unroll
      for (int st = 0; st < 7; st++) {
        const int k = step_k(st);
        mbar_wait(bar_staged + 8 * (wg * 8 + st), 0);
        if (step_kind(st) == 0) {
          if (st == 0) mbar_wait_cluster(bar_peer, 0);
          asm volatile("cp.async.bulk.shared::cluster.shared::cta.mbarrier::complete_tx::bytes [%0], [%1], %2, [%3];"
                       :: "r"(peer_base + uslot_off(k)), "r"(sbase + yslot_off(k & 1) + wg * 8192), "r"(8192), "r"(peer_dfull + 8 * k) : "memory");
        } else {
          const int dest = (j + 2 * (k + 1)) & 7;
          const uint4* p = &g_box[mb * NSPLIT + dest].part[k * 1024 + wg * 512];
          asm volatile("cp.async.bulk.global.shared::cta.bulk_group [%0], [%1], %2;"
                       :: "l"(p), "r"(sbase + uslot_off(k) + wg * 8192), "r"(8192) : "memory");
          asm volatile("cp.async.bulk.commit_group;" ::: "memory");
        }
      }
      asm volatile("cp.async.bulk.wait_group 0;" ::: "memory");
    }
    __syncwarp();
    asm volatile("barrier.cluster.arrive.relaxed.aligned;\nbarrier.cluster.wait.aligned;" ::: "memory");
  } else {
    asm volatile("setmaxnreg.inc.sync.aligned.u32 232;");
    {
      const int wg_ = warp >> 2, w4_ = warp & 3;
      const unsigned char* xg = reinterpret_cast<const unsigned char*>(x + (size_t)(mb * BM + wg_ * 64 + w4_ * 16) * D_MOD) + (lane >> 4) * 1024 + (lane & 15) * 16;
      const uint32_t xs = sbase + wg_ * 65536 + ((lane & 15) >> 3) * 8192 + (w4_ * 16 + (lane >> 4)) * 128;
#pragma unroll
      for (int kq = 0; kq < 4; kq++) {
#pragma unroll
        for (int i = 0; i < 8; i++) {
          const uint32_t dst = xs + kq * 16384 + i * 256 + (((lane & 7) ^ ((2 * i + (lane >> 4)) & 7)) << 4);
          asm volatile("cp.async.cg.shared.global [%0], [%1], 16;" :: "r"(dst), "l"(xg + i * 2048 + kq * 256) : "memory");
        }
        asm volatile("cp.async.commit_group;" ::: "memory");
      }
    }
    TSC(29);
    const int wg = warp >> 2, w4 = warp & 3, t128 = tid & 127;
    const int q = lane & 3, g = lane >> 2;
    uint32_t* b1s = reinterpret_cast<uint32_t*>(smem + OFF_B1 + wg * 512);
    uint32_t* b2s = reinterpret_cast<uint32_t*>(smem + OFF_B2 + wg * 128);
    uint32_t bias_a = 0, bias_b = 0;
    if (t128 < BF / 2) bias_a = reinterpret_cast<const uint32_t*>(b1 + j * BF)[t128];
    if (t128 < BN2 / 2) bias_b = reinterpret_cast<const uint32_t*>(b2 + j * BN2)[t128];
    const uint32_t epoch = g_box[blockIdx.x].epoch;

    float r0, r1;
    uint32_t xa[16][4];
    TSC(24);
    {
      uint32_t xb[16][4];
      float cs[2][4], c0[2][4], c1[2][4];
#pragma unroll
      for (int u = 0; u < 2; u++)
#pragma unroll
        for (int e = 0; e < 4; e++) { cs[u][e] = 0.f; c0[u][e] = 0.f; c1[u][e] = 0.f; }
      const int lrow = w4 * 16 + (lane & 7) + ((lane >> 3) & 1) * 8;
      const uint32_t lbase = sbase + wg * 65536 + lrow * 128;
      const uint32_t ones = 0x3F803F80u;
#pragma unroll
      for (int ks = 0; ks < 32; ks++) {
        if (ks == 0) { asm volatile("cp.async.wait_group 3;" ::: "memory"); __syncwarp(); TSC(25); }
        if (ks == 8) { asm volatile("cp.async.wait_group 2;" ::: "memory"); __syncwarp(); }
        if (ks == 16) { asm volatile("cp.async.wait_group 1;" ::: "memory"); __syncwarp(); }
        if (ks == 24) { asm volatile("cp.async.wait_group 0;" ::: "memory"); __syncwarp(); TSC(22); }
        uint32_t (&a)[4] = ks < 16 ? xa[ks] : xb[ks - 16];
        const uint32_t addr = lbase + (ks >> 2) * 8192 + (((2 * (ks & 3) + (lane >> 4)) ^ (lane & 7)) << 4);
        asm volatile("ldmatrix.sync.aligned.m8n8.x4.shared.b16 {%0,%1,%2,%3}, [%4];" : "=r"(a[0]), "=r"(a[1]), "=r"(a[2]), "=r"(a[3]) : "r"(addr));
        mma16816(cs[ks & 1], a[0], a[1], a[2], a[3], ones, ones);
        mma16816(c0[ks & 1], a[0], a[1], a[2], a[3], a[0], a[2]);
        mma16816(c1[ks & 1], a[0], a[1], a[2], a[3], a[1], a[3]);
      }
      TSC(27);
      const int dsrc = g * 4 + (g >> 1);
      const float q0 = __shfl_sync(0xffffffffu, (g & 1) ? c0[0][1] + c0[1][1] : c0[0][0] + c0[1][0], dsrc);
      const float q1 = __shfl_sync(0xffffffffu, (g & 1) ? c1[0][3] + c1[1][3] : c1[0][2] + c1[1][2], dsrc);
      const float m0 = (cs[0][0] + cs[1][0]) * (1.0f / D_MOD), m1 = (cs[0][2] + cs[1][2]) * (1.0f / D_MOD);
      const uint32_t mm0 = pack_bf16(m0, m0), mm1 = pack_bf16(m1, m1);
#pragma unroll
      for (int ks = 16; ks < 32; ks++) {
        const uint32_t addr = lbase + (ks >> 2) * 8192 + (((2 * (ks & 3) + (lane >> 4)) ^ (lane & 7)) << 4);
        asm volatile("stmatrix.sync.aligned.m8n8.x4.shared.b16 [%0], {%1,%2,%3,%4};" :: "r"(addr),
                     "r"(hsub2_bf(xb[ks - 16][0], mm0)), "r"(hsub2_bf(xb[ks - 16][1], mm1)),
                     "r"(hsub2_bf(xb[ks - 16][2], mm0)), "r"(hsub2_bf(xb[ks - 16][3], mm1)) : "memory");
      }
#pragma unroll
      for (int ks = 0; ks < 16; ks++) {
        xa[ks][0] = hsub2_bf(xa[ks][0], mm0); xa[ks][1] = hsub2_bf(xa[ks][1], mm1);
        xa[ks][2] = hsub2_bf(xa[ks][2], mm0); xa[ks][3] = hsub2_bf(xa[ks][3], mm1);
      }
      const float v0 = fmaxf(fmaf(-m0, m0, q0 * (1.0f / D_MOD)), 0.f), v1 = fmaxf(fmaf(-m1, m1, q1 * (1.0f / D_MOD)), 0.f);
      r0 = 1.0f / bf16r(sqrtf(bf16r(bf16r(v0) + 1e-5f)));
      r1 = 1.0f / bf16r(sqrtf(bf16r(bf16r(v1) + 1e-5f)));
    }
    TSC(1);
    fence_async_smem();
    asm volatile("bar.sync 0, 384;" ::: "memory");
    if (t128 == 0) mbar_arrive(bar_ln);
    asm volatile("barrier.cluster.arrive.relaxed.aligned;" ::: "memory");
    TSC(2);

    uint32_t h[14][4];
    {
      float acc[112];
#pragma unroll
      for (int kb = 0; kb < 16; kb++) {
        mbar_wait(bar_full + 8 * kb, 0);
        wg_fence();
        const uint32_t abase = sbase + wg * 65536 + (kb >> 1) * 8192 + (kb & 1) * 64;
        const uint32_t bbase = sbase + load_off(kb);
#pragma unroll
        for (int kk = 0; kk < 2; kk++) {
          if (kb < 8) wgmma_rs_n224(acc, xa[2 * kb + kk], make_desc(bbase + kk * 1024, 2048, 512, 2), (kb | kk) != 0);
          else wgmma_ss_n224(acc, make_desc(abase + kk * 32, 16, 1024, 1), make_desc(bbase + kk * 1024, 2048, 512, 2), 1);
        }
        wg_commit();
        if (kb > 0) { wg_wait<1>(); if (t128 == 0) mbar_arrive(bar_cons + 8 * (kb - 1)); }
      }
      if (t128 < BF / 2) b1s[t128] = bias_a;
      if (t128 < BN2 / 2) b2s[t128] = bias_b;
      wg_bar(wg);
      wg_wait<0>();
      reg_fence(acc);
      asm volatile("barrier.cluster.wait.aligned;" ::: "memory");
      if (t128 == 0) { mbar_arrive(bar_cons + 8 * 15); mbar_arrive_remote(mapa(bar_peer, (j & 1) ^ 1)); }
      TSC(11);

#pragma unroll
      for (int i = 0; i < 28; i++) {
        const uint32_t bb = b1s[i * 4 + q];
        uint32_t p0 = hadd2_bf(pack_bf16(acc[4 * i] * r0, acc[4 * i + 1] * r0), bb);
        uint32_t p1 = hadd2_bf(pack_bf16(acc[4 * i + 2] * r1, acc[4 * i + 3] * r1), bb);
        h[i >> 1][(i & 1) * 2 + 0] = pack_bf16(gelu_tanh(bf_lo(p0)), gelu_tanh(bf_hi(p0)));
        h[i >> 1][(i & 1) * 2 + 1] = pack_bf16(gelu_tanh(bf_lo(p1)), gelu_tanh(bf_hi(p1)));
      }
    }

    const uint32_t par = (epoch + 1) & 1;
    float acc2[2][32];
    float sum[32];
    uint4 pf[3][4];
    uint4* my_base = reinterpret_cast<uint4*>(smem) + wg * 512 + t128;
    const uint4* in_part = &g_box[blockIdx.x].part[wg * 512 + t128];
    auto ld_part = [&](const uint4* p) {
      uint4 v;
      asm volatile("ld.relaxed.gpu.global.v4.u32 {%0, %1, %2, %3}, [%4];" : "=r"(v.x), "=r"(v.y), "=r"(v.z), "=r"(v.w) : "l"(p) : "memory");
      return v;
    };
    auto prefetch = [&](int k) {
#pragma unroll
      for (int c = 0; c < 4; c++) pf[k][c] = ld_part(in_part + k * 1024 + c * 128);
    };
    auto consume = [&](int k) {
#pragma unroll
      for (int c = 0; c < 4; c++) {
        uint4 v = pf[k][c];
        uint32_t it = 0;
        while ((((v.x ^ par) | (v.y ^ par) | (v.z ^ par) | (v.w ^ par)) & 1u) != 0) {
          v = ld_part(in_part + k * 1024 + c * 128);
          if (++it > (1u << 20)) asm volatile("trap;");
        }
        sum[c * 8 + 0] += bf_lo(v.x & ~1u); sum[c * 8 + 1] += bf_hi(v.x);
        sum[c * 8 + 2] += bf_lo(v.y & ~1u); sum[c * 8 + 3] += bf_hi(v.y);
        sum[c * 8 + 4] += bf_lo(v.z & ~1u); sum[c * 8 + 5] += bf_hi(v.z);
        sum[c * 8 + 6] += bf_lo(v.w & ~1u); sum[c * 8 + 7] += bf_hi(v.w);
      }
    };
    auto post_pack = [&](int st, float (&a)[32], uint4 (&v)[4]) {
      const int kind = step_kind(st), k = step_k(st);
      if (kind == 0) {
#pragma unroll
        for (int c = 0; c < 4; c++) {
          v[c].x = pack_bf16(a[c * 8 + 0], a[c * 8 + 1]); v[c].y = pack_bf16(a[c * 8 + 2], a[c * 8 + 3]);
          v[c].z = pack_bf16(a[c * 8 + 4], a[c * 8 + 5]); v[c].w = pack_bf16(a[c * 8 + 6], a[c * 8 + 7]);
        }
      } else {
#pragma unroll
        for (int c = 0; c < 4; c++) {
          const uint4 d = v[c];
          v[c].x = (pack_bf16(a[c * 8 + 0] + bf_lo(d.x), a[c * 8 + 1] + bf_hi(d.x)) & ~1u) | par;
          v[c].y = (pack_bf16(a[c * 8 + 2] + bf_lo(d.y), a[c * 8 + 3] + bf_hi(d.y)) & ~1u) | par;
          v[c].z = (pack_bf16(a[c * 8 + 4] + bf_lo(d.z), a[c * 8 + 5] + bf_hi(d.z)) & ~1u) | par;
          v[c].w = (pack_bf16(a[c * 8 + 6] + bf_lo(d.w), a[c * 8 + 7] + bf_hi(d.w)) & ~1u) | par;
        }
      }
      (void)k;
    };
    auto post_send = [&](int st, uint4 (&v)[4]) {
      const int kind = step_kind(st), k = step_k(st);
      if (kind == 0) {
        if (st == 0) mbar_wait(bar_cons + 8 * 15, 0);
        if (k >= 2) mbar_wait_cluster(bar_dack + 8 * (k - 2), 0);
#pragma unroll
        for (int c = 0; c < 4; c++) my_base[yslot_off(k & 1) / 16 + c * 128] = v[c];
      } else {
#pragma unroll
        for (int c = 0; c < 4; c++) my_base[uslot_off(k) / 16 + c * 128] = v[c];
      }
      fence_async_smem();
      mbar_arrive(bar_staged + 8 * (wg * 8 + st));
    };
    auto issue = [&](int i) {
      mbar_wait(bar_full + 8 * (16 + 2 * i), 0);
      wg_fence();
#pragma unroll
      for (int ks = 0; ks < 7; ks++) {
        wgmma_rs_n64(acc2[i & 1], h[ks], make_desc(sbase + load_off(16 + 2 * i) + ks * 2048, 16, 1024, 1), ks != 0);
      }
      mbar_wait(bar_full + 8 * (17 + 2 * i), 0);
      wg_fence();
#pragma unroll
      for (int ks = 0; ks < 7; ks++) {
        wgmma_rs_n64(acc2[i & 1], h[7 + ks], make_desc(sbase + load_off(17 + 2 * i) + ks * 2048, 16, 1024, 1), 1);
      }
      wg_commit();
    };
    TSC(12);
    issue(0);
    issue(1);
#pragma unroll
    for (int i = 0; i < 7; i++) {
      uint4 v[4];
      if (step_kind(i) == 1) {
        mbar_wait_cluster(bar_dfull + 8 * step_k(i), 0);
#pragma unroll
        for (int c = 0; c < 4; c++) v[c] = my_base[uslot_off(step_k(i)) / 16 + c * 128];
      }
      wg_wait<1>();
      reg_fence(acc2[i & 1]);
      post_pack(i, acc2[i & 1], v);
      if (i <= 3 && t128 == 0) { mbar_arrive(bar_cons + 8 * (16 + 2 * i)); mbar_arrive(bar_cons + 8 * (17 + 2 * i)); }
      post_send(i, v);
      if (i + 2 < 8) issue(i + 2);
      TSC(13 + i);
    }
    prefetch(0); prefetch(1); prefetch(2);
    mbar_wait_cluster(bar_dfull + 8 * 3, 0);
#pragma unroll
    for (int c = 0; c < 4; c++) {
      const uint4 d = my_base[uslot_off(3) / 16 + c * 128];
      sum[c * 8 + 0] = bf_lo(d.x); sum[c * 8 + 1] = bf_hi(d.x); sum[c * 8 + 2] = bf_lo(d.y); sum[c * 8 + 3] = bf_hi(d.y);
      sum[c * 8 + 4] = bf_lo(d.z); sum[c * 8 + 5] = bf_hi(d.z); sum[c * 8 + 6] = bf_lo(d.w); sum[c * 8 + 7] = bf_hi(d.w);
    }
    consume(0);
    consume(1);
    wg_wait<0>();
    reg_fence(acc2[1]);
    TSC(20);
    consume(2);
    TSC(21);
    if (tid == 0) g_box[blockIdx.x].epoch = epoch + 1;

    {
      const int row0 = mb * BM + wg * 64 + w4 * 16 + g;
      uint32_t* o0 = reinterpret_cast<uint32_t*>(out + (size_t)row0 * D_MOD + j * BN2) + q;
      uint32_t* o1 = o0 + 8 * D_MOD / 2;
#pragma unroll
      for (int i = 0; i < 8; i++) {
        const uint32_t bb = b2s[i * 4 + q];
        o0[i * 4] = hadd2_bf(pack_bf16(acc2[1][4 * i] + sum[4 * i], acc2[1][4 * i + 1] + sum[4 * i + 1]), bb);
        o1[i * 4] = hadd2_bf(pack_bf16(acc2[1][4 * i + 2] + sum[4 * i + 2], acc2[1][4 * i + 3] + sum[4 * i + 3]), bb);
      }
    }
    TSC(26);
    TS_FLUSH;
    asm volatile("barrier.cluster.arrive.relaxed.aligned;\nbarrier.cluster.wait.aligned;" ::: "memory");
  }
}

typedef CUresult (*EncodeFn)(CUtensorMap*, CUtensorMapDataType, cuuint32_t, void*, const cuuint64_t*, const cuuint64_t*,
                             const cuuint32_t*, const cuuint32_t*, CUtensorMapInterleave, CUtensorMapSwizzle,
                             CUtensorMapL2promotion, CUtensorMapFloatOOBfill);

}

extern "C" void kernel_launch(void* const* d_in, const int* in_sizes, int n_in, void* d_out, int out_size) {
  (void)in_sizes; (void)n_in; (void)out_size;
  static CUtensorMap tm_w1, tm_w2;
  static const void* cached_w1 = nullptr; static const void* cached_w2 = nullptr; static const void* cached_x = nullptr;
  const void* w1 = d_in[1]; const void* w2 = d_in[3]; const void* xp = d_in[0];
  if (cached_w1 != w1 || cached_w2 != w2 || cached_x != xp) {
    void* fn = nullptr; cudaDriverEntryPointQueryResult st;
    cudaGetDriverEntryPoint("cuTensorMapEncodeTiled", &fn, cudaEnableDefault, &st);
    EncodeFn enc = (EncodeFn)fn;
    {
      cuuint64_t dims[3] = {32, (cuuint64_t)D_MOD, (cuuint64_t)(F_HID / 32)};
      cuuint64_t strides[2] = {(cuuint64_t)F_HID * 2, 64};
      cuuint32_t box[3] = {32, 32, 7};
      cuuint32_t es[3] = {1, 1, 1};
      enc(&tm_w1, CU_TENSOR_MAP_DATA_TYPE_BFLOAT16, 3, const_cast<void*>(w1), dims, strides, box, es,
          CU_TENSOR_MAP_INTERLEAVE_NONE, CU_TENSOR_MAP_SWIZZLE_64B, CU_TENSOR_MAP_L2_PROMOTION_L2_128B, CU_TENSOR_MAP_FLOAT_OOB_FILL_NONE);
    }
    {
      cuuint64_t dims[2] = {(cuuint64_t)D_MOD, (cuuint64_t)F_HID};
      cuuint64_t strides[1] = {(cuuint64_t)D_MOD * 2};
      cuuint32_t box[2] = {64, 112};
      cuuint32_t es[2] = {1, 1};
      enc(&tm_w2, CU_TENSOR_MAP_DATA_TYPE_BFLOAT16, 2, const_cast<void*>(w2), dims, strides, box, es,
          CU_TENSOR_MAP_INTERLEAVE_NONE, CU_TENSOR_MAP_SWIZZLE_128B, CU_TENSOR_MAP_L2_PROMOTION_L2_128B, CU_TENSOR_MAP_FLOAT_OOB_FILL_NONE);
    }
    cudaFuncSetAttribute(fused_mlp_kernel, cudaFuncAttributeMaxDynamicSharedMemorySize, SMEM_TOTAL);
    cached_w1 = w1; cached_w2 = w2; cached_x = xp;
  }
  fused_mlp_kernel<<<NMB * NSPLIT, NTHREADS, SMEM_TOTAL>>>((const __nv_bfloat16*)d_in[0], tm_w1, tm_w2,
      (const __nv_bfloat16*)d_in[1], (const __nv_bfloat16*)d_in[3], (const __nv_bfloat16*)d_in[2], (const __nv_bfloat16*)d_in[4], (__nv_bfloat16*)d_out);
}
```

```cpp
#include <cuda_runtime.h>
#include <cuda_bf16.h>
#include <cuda.h>
#include <stdint.h>

namespace {

constexpr int S_TOK = 2048, D_MOD = 512, F_HID = 1792;
constexpr int BM = 128, NSPLIT = 8, BF = F_HID / NSPLIT;
constexpr int BN2 = D_MOD / NSPLIT;
constexpr int NMB = S_TOK / BM;
constexpr int STAGE_BYTES = 14336;
constexpr int Y_BYTES = BM * D_MOD * 2;
constexpr int NRING = 6;
constexpr int NLOAD = 32;
constexpr int OFF_RING = Y_BYTES;
constexpr int OFF_DSLOT = 4 * STAGE_BYTES;
constexpr int DSLOT_BYTES = 16384;
constexpr int OFF_BAR = OFF_RING + NRING * STAGE_BYTES;
constexpr int OFF_B1 = OFF_BAR + 1024;
constexpr int OFF_B2 = OFF_B1 + 2048;
constexpr int SMEM_TOTAL = OFF_B2 + 256;
constexpr int NTHREADS = 384;

__device__ uint4 g_part[(size_t)NMB * NSPLIT * 3 * 1024];
__device__ unsigned int g_epoch[NMB * NSPLIT];

#define TS(role, idx) do {} while (0)
#define TSC(idx) do {} while (0)

__device__ __forceinline__ uint32_t smem_u32(const void* p) { return (uint32_t)__cvta_generic_to_shared(p); }
__device__ __forceinline__ uint32_t mapa(uint32_t a, uint32_t r) {
  uint32_t d; asm volatile("mapa.shared::cluster.u32 %0, %1, %2;" : "=r"(d) : "r"(a), "r"(r)); return d;
}
__device__ __forceinline__ void mbar_init(uint32_t bar, uint32_t cnt) {
  asm volatile("mbarrier.init.shared::cta.b64 [%0], %1;" :: "r"(bar), "r"(cnt) : "memory");
}
__device__ __forceinline__ void mbar_expect_tx(uint32_t bar, uint32_t bytes) {
  asm volatile("mbarrier.arrive.expect_tx.shared::cta.b64 _, [%0], %1;" :: "r"(bar), "r"(bytes) : "memory");
}
__device__ __forceinline__ void mbar_arrive(uint32_t bar) {
  asm volatile("mbarrier.arrive.shared::cta.b64 _, [%0];" :: "r"(bar) : "memory");
}
__device__ __forceinline__ void mbar_arrive_remote(uint32_t rbar) {
  asm volatile("mbarrier.arrive.release.cluster.shared::cluster.b64 _, [%0];" :: "r"(rbar) : "memory");
}
__device__ __forceinline__ void mbar_wait(uint32_t bar, uint32_t parity) {
  uint32_t done = 0; uint32_t it = 0;
  while (true) {
    asm volatile("{\n.reg .pred p;\nmbarrier.try_wait.parity.shared::cta.b64 p, [%1], %2;\nselp.u32 %0, 1, 0, p;\n}"
                 : "=r"(done) : "r"(bar), "r"(parity) : "memory");
    if (done) break;
    if (++it > (1u << 22)) asm volatile("trap;");
  }
}
__device__ __forceinline__ void mbar_wait_cluster(uint32_t bar, uint32_t parity) {
  uint32_t done = 0; uint32_t it = 0;
  while (true) {
    asm volatile("{\n.reg .pred p;\nmbarrier.try_wait.parity.acquire.cluster.shared::cta.b64 p, [%1], %2;\nselp.u32 %0, 1, 0, p;\n}"
                 : "=r"(done) : "r"(bar), "r"(parity) : "memory");
    if (done) break;
    if (++it > (1u << 22)) asm volatile("trap;");
  }
}
__device__ __forceinline__ void tma_load_3d(uint32_t dst, const CUtensorMap* tm, int c0, int c1, int c2, uint32_t bar) {
  asm volatile("cp.async.bulk.tensor.3d.shared::cluster.global.mbarrier::complete_tx::bytes [%0], [%1, {%3, %4, %5}], [%2];"
               :: "r"(dst), "l"(tm), "r"(bar), "r"(c0), "r"(c1), "r"(c2) : "memory");
}
__device__ __forceinline__ void tma_load_2d(uint32_t dst, const CUtensorMap* tm, int c0, int c1, uint32_t bar) {
  asm volatile("cp.async.bulk.tensor.2d.shared::cluster.global.mbarrier::complete_tx::bytes [%0], [%1, {%3, %4}], [%2];"
               :: "r"(dst), "l"(tm), "r"(bar), "r"(c0), "r"(c1) : "memory");
}
__device__ __forceinline__ void tma_prefetch_3d(const CUtensorMap* tm, int c0, int c1, int c2) {
  asm volatile("cp.async.bulk.prefetch.tensor.3d.L2.global.tile [%0, {%1, %2, %3}];" :: "l"(tm), "r"(c0), "r"(c1), "r"(c2) : "memory");
}
__device__ __forceinline__ void tma_prefetch_2d(const CUtensorMap* tm, int c0, int c1) {
  asm volatile("cp.async.bulk.prefetch.tensor.2d.L2.global.tile [%0, {%1, %2}];" :: "l"(tm), "r"(c0), "r"(c1) : "memory");
}
__device__ __forceinline__ void wg_fence() { asm volatile("wgmma.fence.sync.aligned;" ::: "memory"); }
__device__ __forceinline__ void wg_commit() { asm volatile("wgmma.commit_group.sync.aligned;" ::: "memory"); }
template <int N> __device__ __forceinline__ void wg_wait() { asm volatile("wgmma.wait_group.sync.aligned %0;" :: "n"(N) : "memory"); }
template <int N> __device__ __forceinline__ void reg_fence(float (&d)[N]) {
#pragma unroll
  for (int i = 0; i < N; i++) asm volatile("" : "+f"(d[i]) :: "memory");
}
__device__ __forceinline__ uint64_t make_desc(uint32_t addr, uint32_t lbo, uint32_t sbo, uint32_t lt) {
  return (uint64_t)((addr & 0x3FFFF) >> 4) | ((uint64_t)(lbo >> 4) << 16) | ((uint64_t)(sbo >> 4) << 32) | ((uint64_t)lt << 62);
}
__device__ __forceinline__ uint32_t pack_bf16(float lo, float hi) {
  uint32_t r; asm("cvt.rn.bf16x2.f32 %0, %1, %2;" : "=r"(r) : "f"(hi), "f"(lo)); return r;
}
__device__ __forceinline__ float bf_lo(uint32_t v) { return __uint_as_float(v << 16); }
__device__ __forceinline__ float bf_hi(uint32_t v) { return __uint_as_float(v & 0xffff0000u); }
__device__ __forceinline__ float bf16r(float v) { return __bfloat162float(__float2bfloat16_rn(v)); }
__device__ __forceinline__ uint32_t hadd2_bf(uint32_t a, uint32_t b) {
  uint32_t r; asm("add.rn.bf16x2 %0, %1, %2;" : "=r"(r) : "r"(a), "r"(b)); return r;
}
__device__ __forceinline__ uint32_t hsub2_bf(uint32_t a, uint32_t b) {
  uint32_t r; asm("sub.rn.bf16x2 %0, %1, %2;" : "=r"(r) : "r"(a), "r"(b)); return r;
}
__device__ __forceinline__ float gelu_half(float hu) {
  const float inner = hu * fmaf(8.0f * 0.035677408136300125f, hu * hu, 2.0f * 0.7978845608028654f);
  float th; asm("tanh.approx.f32 %0, %1;" : "=f"(th) : "f"(inner));
  return fmaf(hu, th, hu);
}
__device__ __forceinline__ void mma16816(float (&c)[4], uint32_t a0, uint32_t a1, uint32_t a2, uint32_t a3, uint32_t b0, uint32_t b1) {
  asm volatile("mma.sync.aligned.m16n8k16.row.col.f32.bf16.bf16.f32 {%0,%1,%2,%3}, {%4,%5,%6,%7}, {%8,%9}, {%0,%1,%2,%3};"
               : "+f"(c[0]), "+f"(c[1]), "+f"(c[2]), "+f"(c[3]) : "r"(a0), "r"(a1), "r"(a2), "r"(a3), "r"(b0), "r"(b1));
}

__device__ __forceinline__ void wgmma_ss_n224(float (&d)[112], uint64_t descA, uint64_t descB, int scaleD) {
  asm volatile("{\n.reg .pred p;\nsetp.ne.b32 p, %114, 0;\n"
    "wgmma.mma_async.sync.aligned.m64n224k16.f32.bf16.bf16 {%0, %1, %2, %3, %4, %5, %6, %7, %8, %9, %10, %11, %12, %13, %14, %15, %16, %17, %18, %19, %20, %21, %22, %23, %24, %25, %26, %27, %28, %29, %30, %31, %32, %33, %34, %35, %36, %37, %38, %39, %40, %41, %42, %43, %44, %45, %46, %47, %48, %49, %50, %51, %52, %53, %54, %55, %56, %57, %58, %59, %60, %61, %62, %63, %64, %65, %66, %67, %68, %69, %70, %71, %72, %73, %74, %75, %76, %77, %78, %79, %80, %81, %82, %83, %84, %85, %86, %87, %88, %89, %90, %91, %92, %93, %94, %95, %96, %97, %98, %99, %100, %101, %102, %103, %104, %105, %106, %107, %108, %109, %110, %111}, %112, %113, p, 1, 1, 0, 1;\n}\n"
    : "+f"(d[0]), "+f"(d[1]), "+f"(d[2]), "+f"(d[3]), "+f"(d[4]), "+f"(d[5]), "+f"(d[6]), "+f"(d[7]), "+f"(d[8]), "+f"(d[9]), "+f"(d[10]), "+f"(d[11]), "+f"(d[12]), "+f"(d[13]), "+f"(d[14]), "+f"(d[15]), "+f"(d[16]), "+f"(d[17]), "+f"(d[18]), "+f"(d[19]), "+f"(d[20]), "+f"(d[21]), "+f"(d[22]), "+f"(d[23]), "+f"(d[24]), "+f"(d[25]), "+f"(d[26]), "+f"(d[27]), "+f"(d[28]), "+f"(d[29]), "+f"(d[30]), "+f"(d[31]), "+f"(d[32]), "+f"(d[33]), "+f"(d[34]), "+f"(d[35]), "+f"(d[36]), "+f"(d[37]), "+f"(d[38]), "+f"(d[39]), "+f"(d[40]), "+f"(d[41]), "+f"(d[42]), "+f"(d[43]), "+f"(d[44]), "+f"(d[45]), "+f"(d[46]), "+f"(d[47]), "+f"(d[48]), "+f"(d[49]), "+f"(d[50]), "+f"(d[51]), "+f"(d[52]), "+f"(d[53]), "+f"(d[54]), "+f"(d[55]), "+f"(d[56]), "+f"(d[57]), "+f"(d[58]), "+f"(d[59]), "+f"(d[60]), "+f"(d[61]), "+f"(d[62]), "+f"(d[63]), "+f"(d[64]), "+f"(d[65]), "+f"(d[66]), "+f"(d[67]), "+f"(d[68]), "+f"(d[69]), "+f"(d[70]), "+f"(d[71]), "+f"(d[72]), "+f"(d[73]), "+f"(d[74]), "+f"(d[75]), "+f"(d[76]), "+f"(d[77]), "+f"(d[78]), "+f"(d[79]), "+f"(d[80]), "+f"(d[81]), "+f"(d[82]), "+f"(d[83]), "+f"(d[84]), "+f"(d[85]), "+f"(d[86]), "+f"(d[87]), "+f"(d[88]), "+f"(d[89]), "+f"(d[90]), "+f"(d[91]), "+f"(d[92]), "+f"(d[93]), "+f"(d[94]), "+f"(d[95]), "+f"(d[96]), "+f"(d[97]), "+f"(d[98]), "+f"(d[99]), "+f"(d[100]), "+f"(d[101]), "+f"(d[102]), "+f"(d[103]), "+f"(d[104]), "+f"(d[105]), "+f"(d[106]), "+f"(d[107]), "+f"(d[108]), "+f"(d[109]), "+f"(d[110]), "+f"(d[111])
    : "l"(descA), "l"(descB), "r"(scaleD));
}

__device__ __forceinline__ void wgmma_rs_n64(float (&d)[32], const uint32_t (&a)[4], uint64_t descB, int scaleD) {
  asm volatile("{\n.reg .pred p;\nsetp.ne.b32 p, %37, 0;\n"
    "wgmma.mma_async.sync.aligned.m64n64k16.f32.bf16.bf16 {%0, %1, %2, %3, %4, %5, %6, %7, %8, %9, %10, %11, %12, %13, %14, %15, %16, %17, %18, %19, %20, %21, %22, %23, %24, %25, %26, %27, %28, %29, %30, %31}, {%32, %33, %34, %35}, %36, p, 1, 1, 1;\n}\n"
    : "+f"(d[0]), "+f"(d[1]), "+f"(d[2]), "+f"(d[3]), "+f"(d[4]), "+f"(d[5]), "+f"(d[6]), "+f"(d[7]), "+f"(d[8]), "+f"(d[9]), "+f"(d[10]), "+f"(d[11]), "+f"(d[12]), "+f"(d[13]), "+f"(d[14]), "+f"(d[15]), "+f"(d[16]), "+f"(d[17]), "+f"(d[18]), "+f"(d[19]), "+f"(d[20]), "+f"(d[21]), "+f"(d[22]), "+f"(d[23]), "+f"(d[24]), "+f"(d[25]), "+f"(d[26]), "+f"(d[27]), "+f"(d[28]), "+f"(d[29]), "+f"(d[30]), "+f"(d[31])
    : "r"(a[0]), "r"(a[1]), "r"(a[2]), "r"(a[3]), "l"(descB), "r"(scaleD));
}

__device__ __forceinline__ void wgmma_rs_n224(float (&d)[112], const uint32_t (&a)[4], uint64_t descB, int scaleD) {
  asm volatile("{\n.reg .pred p;\nsetp.ne.b32 p, %117, 0;\n"
    "wgmma.mma_async.sync.aligned.m64n224k16.f32.bf16.bf16 {%0, %1, %2, %3, %4, %5, %6, %7, %8, %9, %10, %11, %12, %13, %14, %15, %16, %17, %18, %19, %20, %21, %22, %23, %24, %25, %26, %27, %28, %29, %30, %31, %32, %33, %34, %35, %36, %37, %38, %39, %40, %41, %42, %43, %44, %45, %46, %47, %48, %49, %50, %51, %52, %53, %54, %55, %56, %57, %58, %59, %60, %61, %62, %63, %64, %65, %66, %67, %68, %69, %70, %71, %72, %73, %74, %75, %76, %77, %78, %79, %80, %81, %82, %83, %84, %85, %86, %87, %88, %89, %90, %91, %92, %93, %94, %95, %96, %97, %98, %99, %100, %101, %102, %103, %104, %105, %106, %107, %108, %109, %110, %111}, {%112, %113, %114, %115}, %116, p, 1, 1, 1;\n}\n"
    : "+f"(d[0]), "+f"(d[1]), "+f"(d[2]), "+f"(d[3]), "+f"(d[4]), "+f"(d[5]), "+f"(d[6]), "+f"(d[7]), "+f"(d[8]), "+f"(d[9]), "+f"(d[10]), "+f"(d[11]), "+f"(d[12]), "+f"(d[13]), "+f"(d[14]), "+f"(d[15]), "+f"(d[16]), "+f"(d[17]), "+f"(d[18]), "+f"(d[19]), "+f"(d[20]), "+f"(d[21]), "+f"(d[22]), "+f"(d[23]), "+f"(d[24]), "+f"(d[25]), "+f"(d[26]), "+f"(d[27]), "+f"(d[28]), "+f"(d[29]), "+f"(d[30]), "+f"(d[31]), "+f"(d[32]), "+f"(d[33]), "+f"(d[34]), "+f"(d[35]), "+f"(d[36]), "+f"(d[37]), "+f"(d[38]), "+f"(d[39]), "+f"(d[40]), "+f"(d[41]), "+f"(d[42]), "+f"(d[43]), "+f"(d[44]), "+f"(d[45]), "+f"(d[46]), "+f"(d[47]), "+f"(d[48]), "+f"(d[49]), "+f"(d[50]), "+f"(d[51]), "+f"(d[52]), "+f"(d[53]), "+f"(d[54]), "+f"(d[55]), "+f"(d[56]), "+f"(d[57]), "+f"(d[58]), "+f"(d[59]), "+f"(d[60]), "+f"(d[61]), "+f"(d[62]), "+f"(d[63]), "+f"(d[64]), "+f"(d[65]), "+f"(d[66]), "+f"(d[67]), "+f"(d[68]), "+f"(d[69]), "+f"(d[70]), "+f"(d[71]), "+f"(d[72]), "+f"(d[73]), "+f"(d[74]), "+f"(d[75]), "+f"(d[76]), "+f"(d[77]), "+f"(d[78]), "+f"(d[79]), "+f"(d[80]), "+f"(d[81]), "+f"(d[82]), "+f"(d[83]), "+f"(d[84]), "+f"(d[85]), "+f"(d[86]), "+f"(d[87]), "+f"(d[88]), "+f"(d[89]), "+f"(d[90]), "+f"(d[91]), "+f"(d[92]), "+f"(d[93]), "+f"(d[94]), "+f"(d[95]), "+f"(d[96]), "+f"(d[97]), "+f"(d[98]), "+f"(d[99]), "+f"(d[100]), "+f"(d[101]), "+f"(d[102]), "+f"(d[103]), "+f"(d[104]), "+f"(d[105]), "+f"(d[106]), "+f"(d[107]), "+f"(d[108]), "+f"(d[109]), "+f"(d[110]), "+f"(d[111])
    : "r"(a[0]), "r"(a[1]), "r"(a[2]), "r"(a[3]), "l"(descB), "r"(scaleD));
}

__device__ __forceinline__ void wgmma_ss_n128(float (&d)[64], uint64_t descA, uint64_t descB, int scaleD) {
  asm volatile("{\n.reg .pred p;\nsetp.ne.b32 p, %66, 0;\n"
    "wgmma.mma_async.sync.aligned.m64n128k16.f32.bf16.bf16 {%0, %1, %2, %3, %4, %5, %6, %7, %8, %9, %10, %11, %12, %13, %14, %15, %16, %17, %18, %19, %20, %21, %22, %23, %24, %25, %26, %27, %28, %29, %30, %31, %32, %33, %34, %35, %36, %37, %38, %39, %40, %41, %42, %43, %44, %45, %46, %47, %48, %49, %50, %51, %52, %53, %54, %55, %56, %57, %58, %59, %60, %61, %62, %63}, %64, %65, p, 1, 1, 0, 1;\n}\n"
    : "+f"(d[0]), "+f"(d[1]), "+f"(d[2]), "+f"(d[3]), "+f"(d[4]), "+f"(d[5]), "+f"(d[6]), "+f"(d[7]), "+f"(d[8]), "+f"(d[9]), "+f"(d[10]), "+f"(d[11]), "+f"(d[12]), "+f"(d[13]), "+f"(d[14]), "+f"(d[15]), "+f"(d[16]), "+f"(d[17]), "+f"(d[18]), "+f"(d[19]), "+f"(d[20]), "+f"(d[21]), "+f"(d[22]), "+f"(d[23]), "+f"(d[24]), "+f"(d[25]), "+f"(d[26]), "+f"(d[27]), "+f"(d[28]), "+f"(d[29]), "+f"(d[30]), "+f"(d[31]), "+f"(d[32]), "+f"(d[33]), "+f"(d[34]), "+f"(d[35]), "+f"(d[36]), "+f"(d[37]), "+f"(d[38]), "+f"(d[39]), "+f"(d[40]), "+f"(d[41]), "+f"(d[42]), "+f"(d[43]), "+f"(d[44]), "+f"(d[45]), "+f"(d[46]), "+f"(d[47]), "+f"(d[48]), "+f"(d[49]), "+f"(d[50]), "+f"(d[51]), "+f"(d[52]), "+f"(d[53]), "+f"(d[54]), "+f"(d[55]), "+f"(d[56]), "+f"(d[57]), "+f"(d[58]), "+f"(d[59]), "+f"(d[60]), "+f"(d[61]), "+f"(d[62]), "+f"(d[63])
    : "l"(descA), "l"(descB), "r"(scaleD));
}

__device__ __forceinline__ void wgmma_ss_n96(float (&d)[48], uint64_t descA, uint64_t descB, int scaleD) {
  asm volatile("{\n.reg .pred p;\nsetp.ne.b32 p, %50, 0;\n"
    "wgmma.mma_async.sync.aligned.m64n96k16.f32.bf16.bf16 {%0, %1, %2, %3, %4, %5, %6, %7, %8, %9, %10, %11, %12, %13, %14, %15, %16, %17, %18, %19, %20, %21, %22, %23, %24, %25, %26, %27, %28, %29, %30, %31, %32, %33, %34, %35, %36, %37, %38, %39, %40, %41, %42, %43, %44, %45, %46, %47}, %48, %49, p, 1, 1, 0, 1;\n}\n"
    : "+f"(d[0]), "+f"(d[1]), "+f"(d[2]), "+f"(d[3]), "+f"(d[4]), "+f"(d[5]), "+f"(d[6]), "+f"(d[7]), "+f"(d[8]), "+f"(d[9]), "+f"(d[10]), "+f"(d[11]), "+f"(d[12]), "+f"(d[13]), "+f"(d[14]), "+f"(d[15]), "+f"(d[16]), "+f"(d[17]), "+f"(d[18]), "+f"(d[19]), "+f"(d[20]), "+f"(d[21]), "+f"(d[22]), "+f"(d[23]), "+f"(d[24]), "+f"(d[25]), "+f"(d[26]), "+f"(d[27]), "+f"(d[28]), "+f"(d[29]), "+f"(d[30]), "+f"(d[31]), "+f"(d[32]), "+f"(d[33]), "+f"(d[34]), "+f"(d[35]), "+f"(d[36]), "+f"(d[37]), "+f"(d[38]), "+f"(d[39]), "+f"(d[40]), "+f"(d[41]), "+f"(d[42]), "+f"(d[43]), "+f"(d[44]), "+f"(d[45]), "+f"(d[46]), "+f"(d[47])
    : "l"(descA), "l"(descB), "r"(scaleD));
}

__host__ __device__ constexpr int step_kind(int i) { return (i == 0 || i == 1 || i == 3 || i == 6) ? 0 : (i == 7 ? 2 : 1); }
__host__ __device__ constexpr int step_k(int i) { return i == 0 ? 0 : i == 1 ? 1 : i == 2 ? 0 : i == 3 ? 2 : i == 4 ? 1 : i == 5 ? 2 : 3; }
__device__ __forceinline__ int step_slice(int i, int j) {
  const int kind = step_kind(i), k = step_k(i);
  const int base = (kind == 0) ? (j ^ 1) : j;
  return (k == 3) ? base : ((base + 2 * (k + 1)) & 7);
}

__host__ __device__ constexpr int load_off(int i) {
  return i < 22 ? OFF_RING + (i % NRING) * STAGE_BYTES : (i < 26 ? (i - 22) * STAGE_BYTES : OFF_RING + ((i - 10) % NRING) * STAGE_BYTES);
}
__host__ __device__ constexpr int load_dep(int i) { return i < NRING ? -1 : (i < 22 ? i - NRING : (i < 26 ? 15 : i - 10)); }

__global__ void __cluster_dims__(2, 1, 1) __launch_bounds__(NTHREADS, 1)
fused_mlp_kernel(const __grid_constant__ CUtensorMap tm_x, const __grid_constant__ CUtensorMap tm_w1, const __grid_constant__ CUtensorMap tm_w2,
                 const __nv_bfloat16* __restrict__ b1, const __nv_bfloat16* __restrict__ b2, __nv_bfloat16* __restrict__ out)
{
  extern __shared__ __align__(1024) unsigned char smem[];
  const uint32_t sbase = smem_u32(smem);
  const uint32_t bar_full = sbase + OFF_BAR;
  const uint32_t bar_cons = sbase + OFF_BAR + 256;
  const uint32_t bar_x = sbase + OFF_BAR + 576;
  const uint32_t bar_dfull = sbase + OFF_BAR + 528;
  const uint32_t bar_peer = sbase + OFF_BAR + 560;
  const int tid = threadIdx.x, warp = tid >> 5, lane = tid & 31;
  const int mb = blockIdx.x >> 3, j = blockIdx.x & 7;

  TSC(0);
  if (warp == 8 && lane == 0) {
    for (int i = 0; i < NLOAD; i++) { mbar_init(bar_full + 8 * i, 1); mbar_init(bar_cons + 8 * i, 2); }
    for (int i = 0; i < 4; i++) mbar_init(bar_x + 8 * i, 1);
    for (int i = 0; i < 4; i++) mbar_init(bar_dfull + 8 * i, 1);
    mbar_init(bar_peer, 2);
    asm volatile("fence.mbarrier_init.release.cluster;" ::: "memory");
    asm volatile("fence.proxy.async.shared::cta;" ::: "memory");
    for (int kq = 0; kq < 1; kq++) {
      mbar_expect_tx(bar_x + 8 * kq, 32768);
      tma_load_3d(sbase + kq * 16384, &tm_x, 0, mb * BM, 2 * kq, bar_x + 8 * kq);
      tma_load_3d(sbase + 65536 + kq * 16384, &tm_x, 0, mb * BM + 64, 2 * kq, bar_x + 8 * kq);
    }
    for (int i = 0; i < 4; i++) mbar_expect_tx(bar_dfull + 8 * i, DSLOT_BYTES);
    TS(2, 1);
  }
  asm volatile("barrier.cluster.arrive.relaxed.aligned;\nbarrier.cluster.wait.aligned;" ::: "memory");

  if (warp >= 8) {
    asm volatile("setmaxnreg.dec.sync.aligned.u32 40;");
    if (warp == 8 && lane == 0) {
      for (int kq = 1; kq < 4; kq++) {
        mbar_expect_tx(bar_x + 8 * kq, 32768);
        tma_load_3d(sbase + kq * 16384, &tm_x, 0, mb * BM, 2 * kq, bar_x + 8 * kq);
        tma_load_3d(sbase + 65536 + kq * 16384, &tm_x, 0, mb * BM + 64, 2 * kq, bar_x + 8 * kq);
      }
      for (int i = 0; i < NRING; i++) {
        mbar_expect_tx(bar_full + 8 * i, STAGE_BYTES);
        tma_load_3d(sbase + OFF_RING + i * STAGE_BYTES, &tm_w1, 0, i * 32, j * 7, bar_full + 8 * i);
      }
    for (int t = 2 * mb; t < 2 * mb + 2; t++) {
      if (t < 16) { if (t >= NRING) tma_prefetch_3d(&tm_w1, 0, t * 32, j * 7); }
      else tma_prefetch_2d(&tm_w2, ((t - 16) >> 1) * 64, j * BF + ((t - 16) & 1) * 112);
    }
#pragma unroll
      for (int i = NRING; i < NLOAD; i++) {
        if (i < 23 || i >= 26) mbar_wait(bar_cons + 8 * load_dep(i), 0);
        mbar_expect_tx(bar_full + 8 * i, STAGE_BYTES);
        if (i < 16) tma_load_3d(sbase + load_off(i), &tm_w1, 0, i * 32, j * 7, bar_full + 8 * i);
        else tma_load_2d(sbase + load_off(i), &tm_w2, step_slice((i - 16) >> 1, j) * BN2, j * BF + ((i - 16) & 1) * 112, bar_full + 8 * i);
      }
    }
  } else {
    TSC(22);
    asm volatile("setmaxnreg.inc.sync.aligned.u32 232;");
    TSC(23);
    const int wg = warp >> 2, w4 = warp & 3, t128 = tid & 127;
    const int q = lane & 3, g = lane >> 2;
    float2* b1s = reinterpret_cast<float2*>(smem + OFF_B1 + wg * 1024);
    uint32_t* b2s = reinterpret_cast<uint32_t*>(smem + OFF_B2 + wg * 128);
    uint32_t bias_a = 0, bias_b = 0;
    if (t128 < BF / 2) bias_a = reinterpret_cast<const uint32_t*>(b1 + j * BF)[t128];
    if (t128 < BN2 / 2) bias_b = reinterpret_cast<const uint32_t*>(b2 + j * BN2)[t128];
    const uint32_t epoch = g_epoch[blockIdx.x];

    float r0, r1;
    {
      uint32_t xa[32][4];
      float cs[2][4], c0[2][4], c1[2][4];
#pragma unroll
      for (int u = 0; u < 2; u++)
#pragma unroll
        for (int e = 0; e < 4; e++) { cs[u][e] = 0.f; c0[u][e] = 0.f; c1[u][e] = 0.f; }
      const int lrow = w4 * 16 + (lane & 7) + ((lane >> 3) & 1) * 8;
      const uint32_t lbase = sbase + wg * 65536 + lrow * 128;
      const uint32_t ones = 0x3F803F80u;
#pragma unroll
      for (int ks = 0; ks < 32; ks++) {
        if ((ks & 7) == 0) mbar_wait(bar_x + 8 * (ks >> 3), 0);
        uint32_t (&a)[4] = xa[ks];
        const uint32_t addr = lbase + (ks >> 2) * 8192 + (((2 * (ks & 3) + (lane >> 4)) ^ (lane & 7)) << 4);
        asm volatile("ldmatrix.sync.aligned.m8n8.x4.shared.b16 {%0,%1,%2,%3}, [%4];" : "=r"(a[0]), "=r"(a[1]), "=r"(a[2]), "=r"(a[3]) : "r"(addr));
        mma16816(cs[ks & 1], a[0], a[1], a[2], a[3], ones, ones);
        mma16816(c0[ks & 1], a[0], a[1], a[2], a[3], a[0], a[2]);
        mma16816(c1[ks & 1], a[0], a[1], a[2], a[3], a[1], a[3]);
      }
      const float m0 = (cs[0][0] + cs[1][0]) * (1.0f / D_MOD), m1 = (cs[0][2] + cs[1][2]) * (1.0f / D_MOD);
      const uint32_t mm0 = pack_bf16(m0, m0), mm1 = pack_bf16(m1, m1);
#pragma unroll
      for (int ks = 0; ks < 32; ks++) {
        const uint32_t addr = lbase + (ks >> 2) * 8192 + (((2 * (ks & 3) + (lane >> 4)) ^ (lane & 7)) << 4);
        asm volatile("stmatrix.sync.aligned.m8n8.x4.shared.b16 [%0], {%1,%2,%3,%4};" :: "r"(addr),
                     "r"(hsub2_bf(xa[ks][0], mm0)), "r"(hsub2_bf(xa[ks][1], mm1)),
                     "r"(hsub2_bf(xa[ks][2], mm0)), "r"(hsub2_bf(xa[ks][3], mm1)) : "memory");
      }
      const int dsrc = g * 4 + (g >> 1);
      const float q0 = __shfl_sync(0xffffffffu, (g & 1) ? c0[0][1] + c0[1][1] : c0[0][0] + c0[1][0], dsrc);
      const float q1 = __shfl_sync(0xffffffffu, (g & 1) ? c1[0][3] + c1[1][3] : c1[0][2] + c1[1][2], dsrc);
      const float v0 = fmaxf(fmaf(-m0, m0, q0 * (1.0f / D_MOD)), 0.f), v1 = fmaxf(fmaf(-m1, m1, q1 * (1.0f / D_MOD)), 0.f);
      r0 = 1.0f / bf16r(sqrtf(bf16r(bf16r(v0) + 1e-5f)));
      r1 = 1.0f / bf16r(sqrtf(bf16r(bf16r(v1) + 1e-5f)));
    }
    if (t128 < BF / 2) b1s[t128] = make_float2(0.5f * bf_lo(bias_a), 0.5f * bf_hi(bias_a));
    if (t128 < BN2 / 2) b2s[t128] = bias_b;
    TSC(1);
    asm volatile("fence.proxy.async.shared::cta;" ::: "memory");
    if (wg == 0) asm volatile("bar.sync 1, 128;" ::: "memory"); else asm volatile("bar.sync 2, 128;" ::: "memory");
    TSC(2);

    uint32_t h[14][4];
    {
      float acc[112];
#pragma unroll
      for (int kb = 0; kb < 16; kb++) {
        mbar_wait(bar_full + 8 * kb, 0);
        if ((kb & 1) == 0) TSC(3 + (kb >> 1));
        wg_fence();
        const uint32_t abase = sbase + wg * 65536 + (kb >> 1) * 8192 + (kb & 1) * 64;
        const uint32_t bbase = sbase + load_off(kb);
#pragma unroll
        for (int kk = 0; kk < 2; kk++) {
          wgmma_ss_n224(acc, make_desc(abase + kk * 32, 16, 1024, 1), make_desc(bbase + kk * 1024, 2048, 512, 2), (kb | kk) != 0);
        }
        wg_commit();
        if (kb > 0) { wg_wait<1>(); if (t128 == 0) mbar_arrive(bar_cons + 8 * (kb - 1)); }
      }
      wg_wait<0>();
      reg_fence(acc);
      if (t128 == 0) { mbar_arrive(bar_cons + 8 * 15); mbar_arrive_remote(mapa(bar_peer, (j & 1) ^ 1)); }
      TSC(11);

      const float hr0 = 0.5f * r0, hr1 = 0.5f * r1;
#pragma unroll
      for (int i = 0; i < 28; i++) {
        const float2 bb = b1s[i * 4 + q];
        h[i >> 1][(i & 1) * 2 + 0] = pack_bf16(gelu_half(fmaf(acc[4 * i], hr0, bb.x)), gelu_half(fmaf(acc[4 * i + 1], hr0, bb.y)));
        h[i >> 1][(i & 1) * 2 + 1] = pack_bf16(gelu_half(fmaf(acc[4 * i + 2], hr1, bb.x)), gelu_half(fmaf(acc[4 * i + 3], hr1, bb.y)));
      }
    }

    const uint32_t par = (epoch + 1) & 1;
    float acc2[2][32];
    float sum[32];
#pragma unroll
    for (int i = 0; i < 32; i++) sum[i] = 0.f;
    uint4 pf[4];
    const uint32_t peer_slot = mapa(sbase + OFF_DSLOT + (wg * 512 + t128) * 16, (j & 1) ^ 1);
    const uint32_t peer_dfull = mapa(bar_dfull, (j & 1) ^ 1);
    const uint4* my_slot = reinterpret_cast<const uint4*>(smem + OFF_DSLOT) + wg * 512 + t128;
    const uint4* in_part = &g_part[(size_t)((mb * NSPLIT + j) * 3) * 1024 + wg * 512 + t128];
    auto ld_part = [&](const uint4* p) {
      uint4 v;
      asm volatile("ld.relaxed.gpu.global.v4.u32 {%0, %1, %2, %3}, [%4];" : "=r"(v.x), "=r"(v.y), "=r"(v.z), "=r"(v.w) : "l"(p) : "memory");
      return v;
    };
    auto prefetch = [&](int k) {
#pragma unroll
      for (int c = 0; c < 4; c++) pf[c] = ld_part(in_part + k * 1024 + c * 128);
    };
    auto consume = [&](int k) {
#pragma unroll
      for (int c = 0; c < 4; c++) {
        uint4 v = pf[c];
        uint32_t it = 0;
        while ((((v.x ^ par) | (v.y ^ par) | (v.z ^ par) | (v.w ^ par)) & 1u) != 0) {
          v = ld_part(in_part + k * 1024 + c * 128);
          if (++it > (1u << 20)) asm volatile("trap;");
        }
        sum[c * 8 + 0] += bf_lo(v.x & ~1u); sum[c * 8 + 1] += bf_hi(v.x);
        sum[c * 8 + 2] += bf_lo(v.y & ~1u); sum[c * 8 + 3] += bf_hi(v.y);
        sum[c * 8 + 4] += bf_lo(v.z & ~1u); sum[c * 8 + 5] += bf_hi(v.z);
        sum[c * 8 + 6] += bf_lo(v.w & ~1u); sum[c * 8 + 7] += bf_hi(v.w);
      }
    };
    auto post = [&](int st, float (&a)[32]) {
      const int kind = step_kind(st), k = step_k(st);
      if (kind == 0) {
        if (st == 0) mbar_wait_cluster(bar_peer, 0);
#pragma unroll
        for (int c = 0; c < 4; c++) {
          asm volatile("st.async.weak.shared::cluster.mbarrier::complete_tx::bytes.v4.b32 [%0], {%1,%2,%3,%4}, [%5];"
            :: "r"(peer_slot + k * DSLOT_BYTES + c * 2048),
               "r"(pack_bf16(a[c * 8 + 0], a[c * 8 + 1])), "r"(pack_bf16(a[c * 8 + 2], a[c * 8 + 3])),
               "r"(pack_bf16(a[c * 8 + 4], a[c * 8 + 5])), "r"(pack_bf16(a[c * 8 + 6], a[c * 8 + 7])),
               "r"(peer_dfull + 8 * k) : "memory");
        }
      } else {
        mbar_wait_cluster(bar_dfull + 8 * k, 0);
        const int dest = (j + 2 * (k + 1)) & 7;
        uint4* p = &g_part[(size_t)((mb * NSPLIT + dest) * 3 + k) * 1024 + wg * 512 + t128];
#pragma unroll
        for (int c = 0; c < 4; c++) {
          const uint4 d = my_slot[k * 1024 + c * 128];
          uint4 v;
          v.x = (pack_bf16(a[c * 8 + 0] + bf_lo(d.x), a[c * 8 + 1] + bf_hi(d.x)) & ~1u) | par;
          v.y = (pack_bf16(a[c * 8 + 2] + bf_lo(d.y), a[c * 8 + 3] + bf_hi(d.y)) & ~1u) | par;
          v.z = (pack_bf16(a[c * 8 + 4] + bf_lo(d.z), a[c * 8 + 5] + bf_hi(d.z)) & ~1u) | par;
          v.w = (pack_bf16(a[c * 8 + 6] + bf_lo(d.w), a[c * 8 + 7] + bf_hi(d.w)) & ~1u) | par;
          __stcg(p + c * 128, v);
        }
      }
    };
#pragma unroll
    for (int i = 0; i < 8; i++) {
      TSC(12 + i);
      if (i == 0 && wg == 1) asm volatile("bar.sync 4, 256;" ::: "memory");
      mbar_wait(bar_full + 8 * (16 + 2 * i), 0);
      wg_fence();
#pragma unroll
      for (int ks = 0; ks < 7; ks++) {
        wgmma_rs_n64(acc2[i & 1], h[ks], make_desc(sbase + load_off(16 + 2 * i) + ks * 2048, 16, 1024, 1), ks != 0);
      }
      mbar_wait(bar_full + 8 * (17 + 2 * i), 0);
      wg_fence();
#pragma unroll
      for (int ks = 0; ks < 7; ks++) {
        wgmma_rs_n64(acc2[i & 1], h[7 + ks], make_desc(sbase + load_off(17 + 2 * i) + ks * 2048, 16, 1024, 1), 1);
      }
      wg_commit();
      if (i == 0 && wg == 0) asm volatile("bar.arrive 4, 256;" ::: "memory");
      if (i > 0) {
        wg_wait<1>();
        reg_fence(acc2[(i - 1) & 1]);
        if (i <= 3 && t128 == 0) { mbar_arrive(bar_cons + 8 * (16 + 2 * (i - 1))); mbar_arrive(bar_cons + 8 * (17 + 2 * (i - 1))); }
        post(i - 1, acc2[(i - 1) & 1]);
      }
      if (i == 6) prefetch(0);
      if (i == 7) { consume(0); prefetch(1); }
    }
    consume(1);
    prefetch(2);
    mbar_wait_cluster(bar_dfull + 8 * 3, 0);
#pragma unroll
    for (int c = 0; c < 4; c++) {
      const uint4 d = my_slot[3 * 1024 + c * 128];
      sum[c * 8 + 0] += bf_lo(d.x); sum[c * 8 + 1] += bf_hi(d.x); sum[c * 8 + 2] += bf_lo(d.y); sum[c * 8 + 3] += bf_hi(d.y);
      sum[c * 8 + 4] += bf_lo(d.z); sum[c * 8 + 5] += bf_hi(d.z); sum[c * 8 + 6] += bf_lo(d.w); sum[c * 8 + 7] += bf_hi(d.w);
    }
    wg_wait<0>();
    reg_fence(acc2[1]);
    TSC(20);
    consume(2);
    TSC(21);
    if (tid == 0) g_epoch[blockIdx.x] = epoch + 1;

    {
      unsigned char* stg = smem + OFF_DSLOT + wg * 8192 + w4 * 512;
#pragma unroll
      for (int i = 0; i < 8; i++) {
        const uint32_t bb = b2s[i * 4 + q];
        *reinterpret_cast<uint32_t*>(stg + (g >> 2) * 2048 + (g & 3) * 128 + ((i ^ g) << 4) + q * 4) =
            hadd2_bf(pack_bf16(acc2[1][4 * i] + sum[4 * i], acc2[1][4 * i + 1] + sum[4 * i + 1]), bb);
        *reinterpret_cast<uint32_t*>(stg + (2 + (g >> 2)) * 2048 + (g & 3) * 128 + ((i ^ g) << 4) + q * 4) =
            hadd2_bf(pack_bf16(acc2[1][4 * i + 2] + sum[4 * i + 2], acc2[1][4 * i + 3] + sum[4 * i + 3]), bb);
      }
      __syncwarp();
      const int row0 = mb * BM + wg * 64 + w4 * 16;
#pragma unroll
      for (int r = 0; r < 4; r++) {
        const int row = r * 4 + (lane >> 3);
        const uint4 v = *reinterpret_cast<const uint4*>(stg + r * 2048 + (lane >> 3) * 128 + (((lane & 7) ^ (row & 7)) << 4));
        *reinterpret_cast<uint4*>(out + (size_t)(row0 + row) * D_MOD + j * BN2 + (lane & 7) * 8) = v;
      }
    }
  }
}

typedef CUresult (*EncodeFn)(CUtensorMap*, CUtensorMapDataType, cuuint32_t, void*, const cuuint64_t*, const cuuint64_t*,
                             const cuuint32_t*, const cuuint32_t*, CUtensorMapInterleave, CUtensorMapSwizzle,
                             CUtensorMapL2promotion, CUtensorMapFloatOOBfill);

}

extern "C" void kernel_launch(void* const* d_in, const int* in_sizes, int n_in, void* d_out, int out_size) {
  (void)in_sizes; (void)n_in; (void)out_size;
  static CUtensorMap tm_x, tm_w1, tm_w2;
  static const void* cached_w1 = nullptr; static const void* cached_w2 = nullptr; static const void* cached_x = nullptr;
  const void* w1 = d_in[1]; const void* w2 = d_in[3]; const void* xp = d_in[0];
  if (cached_w1 != w1 || cached_w2 != w2 || cached_x != xp) {
    void* fn = nullptr; cudaDriverEntryPointQueryResult st;
    cudaGetDriverEntryPoint("cuTensorMapEncodeTiled", &fn, cudaEnableDefault, &st);
    EncodeFn enc = (EncodeFn)fn;
    {
      cuuint64_t dims[3] = {64, (cuuint64_t)S_TOK, (cuuint64_t)(D_MOD / 64)};
      cuuint64_t strides[2] = {(cuuint64_t)D_MOD * 2, 128};
      cuuint32_t box[3] = {64, 64, 2};
      cuuint32_t es[3] = {1, 1, 1};
      enc(&tm_x, CU_TENSOR_MAP_DATA_TYPE_BFLOAT16, 3, const_cast<void*>(xp), dims, strides, box, es,
          CU_TENSOR_MAP_INTERLEAVE_NONE, CU_TENSOR_MAP_SWIZZLE_128B, CU_TENSOR_MAP_L2_PROMOTION_L2_128B, CU_TENSOR_MAP_FLOAT_OOB_FILL_NONE);
    }
    {
      cuuint64_t dims[3] = {32, (cuuint64_t)D_MOD, (cuuint64_t)(F_HID / 32)};
      cuuint64_t strides[2] = {(cuuint64_t)F_HID * 2, 64};
      cuuint32_t box[3] = {32, 32, 7};
      cuuint32_t es[3] = {1, 1, 1};
      enc(&tm_w1, CU_TENSOR_MAP_DATA_TYPE_BFLOAT16, 3, const_cast<void*>(w1), dims, strides, box, es,
          CU_TENSOR_MAP_INTERLEAVE_NONE, CU_TENSOR_MAP_SWIZZLE_64B, CU_TENSOR_MAP_L2_PROMOTION_L2_128B, CU_TENSOR_MAP_FLOAT_OOB_FILL_NONE);
    }
    {
      cuuint64_t dims[2] = {(cuuint64_t)D_MOD, (cuuint64_t)F_HID};
      cuuint64_t strides[1] = {(cuuint64_t)D_MOD * 2};
      cuuint32_t box[2] = {64, 112};
      cuuint32_t es[2] = {1, 1};
      enc(&tm_w2, CU_TENSOR_MAP_DATA_TYPE_BFLOAT16, 2, const_cast<void*>(w2), dims, strides, box, es,
          CU_TENSOR_MAP_INTERLEAVE_NONE, CU_TENSOR_MAP_SWIZZLE_128B, CU_TENSOR_MAP_L2_PROMOTION_L2_128B, CU_TENSOR_MAP_FLOAT_OOB_FILL_NONE);
    }
    cudaFuncSetAttribute(fused_mlp_kernel, cudaFuncAttributeMaxDynamicSharedMemorySize, SMEM_TOTAL);
    cached_w1 = w1; cached_w2 = w2; cached_x = xp;
  }
  fused_mlp_kernel<<<NMB * NSPLIT, NTHREADS, SMEM_TOTAL>>>(tm_x, tm_w1, tm_w2,
      (const __nv_bfloat16*)d_in[2], (const __nv_bfloat16*)d_in[4], (__nv_bfloat16*)d_out);
}
```
